```python
import torch

def _softmax(x, axis=-1):
    return torch.softmax(x, dim=axis)
def _gelu(x):
    return torch.nn.functional.gelu(x, approximate="tanh")
def _silu(x):
    return torch.nn.functional.silu(x)
def _sigmoid(x):
    return torch.sigmoid(x)
def _layernorm(x, axis=-1, eps=1e-5):
    m = x.mean(dim=axis, keepdim=True)
    v = x.var(dim=axis, keepdim=True, unbiased=False)
    return (x - m) / torch.sqrt(v + eps)
def _scatter_add(tgt, idx, src, axis=0):
    return tgt.clone().index_add_(axis, idx, src)
def _segment_sum(src, seg, n):
    out = torch.zeros((n,) + src.shape[1:], dtype=src.dtype)
    return out.index_add_(0, seg, src)
def _pad(x, pw):
    flat = tuple(v for pair in reversed(pw) for v in pair)
    return torch.nn.functional.pad(x, flat)

kernel_name = 'standalone__normalfloat_lut_codebook_lookup__prompt'

def setup_inputs():

    _w = (lambda a: (lambda t: t.to(torch.bfloat16) if t.is_floating_point() else t)(torch.as_tensor(a)))
    B, S, D, F = 1, 2048, 1024, 3584
    G = 64 if 64 > 0 else D
    D = (D // G) * G
    ng = D // G
    nf4 = torch.tensor([
        -1.0, -0.6961928009986877, -0.5250730514526367, -0.39491748809814453,
        -0.28444138169288635, -0.18477343022823334, -0.09105003625154495, 0.0,
        0.07958029955625534, 0.16093020141124725, 0.24611230194568634, 0.33791524171829224,
        0.44070982933044434, 0.5626170039176941, 0.7229568362236023, 1.0
    ], dtype=float)
    qw = torch.randint(0, 16, (D, F)).to(torch.int64)
    absmax = (torch.abs((lambda *s: torch.randn(*s, dtype=torch.bfloat16) * 0.05)(ng, F)) + 0.01).to(float)
    return {
        "x": _w((lambda *s: torch.randn(*s, dtype=torch.bfloat16) * 0.05)(B, S, D)),
        "qw": _w(qw),
        "codebook": _w(nf4),
        "absmax": _w(absmax),
    }

def reference(x, qw, codebook, absmax):
    B, S, D = x.shape
    ng, F = absmax.shape
    G = D // ng
    w_nf = codebook[qw]
    s = (lambda x, n, axis: torch.repeat_interleave(x, n, dim=axis))(absmax, G, axis=0)
    w = (lambda x, dt: x.to(dt))(w_nf * s, x.dtype)
    return torch.einsum("bsd,df->bsf", x, w)
```

```cpp
#include <cuda_runtime.h>
#include <cuda_bf16.h>
#include <cuda.h>
#include <stdint.h>

constexpr int M_ = 2048, K_ = 1024, N_ = 3584;
constexpr int BM = 256, BN = 224;
constexpr int UNIT = 14336;
constexpr int NW = 6, NR = 3;
constexpr int RAW_OFF = 3 * 32768;
constexpr int SC_OFF = RAW_OFF + 2 * UNIT;
constexpr int W_OFF = 127 * 1024;
constexpr int RAW2_OFF = W_OFF + NW * UNIT;
constexpr int BAR_OFF = RAW2_OFF + UNIT;
__host__ __device__ constexpr int roff(int slot) { return slot < 2 ? slot * UNIT : RAW2_OFF - RAW_OFF; }
constexpr int SMEM_BYTES = BAR_OFF + 192;
#define TRAPSTR ""
#define DLEAD 6
#define PFQ 2
#define PFX 1
#define FT 38
#define TSP 2
#define LATE0 12
#define XLATE 1
#define STFIRST 0
#define RAWFIRST 0
#define F0 2
#define RAMP 4
#define C0 2
#define C1 11

#define GUEST 7
#define PFG 1
constexpr int NU = 26;
constexpr int SC_STRIDE = 464;
__device__ __align__(1024) uint8_t g_wimg[16 * 8 * UNIT];
__device__ __align__(128) unsigned g_flag[16 * 32];

#define TSL(i)
#define TL_DUMP()
#define TSW(w, i)
#define TS_INIT()
#define TS_DUMP()

__device__ __forceinline__ uint32_t smem_u32(const void* p) { return (uint32_t)__cvta_generic_to_shared(p); }
__device__ __forceinline__ bool elect() {
    uint32_t ok;
    asm volatile("{\n.reg .pred p;\nelect.sync _|p, 0xffffffff;\nselp.u32 %0, 1, 0, p;\n}\n" : "=r"(ok));
    return ok != 0;
}
__device__ __forceinline__ void mbar_init(uint32_t bar, uint32_t cnt) { asm volatile("mbarrier.init.shared::cta.b64 [%0], %1;" ::"r"(bar), "r"(cnt) : "memory"); }
__device__ __forceinline__ void mbar_expect_tx(uint32_t bar, uint32_t bytes) { asm volatile("mbarrier.arrive.expect_tx.shared::cta.b64 _, [%0], %1;" ::"r"(bar), "r"(bytes) : "memory"); }
__device__ __forceinline__ void mbar_arrive(uint32_t bar) { asm volatile("mbarrier.arrive.shared::cta.b64 _, [%0];" ::"r"(bar) : "memory"); }
__device__ __forceinline__ void mbar_arrive_cluster(uint32_t cbar) { asm volatile("mbarrier.arrive.shared::cluster.b64 _, [%0];" ::"r"(cbar) : "memory"); }
__device__ __forceinline__ void mbar_arrive_cluster_if(bool c, uint32_t cbar) {
    asm volatile("{\n.reg .pred p;\nsetp.ne.u32 p, %1, 0;\n@p mbarrier.arrive.shared::cluster.b64 _, [%0];\n}\n" ::"r"(cbar), "r"((uint32_t)c) : "memory");
}
__device__ __forceinline__ void mbar_wait(uint32_t bar, uint32_t parity) {
    asm volatile(
        "{\n.reg .pred p;\n.reg .u32 n;\n"
        "mbarrier.try_wait.parity.shared::cta.b64 p, [%0], %1;\n"
        "@p bra.uni LAB_DONE;\n"
        "mov.u32 n, 0;\n"
        "LAB_WAIT:\n"
        "mbarrier.try_wait.parity.shared::cta.b64 p, [%0], %1;\n"
        "@p bra.uni LAB_DONE;\n"
        "add.u32 n, n, 1;\n"
        "setp.lt.u32 p, n, 0x4000;\n"
        "@p bra.uni LAB_WAIT;\n"
        TRAPSTR
        "LAB_DONE:\n}\n" ::"r"(bar), "r"(parity) : "memory");
}
__device__ __forceinline__ bool mbar_try(uint32_t bar, uint32_t parity) {
    uint32_t ok;
    asm volatile("{\n.reg .pred p;\nmbarrier.test_wait.parity.shared::cta.b64 p, [%1], %2;\nselp.u32 %0, 1, 0, p;\n}\n" : "=r"(ok) : "r"(bar), "r"(parity) : "memory");
    return ok != 0;
}
__device__ __forceinline__ void mbar_wait1(uint32_t b0, uint32_t p0, bool skip) {
    asm volatile(
        "{\n.reg .pred p;\n.reg .u32 n;\n"
        "setp.ne.u32 p, %2, 0;\n@p bra.uni LAB_DONE;\n"
        "mov.u32 n, 0;\n"
        "LAB_WAIT:\n"
        "mbarrier.try_wait.parity.shared::cta.b64 p, [%0], %1;\n"
        "@p bra.uni LAB_DONE;\n"
        "add.u32 n, n, 1;\n"
        "setp.lt.u32 p, n, 0x4000;\n"
        "@p bra.uni LAB_WAIT;\n"
        TRAPSTR
        "LAB_DONE:\n}\n" ::"r"(b0), "r"(p0), "r"((uint32_t)skip) : "memory");
}
__device__ __forceinline__ void mbar_wait2(uint32_t b0, uint32_t p0, uint32_t b1, uint32_t p1, bool skip = false) {
    asm volatile(
        "{\n.reg .pred p, q;\n.reg .u32 n;\n"
        "setp.ne.u32 p, %4, 0;\n@p bra.uni LAB_DONE;\n"
        "mov.u32 n, 0;\n"
        "LAB_WAIT:\n"
        "mbarrier.try_wait.parity.shared::cta.b64 p, [%0], %1;\n"
        "mbarrier.try_wait.parity.shared::cta.b64 q, [%2], %3;\n"
        "and.pred p, p, q;\n"
        "@p bra.uni LAB_DONE;\n"
        "add.u32 n, n, 1;\n"
        "setp.lt.u32 p, n, 0x4000;\n"
        "@p bra.uni LAB_WAIT;\n"
        TRAPSTR
        "LAB_DONE:\n}\n" ::"r"(b0), "r"(p0), "r"(b1), "r"(p1), "r"((uint32_t)skip) : "memory");
}
__device__ __forceinline__ void mbar_wait3(uint32_t b0, uint32_t p0, uint32_t b1, uint32_t p1, uint32_t b2, uint32_t p2, bool skip = false) {
    asm volatile(
        "{\n.reg .pred p, q, r;\n.reg .u32 n;\n"
        "setp.ne.u32 p, %6, 0;\n@p bra.uni LAB_DONE;\n"
        "mov.u32 n, 0;\n"
        "LAB_WAIT:\n"
        "mbarrier.try_wait.parity.shared::cta.b64 p, [%0], %1;\n"
        "mbarrier.try_wait.parity.shared::cta.b64 q, [%2], %3;\n"
        "mbarrier.try_wait.parity.shared::cta.b64 r, [%4], %5;\n"
        "and.pred p, p, q;\n"
        "and.pred p, p, r;\n"
        "@p bra.uni LAB_DONE;\n"
        "add.u32 n, n, 1;\n"
        "setp.lt.u32 p, n, 0x4000;\n"
        "@p bra.uni LAB_WAIT;\n"
        TRAPSTR
        "LAB_DONE:\n}\n" ::"r"(b0), "r"(p0), "r"(b1), "r"(p1), "r"(b2), "r"(p2), "r"((uint32_t)skip) : "memory");
}
__device__ __forceinline__ void tma_load_2d(uint32_t dst, const CUtensorMap* tm, int c0, int c1, uint32_t bar) {
    asm volatile("cp.async.bulk.tensor.2d.shared::cluster.global.mbarrier::complete_tx::bytes [%0], [%1, {%2, %3}], [%4];"
                 ::"r"(dst), "l"(tm), "r"(c0), "r"(c1), "r"(bar) : "memory");
}
__device__ __forceinline__ void tma_load_4d(uint32_t dst, const CUtensorMap* tm, int c0, int c1, int c2, int c3, uint32_t bar) {
    asm volatile("cp.async.bulk.tensor.4d.shared::cluster.global.mbarrier::complete_tx::bytes [%0], [%1, {%2, %3, %4, %5}], [%6];"
                 ::"r"(dst), "l"(tm), "r"(c0), "r"(c1), "r"(c2), "r"(c3), "r"(bar) : "memory");
}
__device__ __forceinline__ void tma_load_5d(uint32_t dst, const CUtensorMap* tm, int c0, int c1, int c2, int c3, int c4, uint32_t bar) {
    asm volatile("cp.async.bulk.tensor.5d.shared::cluster.global.mbarrier::complete_tx::bytes [%0], [%1, {%2, %3, %4, %5, %6}], [%7];"
                 ::"r"(dst), "l"(tm), "r"(c0), "r"(c1), "r"(c2), "r"(c3), "r"(c4), "r"(bar) : "memory");
}
__device__ __forceinline__ void tma_prefetch_2d(const CUtensorMap* tm, int c0, int c1) {
    asm volatile("cp.async.bulk.prefetch.tensor.2d.L2.global [%0, {%1, %2}];" ::"l"(tm), "r"(c0), "r"(c1) : "memory");
}
__device__ __forceinline__ void bulk_load(uint32_t dst, const void* src, uint32_t bytes, uint32_t bar) {
    asm volatile("cp.async.bulk.shared::cluster.global.mbarrier::complete_tx::bytes [%0], [%1], %2, [%3];"
                 ::"r"(dst), "l"(src), "r"(bytes), "r"(bar) : "memory");
}
__device__ __forceinline__ void tma_store_3d(const CUtensorMap* tm, uint32_t src, int c0, int c1, int c2) {
    asm volatile("cp.async.bulk.tensor.3d.global.shared::cta.bulk_group [%0, {%2, %3, %4}], [%1];"
                 ::"l"(tm), "r"(src), "r"(c0), "r"(c1), "r"(c2) : "memory");
}
__device__ __forceinline__ void cluster_arrive() { asm volatile("barrier.cluster.arrive.relaxed.aligned;" ::: "memory"); }
__device__ __forceinline__ void cluster_wait() { asm volatile("barrier.cluster.wait.acquire.aligned;" ::: "memory"); }
__device__ __forceinline__ uint32_t mapa(uint32_t addr, uint32_t cta) {
    uint32_t r; asm("mapa.shared::cluster.u32 %0, %1, %2;" : "=r"(r) : "r"(addr), "r"(cta)); return r;
}
__device__ __forceinline__ void copy_to_peer(uint32_t cdst, uint32_t src, uint32_t bytes, uint32_t cbar) {
    asm volatile("cp.async.bulk.shared::cluster.shared::cta.mbarrier::complete_tx::bytes [%0], [%1], %2, [%3];"
                 ::"r"(cdst), "r"(src), "r"(bytes), "r"(cbar) : "memory");
}
__device__ __forceinline__ void wgmma_fence() { asm volatile("wgmma.fence.sync.aligned;" ::: "memory"); }
__device__ __forceinline__ void wgmma_commit() { asm volatile("wgmma.commit_group.sync.aligned;" ::: "memory"); }
template <int N> __device__ __forceinline__ void wgmma_wait() { asm volatile("wgmma.wait_group.sync.aligned %0;" ::"n"(N) : "memory"); }
__device__ __forceinline__ uint32_t pack_bf16(float lo, float hi) {
    uint32_t r; asm("cvt.rn.bf16x2.f32 %0, %1, %2;" : "=r"(r) : "f"(hi), "f"(lo)); return r;
}
__device__ __forceinline__ void stmatrix_x4(uint32_t addr, uint32_t a, uint32_t b, uint32_t c, uint32_t d) {
    asm volatile("stmatrix.sync.aligned.m8n8.x4.shared.b16 [%0], {%1, %2, %3, %4};" ::"r"(addr), "r"(a), "r"(b), "r"(c), "r"(d) : "memory");
}
__device__ __forceinline__ uint4 lds128(uint32_t a) {
    uint4 v; asm volatile("ld.shared.v4.b32 {%0, %1, %2, %3}, [%4];" : "=r"(v.x), "=r"(v.y), "=r"(v.z), "=r"(v.w) : "r"(a) : "memory"); return v;
}
__device__ __forceinline__ void sts128(uint32_t a, uint4 v) {
    asm volatile("st.shared.v4.b32 [%0], {%1, %2, %3, %4};" ::"r"(a), "r"(v.x), "r"(v.y), "r"(v.z), "r"(v.w) : "memory");
}
__device__ __forceinline__ void sts128x(uint32_t a, uint4 v) {
    asm volatile("st.shared.v4.b32 [%0], {%1, %2, %3, %4};" ::"r"(a), "r"(v.x), "r"(v.y), "r"(v.z), "r"(v.w) : "memory");
}
__device__ __forceinline__ uint4 ldg128(const void* p) {
    uint4 v; asm volatile("ld.global.nc.v4.b32 {%0, %1, %2, %3}, [%4];" : "=r"(v.x), "=r"(v.y), "=r"(v.z), "=r"(v.w) : "l"(p)); return v;
}
__device__ __forceinline__ uint32_t mul_bf16x2(uint32_t a, uint32_t b) { uint32_t r; asm("mul.rn.bf16x2 %0, %1, %2;" : "=r"(r) : "r"(a), "r"(b)); return r; }
struct Lut { uint32_t lo[4], hi[4]; };
__device__ __forceinline__ uint32_t prmt(uint32_t a, uint32_t b, uint32_t s) { uint32_t r; asm("prmt.b32 %0, %1, %2, %3;" : "=r"(r) : "r"(a), "r"(b), "r"(s)); return r; }
__device__ __forceinline__ uint32_t pack4(const uint4& q) {
    uint32_t ab, cd, p;
    asm volatile("mad.lo.u32 %0, %1, 16, %2;" : "=r"(ab) : "r"(q.y), "r"(q.x));
    asm volatile("mad.lo.u32 %0, %1, 16, %2;" : "=r"(cd) : "r"(q.w), "r"(q.z));
    asm volatile("mad.lo.u32 %0, %1, 256, %2;" : "=r"(p) : "r"(cd), "r"(ab));
    return p;
}
__device__ __forceinline__ void lookup4(uint32_t p, const Lut& t, uint32_t& w01, uint32_t& w23) {
    const uint32_t t8 = p & 0x8888u, s7 = p & 0x7777u;
    const uint32_t sel = (t8 >> 1) + 0x3210u;
    const uint32_t lo = prmt(prmt(t.lo[0], t.lo[1], p), prmt(t.lo[2], t.lo[3], s7), sel);
    const uint32_t hi = prmt(prmt(t.hi[0], t.hi[1], p), prmt(t.hi[2], t.hi[3], s7), sel);
    w01 = prmt(lo, hi, 0x5140);
    w23 = prmt(lo, hi, 0x7362);
}
__device__ __forceinline__ uint4 dequant8(uint32_t p0, uint32_t p1, const uint4& sc, const Lut& tu) {
    uint4 r;
    const Lut& t = tu;
    lookup4(p0, t, r.x, r.y);
    lookup4(p1, t, r.z, r.w);
    r.x = mul_bf16x2(r.x, sc.x); r.y = mul_bf16x2(r.y, sc.y); r.z = mul_bf16x2(r.z, sc.z); r.w = mul_bf16x2(r.w, sc.w);
    return r;
}
__device__ __forceinline__ void fence_async_smem() { asm volatile("fence.proxy.async.shared::cta;" ::: "memory"); }

template <int SCALE_D, int BHI>
__device__ __forceinline__ void wgmma224(float (&d)[112], uint32_t descA, uint32_t descB) {
    asm volatile(
        "{\n.reg .pred p;\n.reg .b64 da, db;\nsetp.ne.b32 p, %114, 0;\n"
        "mov.b64 da, {%112, 0x40000040};\nmov.b64 db, {%113, %115};\n"
        "wgmma.mma_async.sync.aligned.m64n224k16.f32.bf16.bf16 "
        "{%0, %1, %2, %3, %4, %5, %6, %7, %8, %9, %10, %11, %12, %13, %14, %15, "
        "%16, %17, %18, %19, %20, %21, %22, %23, %24, %25, %26, %27, %28, %29, %30, %31, "
        "%32, %33, %34, %35, %36, %37, %38, %39, %40, %41, %42, %43, %44, %45, %46, %47, "
        "%48, %49, %50, %51, %52, %53, %54, %55, %56, %57, %58, %59, %60, %61, %62, %63, "
        "%64, %65, %66, %67, %68, %69, %70, %71, %72, %73, %74, %75, %76, %77, %78, %79, "
        "%80, %81, %82, %83, %84, %85, %86, %87, %88, %89, %90, %91, %92, %93, %94, %95, "
        "%96, %97, %98, %99, %100, %101, %102, %103, %104, %105, %106, %107, %108, %109, %110, %111}, "
        "da, db, p, 1, 1, 0, 1;\n}\n"
        : "+f"(d[0]), "+f"(d[1]), "+f"(d[2]), "+f"(d[3]), "+f"(d[4]), "+f"(d[5]), "+f"(d[6]), "+f"(d[7]),
          "+f"(d[8]), "+f"(d[9]), "+f"(d[10]), "+f"(d[11]), "+f"(d[12]), "+f"(d[13]), "+f"(d[14]), "+f"(d[15]),
          "+f"(d[16]), "+f"(d[17]), "+f"(d[18]), "+f"(d[19]), "+f"(d[20]), "+f"(d[21]), "+f"(d[22]), "+f"(d[23]),
          "+f"(d[24]), "+f"(d[25]), "+f"(d[26]), "+f"(d[27]), "+f"(d[28]), "+f"(d[29]), "+f"(d[30]), "+f"(d[31]),
          "+f"(d[32]), "+f"(d[33]), "+f"(d[34]), "+f"(d[35]), "+f"(d[36]), "+f"(d[37]), "+f"(d[38]), "+f"(d[39]),
          "+f"(d[40]), "+f"(d[41]), "+f"(d[42]), "+f"(d[43]), "+f"(d[44]), "+f"(d[45]), "+f"(d[46]), "+f"(d[47]),
          "+f"(d[48]), "+f"(d[49]), "+f"(d[50]), "+f"(d[51]), "+f"(d[52]), "+f"(d[53]), "+f"(d[54]), "+f"(d[55]),
          "+f"(d[56]), "+f"(d[57]), "+f"(d[58]), "+f"(d[59]), "+f"(d[60]), "+f"(d[61]), "+f"(d[62]), "+f"(d[63]),
          "+f"(d[64]), "+f"(d[65]), "+f"(d[66]), "+f"(d[67]), "+f"(d[68]), "+f"(d[69]), "+f"(d[70]), "+f"(d[71]),
          "+f"(d[72]), "+f"(d[73]), "+f"(d[74]), "+f"(d[75]), "+f"(d[76]), "+f"(d[77]), "+f"(d[78]), "+f"(d[79]),
          "+f"(d[80]), "+f"(d[81]), "+f"(d[82]), "+f"(d[83]), "+f"(d[84]), "+f"(d[85]), "+f"(d[86]), "+f"(d[87]),
          "+f"(d[88]), "+f"(d[89]), "+f"(d[90]), "+f"(d[91]), "+f"(d[92]), "+f"(d[93]), "+f"(d[94]), "+f"(d[95]),
          "+f"(d[96]), "+f"(d[97]), "+f"(d[98]), "+f"(d[99]), "+f"(d[100]), "+f"(d[101]), "+f"(d[102]), "+f"(d[103]),
          "+f"(d[104]), "+f"(d[105]), "+f"(d[106]), "+f"(d[107]), "+f"(d[108]), "+f"(d[109]), "+f"(d[110]), "+f"(d[111])
        : "r"(descA), "r"(descB), "n"(SCALE_D), "n"(BHI));
}

template <int SCALE_D, int BHI>
__device__ __forceinline__ void wgmma128(float (&d)[64], uint32_t descA, uint32_t descB) {
    asm volatile(
        "{\n.reg .pred p;\n.reg .b64 da, db;\nsetp.ne.b32 p, %66, 0;\n"
        "mov.b64 da, {%64, 0x40000040};\nmov.b64 db, {%65, %67};\n"
        "wgmma.mma_async.sync.aligned.m64n128k16.f32.bf16.bf16 "
        "{%0, %1, %2, %3, %4, %5, %6, %7, %8, %9, %10, %11, %12, %13, %14, %15, "
        "%16, %17, %18, %19, %20, %21, %22, %23, %24, %25, %26, %27, %28, %29, %30, %31, "
        "%32, %33, %34, %35, %36, %37, %38, %39, %40, %41, %42, %43, %44, %45, %46, %47, "
        "%48, %49, %50, %51, %52, %53, %54, %55, %56, %57, %58, %59, %60, %61, %62, %63}, "
        "da, db, p, 1, 1, 0, 1;\n}\n"
        : "+f"(d[0]), "+f"(d[1]), "+f"(d[2]), "+f"(d[3]), "+f"(d[4]), "+f"(d[5]), "+f"(d[6]), "+f"(d[7]),
          "+f"(d[8]), "+f"(d[9]), "+f"(d[10]), "+f"(d[11]), "+f"(d[12]), "+f"(d[13]), "+f"(d[14]), "+f"(d[15]),
          "+f"(d[16]), "+f"(d[17]), "+f"(d[18]), "+f"(d[19]), "+f"(d[20]), "+f"(d[21]), "+f"(d[22]), "+f"(d[23]),
          "+f"(d[24]), "+f"(d[25]), "+f"(d[26]), "+f"(d[27]), "+f"(d[28]), "+f"(d[29]), "+f"(d[30]), "+f"(d[31]),
          "+f"(d[32]), "+f"(d[33]), "+f"(d[34]), "+f"(d[35]), "+f"(d[36]), "+f"(d[37]), "+f"(d[38]), "+f"(d[39]),
          "+f"(d[40]), "+f"(d[41]), "+f"(d[42]), "+f"(d[43]), "+f"(d[44]), "+f"(d[45]), "+f"(d[46]), "+f"(d[47]),
          "+f"(d[48]), "+f"(d[49]), "+f"(d[50]), "+f"(d[51]), "+f"(d[52]), "+f"(d[53]), "+f"(d[54]), "+f"(d[55]),
          "+f"(d[56]), "+f"(d[57]), "+f"(d[58]), "+f"(d[59]), "+f"(d[60]), "+f"(d[61]), "+f"(d[62]), "+f"(d[63])
        : "r"(descA), "r"(descB), "n"(SCALE_D), "n"(BHI));
}

template <int SCALE_D, int BHI>
__device__ __forceinline__ void wgmma96(float (&d)[48], uint32_t descA, uint32_t descB) {
    asm volatile(
        "{\n.reg .pred p;\n.reg .b64 da, db;\nsetp.ne.b32 p, %50, 0;\n"
        "mov.b64 da, {%48, 0x40000040};\nmov.b64 db, {%49, %51};\n"
        "wgmma.mma_async.sync.aligned.m64n96k16.f32.bf16.bf16 "
        "{%0, %1, %2, %3, %4, %5, %6, %7, %8, %9, %10, %11, %12, %13, %14, %15, "
        "%16, %17, %18, %19, %20, %21, %22, %23, %24, %25, %26, %27, %28, %29, %30, %31, "
        "%32, %33, %34, %35, %36, %37, %38, %39, %40, %41, %42, %43, %44, %45, %46, %47}, "
        "da, db, p, 1, 1, 0, 1;\n}\n"
        : "+f"(d[0]), "+f"(d[1]), "+f"(d[2]), "+f"(d[3]), "+f"(d[4]), "+f"(d[5]), "+f"(d[6]), "+f"(d[7]),
          "+f"(d[8]), "+f"(d[9]), "+f"(d[10]), "+f"(d[11]), "+f"(d[12]), "+f"(d[13]), "+f"(d[14]), "+f"(d[15]),
          "+f"(d[16]), "+f"(d[17]), "+f"(d[18]), "+f"(d[19]), "+f"(d[20]), "+f"(d[21]), "+f"(d[22]), "+f"(d[23]),
          "+f"(d[24]), "+f"(d[25]), "+f"(d[26]), "+f"(d[27]), "+f"(d[28]), "+f"(d[29]), "+f"(d[30]), "+f"(d[31]),
          "+f"(d[32]), "+f"(d[33]), "+f"(d[34]), "+f"(d[35]), "+f"(d[36]), "+f"(d[37]), "+f"(d[38]), "+f"(d[39]),
          "+f"(d[40]), "+f"(d[41]), "+f"(d[42]), "+f"(d[43]), "+f"(d[44]), "+f"(d[45]), "+f"(d[46]), "+f"(d[47])
        : "r"(descA), "r"(descB), "n"(SCALE_D), "n"(BHI));
}

__device__ __forceinline__ uint32_t opq(uint32_t v) { asm volatile("" : "+r"(v)); return v; }
template <int I> struct IC { static constexpr int value = I; };
template <int B, int E, class F> __device__ __forceinline__ void static_for(F&& f) {
    if constexpr (B < E) { f(IC<B>{}); static_for<B + 1, E>(f); }
}

__device__ __forceinline__ void tma_store_2d(const CUtensorMap* tm, uint32_t src, int c0, int c1) {
    asm volatile("cp.async.bulk.tensor.2d.global.shared::cta.bulk_group [%0, {%2, %3}], [%1];" ::"l"(tm), "r"(src), "r"(c0), "r"(c1) : "memory");
}
__device__ __forceinline__ void bulk_store(void* dst, uint32_t src, uint32_t bytes) {
    asm volatile("cp.async.bulk.global.shared::cta.bulk_group [%0], [%1], %2;" ::"l"(dst), "r"(src), "r"(bytes) : "memory");
}
__device__ __forceinline__ void bulk_commit() { asm volatile("cp.async.bulk.commit_group;" ::: "memory"); }
template <int N> __device__ __forceinline__ void bulk_wait_read() { asm volatile("cp.async.bulk.wait_group.read %0;" ::"n"(N) : "memory"); }
__device__ __forceinline__ void bar_arrive(int id) { asm volatile("bar.arrive %0, 256;" ::"r"(id) : "memory"); }
__device__ __forceinline__ void bar_sync(int id) { asm volatile("bar.sync %0, 256;" ::"r"(id) : "memory"); }
template <int NC, int OFF, int N>
__device__ __forceinline__ void store_cols(const float (&acc)[N], uint32_t stg, const CUtensorMap* tmo, int col, int row) {
    int lane; asm volatile("mov.u32 %0, %%laneid;" : "=r"(lane));
    const int r = lane & 15;
    const uint32_t a0 = NC == 64 ? stg + r * 128 + (((lane >> 4) ^ (r & 7)) << 4) : stg + r * 64 + (((lane >> 4) ^ ((r >> 1) & 3)) << 4);
#pragma unroll
    for (int j = 0; j < NC / 16; j++) {
        const int i = OFF + 8 * j;
        stmatrix_x4(a0 ^ (j * 32), pack_bf16(acc[i], acc[i + 1]), pack_bf16(acc[i + 2], acc[i + 3]), pack_bf16(acc[i + 4], acc[i + 5]), pack_bf16(acc[i + 6], acc[i + 7]));
    }
    fence_async_smem();
    __syncwarp();
    if (elect()) { tma_store_2d(tmo, stg, col, row); bulk_commit(); }
    __syncwarp();
}

__host__ __device__ constexpr int fconv(int s) {
    int a = F0 + RAMP * s / 4 + s, b = s + 6;
    a = a < b ? a : b;
    return a < 2 * NU ? a : 2 * NU;
}
__host__ __device__ constexpr int rslot(int u) { return (2 * u) % 3; }
__host__ __device__ constexpr int rpar(int u) { return (u / 3 - (u % 3 == 0)) & 1; }
__host__ __device__ constexpr int sslot(int c) { return c < 3 ? c + 2 : c % 3; }

__global__ void __cluster_dims__(2, 1, 1) __launch_bounds__(256, 1)
nf4_gemm_kernel(const int* __restrict__ qw, const __nv_bfloat16* __restrict__ cb, const __nv_bfloat16* __restrict__ absmax,
                uint8_t* __restrict__ wimg, unsigned* __restrict__ gflag,
                const __grid_constant__ CUtensorMap tmx, const __grid_constant__ CUtensorMap tmq, const __grid_constant__ CUtensorMap tmo64,
                const __grid_constant__ CUtensorMap tmo32, const __grid_constant__ CUtensorMap tmqp, const __grid_constant__ CUtensorMap tmx16) {
    extern __shared__ __align__(1024) uint8_t smem[];
    const uint32_t sbase = smem_u32(smem);
    const int rank = blockIdx.x & 1;
    const int mt = (blockIdx.x >> 5) * 2 + rank, nt = (blockIdx.x >> 1) & 15;
    const int lane = threadIdx.x & 31;
    uint4 q[4], sc, sc1, sc2, c0, c1;
    {
        const int w = (threadIdx.x >> 5) < 7 ? (threadIdx.x >> 5) : 6;
        const int col = nt * BN + w * 32 + (lane >> 3) * 8;
        const int* p = qw + (rank * 8 + (lane & 7)) * N_ + col;
        if (threadIdx.x < 224) {
            q[0] = ldg128(p); q[1] = ldg128(p + 4);
            sc = ldg128(absmax + col);
            c0 = ldg128(cb); c1 = ldg128(cb + 8);
            q[2] = ldg128(p + 16 * N_); q[3] = ldg128(p + 16 * N_ + 4);
            sc1 = ldg128(absmax + N_ + col);
            sc2 = ldg128(absmax + 2 * N_ + col);
        }
    }
    const int warp = __shfl_sync(~0u, (int)(threadIdx.x >> 5), 0);
    const int wg = warp >> 2;
    const uint32_t bars = sbase + BAR_OFF;
    const uint32_t fullW = bars, rawfull = bars + 48, written = bars + 72, xbar = bars + 96, gbar = bars + 112 + wg * 16;
    const uint32_t wbase = sbase + W_OFF;
    TS_INIT();
    __syncwarp();
    TSW(0, 0);

    const int pair = mt >> 1;
    auto chunk = [&](int i) { return i < GUEST ? i : i == GUEST ? 12 + pair : i <= 12 ? i - 1 : 12 + ((pair + i) & 3); };
    unsigned* flag = gflag + nt * 32;
    uint8_t* wpan = wimg + nt * 8 * UNIT;
    auto load_x4 = [&](int i, int slot, uint32_t bar) {
        const int k0 = chunk(i) * 64, k1 = i < 12 ? k0 : chunk(i + 1) * 64, r1 = i < 12 ? 64 : 0;
        tma_load_2d(sbase + slot * 32768, &tmx, k0, mt * BM, bar);
        tma_load_2d(sbase + slot * 32768 + 16384, &tmx, k0, mt * BM + 128, bar);
        tma_load_2d(sbase + slot * 32768 + 8192, &tmx, k1, mt * BM + r1, bar);
        tma_load_2d(sbase + slot * 32768 + 24576, &tmx, k1, mt * BM + 128 + r1, bar);
    };
    auto load_x = [&](int i, int slot, int ss) {
        const uint32_t bar = fullW + 16 * slot;
        load_x4(i, slot, bar);
        bulk_load(sbase + SC_OFF + ss * SC_STRIDE, absmax + chunk(i + 2) * N_ + nt * BN, 448, bar);
        bulk_load(sbase + SC_OFF + ss * SC_STRIDE + 448, flag, 16, bar);
    };
    auto load_raw = [&](int u, int slot) {
        mbar_expect_tx(rawfull + 8 * slot, UNIT);
        tma_load_5d(sbase + RAW_OFF + roff(slot), &tmq, 0, 0, nt * 7, rank, 4 * chunk(u >> 1) + 2 * (u & 1), rawfull + 8 * slot);
    };
    if (warp == 7) {
        if (elect()) {
            mbar_init(xbar, 1); mbar_init(xbar + 8, 1);
#pragma unroll
            for (int s = 0; s < NR; s++) mbar_init(rawfull + 8 * s, 1);
            fence_async_smem();
            mbar_expect_tx(xbar, 16384);
            tma_load_2d(sbase, &tmx, 0, mt * BM, xbar);
            tma_load_2d(sbase + 8192, &tmx, 0, mt * BM + 64, xbar);
            load_raw(1, rslot(1));
            mbar_expect_tx(xbar + 8, 16384 + 16);
            tma_load_2d(sbase + 16384, &tmx, 0, mt * BM + 128, xbar + 8);
            tma_load_2d(sbase + 24576, &tmx, 0, mt * BM + 192, xbar + 8);
            bulk_load(sbase + SC_OFF + sslot(1) * SC_STRIDE + 448, flag, 16, xbar + 8);
            load_raw(2, rslot(2));
#pragma unroll
            for (int s = 0; s < NW; s++) mbar_init(fullW + 8 * s, 1);
#pragma unroll
            for (int s = 0; s < NR; s++) mbar_init(written + 8 * s, 7);
#pragma unroll
            for (int s = 0; s < 4; s++) mbar_init(bars + 112 + 8 * s, 4);
            asm volatile("fence.mbarrier_init.release.cluster;" ::: "memory");
            fence_async_smem();
            if ((sbase & 0xffffff) != 0x400) __trap();
        }
        __syncwarp();
        cluster_arrive();
        if (elect()) {
            load_x(1, 1, sslot(3));
            load_raw(3, rslot(3));
            load_x(2, 2, sslot(4));
        }
        __syncwarp();
        TSW(7, 41);
        cluster_wait();
    } else {
        cluster_arrive();
    }
    const uint32_t rsrc = __shfl_sync(~0u, sbase + RAW_OFF + warp * 1024 + (lane & 7) * 128 + ((((lane >> 3) * 2) ^ (lane & 7)) << 4), lane);
    const uint32_t rsrc2 = __shfl_sync(~0u, rsrc ^ 16, lane);
    const uint32_t wl = __shfl_sync(~0u, (lane >> 3) * 256 + (lane & 7) * 16, lane);
    const uint32_t ssrc = sbase + SC_OFF + warp * 64;
    const uint32_t wown = wbase + rank * 7168 + warp * 1024;
    const uint32_t whalf = wbase + rank * 7168;
    const uint32_t pwhalf = mapa(whalf, rank ^ 1), pfullW = mapa(fullW, rank ^ 1);
    Lut lut;
    uint4 q0, q1;
    auto fetch = [&](int slot, int h) {
        q0 = lds128(rsrc + roff(slot) + h * 7168);
        q1 = lds128(rsrc2 + roff(slot) + h * 7168);
    };
    auto convert0 = [&](int rs, int ws, bool look, uint32_t lbar, uint32_t lpar, int tl = -1) {
        bool ok = true;
        if (look) ok = mbar_try(lbar, lpar);
        const uint32_t p0 = pack4(q0), p1 = pack4(q1);
        if (tl >= 0 && TSP == 0) TSL(3 * tl + 2);
        uint4 w = dequant8(p0, p1, sc, lut);
        asm volatile("" : "+r"(w.x), "+r"(w.y), "+r"(w.z), "+r"(w.w));
        if (tl >= 0 && TSP == 1) TSL(3 * tl + 2);
        if (look) mbar_wait1(lbar, lpar, ok);
        if (tl >= 0 && TSP == 2) TSL(3 * tl + 2);
        fetch(rs, 1);
        sts128x(wl + wown + ws * UNIT, w);
    };
    auto convert1 = [&](int rs, int ws, bool next, int rsn, int rpn, bool scales, int cs, bool stfirst, bool look, uint32_t lbar, uint32_t lpar, int tl = -1) {
        bool ok = true, ok2 = true;
        if (next) ok = mbar_try(rawfull + 8 * rsn, rpn);
        if (look) ok2 = mbar_try(lbar, lpar);
        const uint32_t p0 = pack4(q0), p1 = pack4(q1);
        if (tl >= 0 && TSP == 0) TSL(3 * tl + 2);
        uint4 w = dequant8(p0, p1, sc, lut);
        asm volatile("" : "+r"(w.x), "+r"(w.y), "+r"(w.z), "+r"(w.w));
        if (stfirst) {
            sts128x(wl + wown + ws * UNIT + 128, w);
            __syncwarp();
            if (elect()) mbar_arrive(written + 8 * rs);
            __syncwarp();
        }
        if (tl >= 0 && TSP == 1) TSL(3 * tl + 2);
        if (look) mbar_wait2(rawfull + 8 * rsn, rpn, lbar, lpar, ok && ok2);
        else if (next) mbar_wait1(rawfull + 8 * rsn, rpn, ok);
        if (tl >= 0 && TSP == 2) TSL(3 * tl + 2);
        if (next) fetch(rsn, 0);
        if (!stfirst) {
            sts128x(wl + wown + ws * UNIT + 128, w);
            __syncwarp();
            if (elect()) mbar_arrive(written + 8 * rs);
            __syncwarp();
        }
        if (scales) sc = lds128(((wl >> 4) & 0x30) + ssrc + cs * SC_STRIDE);
    };
    auto hand_over = [&](int v, int rs, uint32_t par, int ws, uint32_t tx, bool raw) {
        mbar_wait(written + 8 * rs, par);
        fence_async_smem();
        if (elect()) {
            if (raw) load_raw(v + NR, rs);
            copy_to_peer(pwhalf + ws * UNIT, whalf + ws * UNIT, 7168, pfullW + 8 * ws);
            mbar_expect_tx(fullW + 8 * ws, tx);
            if ((v >> 1) == GUEST) { bulk_store(wpan + (2 * pair + (v & 1)) * UNIT + rank * 7168, whalf + ws * UNIT, 7168); bulk_commit(); }
        }
        __syncwarp();
    };
    auto next_x = [&](bool ld, int i, int xs, int ss) {
        if (elect()) {
            if (ld) load_x(i, xs, ss);
            if (PFQ && i + PFQ < 12) tma_prefetch_2d(&tmqp, nt * BN, (i + PFQ) * 64 + pair * 16 + rank * 8);
            if (PFQ && (unsigned)(i - 2 - PFG) < 4) tma_prefetch_2d(&tmqp, nt * BN, (12 + pair) * 64 + (i - 2 - PFG) * 16 + rank * 8);
            if (PFX && i + PFX < 16) tma_prefetch_2d(&tmx16, chunk(i + PFX) * 64, mt * BM + nt * 16);
            if (i == GUEST + 2) {
                asm volatile("cp.async.bulk.wait_group 0;" ::: "memory");
                asm volatile("red.relaxed.gpu.global.add.u32 [%0], 1;" ::"l"(flag) : "memory");
            }
        }
        __syncwarp();
    };
    constexpr uint32_t TXO = 7168, TXE = 7168 + 32768 + SC_STRIDE;
    auto hand_over_c = [&](int v) { hand_over(v, rslot(v), (v / 3) & 1, v % NW, (v & 1) || v == 0 ? TXO : TXE, v >= 1 && v + NR < NU); };
    auto convert = [&](int b) {
        const int u = b >> 1;
        if (warp < 7) {
            if ((b & 1) == 0) convert0(rslot(u), u % NW, u >= NW, written + 8 * rslot(u - 2), ((u - 2) / 3) & 1);
            else convert1(rslot(u), u % NW, u + 1 < NU, rslot(u + 1), rpar(u + 1), (b & 3) == 3 && u + 1 < NU, sslot((b + 1) >> 2), b < LATE0 || STFIRST, false, 0, 0);
        } else if (b < LATE0) {
            if (b & 1) {
                hand_over_c(u);
                if (u & 1) next_x(u >= 5, (u + 1) >> 1, ((u + 1) >> 1) % 3, sslot(((u + 1) >> 1) + 2));
            }
        } else if ((b & 1) == 0) {
            if (b > LATE0) {
                hand_over_c(u - 1);
                if (!(u & 1)) next_x(u >= 6, u >> 1, (u >> 1) % 3, sslot((u >> 1) + 2));
            }
        }
    };
    if (warp < 7) {
        lut.lo[0] = __byte_perm(c0.x, c0.y, 0x6420); lut.hi[0] = __byte_perm(c0.x, c0.y, 0x7531);
        lut.lo[1] = __byte_perm(c0.z, c0.w, 0x6420); lut.hi[1] = __byte_perm(c0.z, c0.w, 0x7531);
        lut.lo[2] = __byte_perm(c1.x, c1.y, 0x6420); lut.hi[2] = __byte_perm(c1.x, c1.y, 0x7531);
        lut.lo[3] = __byte_perm(c1.z, c1.w, 0x6420); lut.hi[3] = __byte_perm(c1.z, c1.w, 0x7531);
        sts128(wl + wown, dequant8(pack4(q[0]), pack4(q[1]), sc, lut));
        TSW(0, 2);
        sts128(wl + wown + 128, dequant8(pack4(q[2]), pack4(q[3]), sc, lut));
        if ((lane & 7) == 0) { sts128(ssrc + (lane >> 3) * 16 + sslot(1) * SC_STRIDE, sc1); sts128(ssrc + (lane >> 3) * 16 + sslot(2) * SC_STRIDE, sc2); }
        TSW(0, 3);
        cluster_wait();
        TSW(0, 1);
        __syncwarp();
        if (elect()) mbar_arrive(written + 8 * rslot(0));
        __syncwarp();
        if (F0 > 2) { mbar_wait(rawfull + 8 * rslot(1), 0); fetch(rslot(1), 0); }
    }
    else hand_over_c(0);
#pragma unroll
    for (int b = 2; b < F0; b++) convert(b);

    float acc0[112], acc1[112];
    const uint32_t descA = ((0x400 + wg * 16384) >> 4) | (1u << 16);
    constexpr uint32_t descB = ((0x400 + W_OFF) >> 4) | ((7168u >> 4) << 16);
    auto mma = [&](int slot, int ks, int tl = -1) {
        const uint32_t da = opq(descA) + slot * (32768 >> 4) + ks * 2, db = descB + (2 * slot + (ks >> 1)) * (UNIT >> 4) + (ks & 1) * 8;
        if (tl >= 0) TSL(3 * tl);
        wgmma_fence();
        wgmma224<1, 16>(acc0, da, db); wgmma224<1, 16>(acc1, da + 512, db);
        wgmma_commit();
        wgmma_wait<2>();
        if (tl >= 0) TSL(3 * tl + 1);
    };
    auto slice = [&](auto S) {
        constexpr int s = S.value;
        constexpr int c = s >> 2, u = s >> 1;
        if (s == 0) mbar_wait2(xbar + 8 * wg, 0, fullW, 0);
        else if ((s & 1) == 0) mbar_wait(fullW + 8 * (u % NW), (u / NW) & 1);
        if (s == 0) { TSW(0, 4); TSW(4, 5); }
        if (s == 0) {
            wgmma_fence();
            wgmma224<0, 16>(acc0, descA, descB); wgmma224<0, 16>(acc1, descA + 512, descB);
            wgmma_commit();
            if (F0 == 2 && warp < 7) { mbar_wait(rawfull + 8 * rslot(1), 0); fetch(rslot(1), 0); }
        } else mma(c % 3, s & 3);
#pragma unroll
        for (int b = fconv(s); b < fconv(s + 1); b++) convert(b);
    };
    static_assert(fconv(4 * C0) == 4 * C0 + 6 && LATE0 <= 4 * C0 + 4, "ramp must be over");
    static_for<0, 4 * C0>(slice);
    {
        mbar_wait(fullW + 16 * (C0 % 3), (C0 / 3) & 1);
        uint32_t ph = (C0 / 3) & 1;
#pragma unroll 1
        for (int cb = C0; cb < C1; cb += 3)
          static_for<0, 3>([&](auto I) {
            constexpr int cc = C0 + I.value;
            constexpr int j0 = cc % 3, j1 = (cc + 1) % 3, j2 = (cc + 2) % 3;
            const int c = cb + I.value;
            mma(j0, 0, 4 * I.value + 0);
            if (warp < 7) convert0(j0, 2 * j1 + 1, true, written + 8 * j2, ((2 * cc + 1) / 3) & 1, 4 * I.value);
            else hand_over(2 * c + 2, j1, ((2 * cc + 2) / 3) & 1, 2 * j1, TXE, true);
            mma(j0, 1, 4 * I.value + 1);
            if (warp < 7) convert1(j0, 2 * j1 + 1, true, j2, rpar(2 * cc + 4), true, j2, STFIRST, true, fullW + 16 * j0 + 8, ph, 4 * I.value + 1);
            else mbar_wait(fullW + 16 * j0 + 8, ph);
            if (j1 == 0) asm volatile("xor.b32 %0, %0, 1;" : "+r"(ph));
            mma(j0, 2, 4 * I.value + 2);
            if (warp < 7) convert0(j2, 2 * j2, true, written + 8 * j1, ((2 * cc + 2) / 3) & 1, 4 * I.value + 2);
            else { hand_over(2 * c + 3, j0, ((2 * cc + 3) / 3) & 1, 2 * j1 + 1, TXO, 2 * c + 6 < NU); if (!XLATE) next_x(true, c + 2, j2, j1); }
            mma(j0, 3, 4 * I.value + 3);
            if (warp < 7) convert1(j2, 2 * j2, true, j1, rpar(2 * cc + 5), false, 0, STFIRST, true, fullW + 16 * j1, ph, 4 * I.value + 3);
            else { if (XLATE) next_x(true, c + 2, j2, j1); mbar_wait(fullW + 16 * j1, ph); }
          });
    }
    static_assert(C1 == 11 && GUEST + 2 <= 10, "");
    auto load_w = [&](int v, uint32_t dst, uint32_t bar, uint32_t more) {
        mbar_expect_tx(bar, UNIT + more);
        bulk_load(dst, wpan + (2 * (chunk(v >> 1) - 12) + (v & 1)) * UNIT, UNIT, bar);
    };
    mma(2, 0);
    convert(50);
    if (warp == 7) {
        unsigned f0, f1;
        asm volatile("ld.shared.u32 %0, [%1];" : "=r"(f0) : "r"(sbase + SC_OFF + sslot(1) * SC_STRIDE + 448) : "memory");
        asm volatile("ld.shared.u32 %0, [%1];" : "=r"(f1) : "r"(sbase + SC_OFF + sslot(13) * SC_STRIDE + 448) : "memory");
        f0 &= ~7u;
        for (int n = 0; f1 - f0 < 8 && n < 0x10000; n++) asm volatile("ld.relaxed.gpu.global.u32 %0, [%1];" : "=r"(f1) : "l"(flag) : "memory");
        TSW(7, 6);
        if (elect()) {
            load_w(26, sbase + RAW_OFF + roff(rslot(23)), rawfull + 8 * rslot(23), 0);
            load_w(27, sbase + RAW_OFF + roff(rslot(24)), rawfull + 8 * rslot(24), 0);
            load_w(28, wbase + 2 * UNIT, fullW + 16, 32768);
        }
        __syncwarp();
    }
    mma(2, 1);
    convert(51);
    if (warp == 7 && elect()) {
        asm volatile("prefetch.tensormap [%0];" ::"l"(&tmo64) : "memory");
        asm volatile("prefetch.tensormap [%0];" ::"l"(&tmo32) : "memory");
        asm volatile("prefetch.tensormap [%0];" ::"l"(&tmx16) : "memory");
    }
    __syncwarp();
    mbar_wait(fullW + 8 * 5, 1);
    if (wg == 1) {
        if (warp == 7) {
            hand_over_c(25);
            if (elect()) {
                load_x4(14, 1, fullW + 16);
                load_w(29, sbase + RAW_OFF + roff(rslot(25)), rawfull + 8 * rslot(25), 0);
                load_w(30, wbase + 3 * UNIT, fullW + 24, 0);
            }
            __syncwarp();
        }
        bar_sync(8);
    }
    mma(2, 2);
    mma(2, 3);
    if (wg == 0) bar_arrive(8);
    else if (warp == 7) {
        mbar_wait(fullW, 0);
        if (elect()) load_w(31, wbase + 4 * UNIT, fullW + 32, 0);
        __syncwarp();
    }
    wgmma_wait<0>();
    TSW(wg * 4, 8 + wg);
    float lo0[64], hi0[48], lo1[64], hi1[48];
#pragma unroll
    for (int i = 0; i < 64; i++) { asm volatile("mov.b32 %0, %1;" : "=f"(lo0[i]) : "f"(acc0[i])); asm volatile("mov.b32 %0, %1;" : "=f"(lo1[i]) : "f"(acc1[i])); }
#pragma unroll
    for (int i = 0; i < 48; i++) { asm volatile("mov.b32 %0, %1;" : "=f"(hi0[i]) : "f"(acc0[64 + i])); asm volatile("mov.b32 %0, %1;" : "=f"(hi1[i]) : "f"(acc1[64 + i])); }
    auto udesc = [](int v) {
        const int off = v == 26 ? RAW_OFF + roff(rslot(23)) : v == 27 ? RAW_OFF + roff(rslot(24)) : v == 29 ? RAW_OFF + roff(rslot(25))
                      : W_OFF + (v < 26 ? v - 24 : v == 28 ? 2 : v - 27) * UNIT;
        return (uint32_t)(((0x400 + off) >> 4) | ((7168u >> 4) << 16));
    };
    const uint32_t tA = opq(descA);
    auto tdesc = [&](int p) { return tA + (p >> 1) * (32768 >> 4) + (p & 1) * 512; };
    const uint32_t slice0 = sbase + wg * 16384 + (warp & 3) * 2048;
    auto slc = [&](int p) { return slice0 + (p >> 1) * 32768 + (p & 1) * 8192; };
    const int row0 = mt * BM + wg * 128 + (warp & 3) * 16, col0 = nt * BN;
    auto load_g = [&](int i, int p, uint32_t bar) {
        mbar_expect_tx(bar, 4096);
        tma_load_2d(slc(p), &tmx16, chunk(i) * 64, row0 + 64, bar);
        tma_load_2d(slc(p + 1), &tmx16, chunk(i + 1) * 64, row0 + 64, bar);
    };
    if (wg == 1) bar_sync(1);
    static_for<24, 32>([&](auto V) {
        constexpr int v = V.value;
        if (v == 24 || v == 25) mbar_wait(fullW + 8 * (v - 24), 0);
        else if (v == 26 || v == 27 || v == 29) mbar_wait(rawfull + 8 * rslot(v == 29 ? 25 : v - 3), rpar(v == 29 ? 28 : v));
        else mbar_wait(fullW + 8 * (v == 28 ? 2 : v - 27), 0);
        if (v == 31) TSW(wg * 4, 10 + wg);
        wgmma_fence();
        wgmma96<1, 16>(hi0, tdesc((v - 24) >> 1) + (v & 1) * 4, udesc(v) + 256);
        wgmma96<1, 16>(hi0, tdesc((v - 24) >> 1) + (v & 1) * 4 + 2, udesc(v) + 256 + 8);
    });
    wgmma_commit();
    bar_arrive(1 + wg);
    cluster_arrive();
    wgmma_wait<0>();
    TSW(wg * 4, 16 + wg);
    store_cols<64, 0>(hi0, slc(4), &tmo64, col0 + 128, row0);
    store_cols<32, 32>(hi0, slc(5), &tmo32, col0 + 192, row0);
    TSW(wg * 4, 18 + wg);
    bar_sync(2 + wg);
    wgmma_fence();
#pragma unroll
    for (int s = 0; s < 16; s++) wgmma128<1, 16>(lo0, tdesc(s >> 2) + (s & 3) * 2, udesc(24 + (s >> 1)) + (s & 1) * 8);
    wgmma_commit();
    bar_arrive(3 + wg);
    if (elect()) { bulk_wait_read<0>(); load_g(12, 4, gbar); }
    __syncwarp();
    wgmma_wait<0>();
    TSW(wg * 4, 20 + wg);
    if (elect()) load_g(14, 0, gbar + 8);
    __syncwarp();
    store_cols<64, 0>(lo0, slc(2), &tmo64, col0, row0);
    store_cols<64, 32>(lo0, slc(3), &tmo64, col0 + 64, row0);
    TSW(wg * 4, 22 + wg);
    mbar_wait(gbar, 0);
    bar_sync(4 + wg);
    wgmma_fence();
#pragma unroll
    for (int s = 0; s < 8; s++) wgmma128<1, 16>(lo1, tdesc(4 + (s >> 2)) + (s & 3) * 2, udesc(24 + (s >> 1)) + (s & 1) * 8);
    mbar_wait(gbar + 8, 0);
    wgmma_fence();
#pragma unroll
    for (int s = 8; s < 16; s++) wgmma128<1, 16>(lo1, tdesc((s >> 2) - 2) + (s & 3) * 2, udesc(24 + (s >> 1)) + (s & 1) * 8);
    wgmma_commit();
    bar_arrive(5 + wg);
    if (elect()) bulk_wait_read<0>();
    __syncwarp();
    wgmma_wait<0>();
    TSW(wg * 4, 24 + wg);
    store_cols<64, 0>(lo1, slc(2), &tmo64, col0, row0 + 64);
    store_cols<64, 32>(lo1, slc(3), &tmo64, col0 + 64, row0 + 64);
    TSW(wg * 4, 26 + wg);
    bar_sync(6 + wg);
    wgmma_fence();
#pragma unroll
    for (int s = 0; s < 16; s++) wgmma96<1, 16>(hi1, tdesc(((s >> 2) + 4) % 6) + (s & 3) * 2, udesc(24 + (s >> 1)) + (s & 1) * 8 + 256);
    wgmma_commit();
    if (wg == 0) bar_arrive(7);
    wgmma_wait<0>();
    TSW(wg * 4, 34 + wg);
    store_cols<64, 0>(hi1, slc(4), &tmo64, col0 + 128, row0 + 64);
    store_cols<32, 32>(hi1, slc(5), &tmo32, col0 + 192, row0 + 64);
    TSW(wg * 4, 36 + wg);
    if (elect()) bulk_wait_read<0>();
    __syncwarp();
    TSW(wg * 4, 38 + wg);
    TS_DUMP();
    TL_DUMP();
    cluster_wait();
}

typedef CUresult (*EncodeFn)(CUtensorMap*, CUtensorMapDataType, cuuint32_t, void*, const cuuint64_t*, const cuuint64_t*,
                             const cuuint32_t*, const cuuint32_t*, CUtensorMapInterleave, CUtensorMapSwizzle,
                             CUtensorMapL2promotion, CUtensorMapFloatOOBfill);

extern "C" void kernel_launch(void* const* d_in, const int* in_sizes, int n_in, void* d_out, int out_size) {
    const __nv_bfloat16* x = (const __nv_bfloat16*)d_in[0];
    const int* qw = (const int*)d_in[1];
    const __nv_bfloat16* cb = (const __nv_bfloat16*)d_in[2];
    const __nv_bfloat16* absmax = (const __nv_bfloat16*)d_in[3];
    static EncodeFn encode = nullptr;
    static void *wimg = nullptr, *gflag = nullptr;
    if (!encode) {
        cudaGetSymbolAddress(&wimg, g_wimg);
        cudaGetSymbolAddress(&gflag, g_flag);
        void* fn = nullptr;
        cudaDriverEntryPointQueryResult qr;
        cudaGetDriverEntryPoint("cuTensorMapEncodeTiled", &fn, cudaEnableDefault, &qr);
        encode = (EncodeFn)fn;
        cudaFuncSetAttribute(nf4_gemm_kernel, cudaFuncAttributeMaxDynamicSharedMemorySize, SMEM_BYTES);
    }
    CUtensorMap tmx, tmq, tmo64, tmo32, tmqp, tmx16;
    {
        cuuint64_t dims[2] = {(cuuint64_t)K_, (cuuint64_t)M_};
        cuuint64_t strides[1] = {(cuuint64_t)K_ * 2};
        cuuint32_t box[2] = {64, 64};
        cuuint32_t es[2] = {1, 1};
        encode(&tmx, CU_TENSOR_MAP_DATA_TYPE_BFLOAT16, 2, (void*)x, dims, strides, box, es, CU_TENSOR_MAP_INTERLEAVE_NONE,
               CU_TENSOR_MAP_SWIZZLE_128B, CU_TENSOR_MAP_L2_PROMOTION_L2_128B, CU_TENSOR_MAP_FLOAT_OOB_FILL_NONE);
        box[1] = 16;
        encode(&tmx16, CU_TENSOR_MAP_DATA_TYPE_BFLOAT16, 2, (void*)x, dims, strides, box, es, CU_TENSOR_MAP_INTERLEAVE_NONE,
               CU_TENSOR_MAP_SWIZZLE_128B, CU_TENSOR_MAP_L2_PROMOTION_L2_128B, CU_TENSOR_MAP_FLOAT_OOB_FILL_NONE);
    }
    {
        cuuint64_t dims[5] = {32, 8, (cuuint64_t)(N_ / 32), 2, (cuuint64_t)(K_ / 16)};
        cuuint64_t strides[4] = {(cuuint64_t)N_ * 4, 128, (cuuint64_t)N_ * 4 * 8, (cuuint64_t)N_ * 4 * 16};
        cuuint32_t box[5] = {32, 8, 7, 1, 2};
        cuuint32_t es[5] = {1, 1, 1, 1, 1};
        encode(&tmq, CU_TENSOR_MAP_DATA_TYPE_INT32, 5, (void*)qw, dims, strides, box, es, CU_TENSOR_MAP_INTERLEAVE_NONE,
               CU_TENSOR_MAP_SWIZZLE_128B, CU_TENSOR_MAP_L2_PROMOTION_L2_128B, CU_TENSOR_MAP_FLOAT_OOB_FILL_NONE);
        cuuint64_t dims2[2] = {(cuuint64_t)N_, (cuuint64_t)K_};
        cuuint32_t box2[2] = {224, 8};
        encode(&tmqp, CU_TENSOR_MAP_DATA_TYPE_INT32, 2, (void*)qw, dims2, strides, box2, es, CU_TENSOR_MAP_INTERLEAVE_NONE,
               CU_TENSOR_MAP_SWIZZLE_NONE, CU_TENSOR_MAP_L2_PROMOTION_L2_128B, CU_TENSOR_MAP_FLOAT_OOB_FILL_NONE);
    }
    {
        cuuint64_t dims[2] = {(cuuint64_t)N_, (cuuint64_t)M_};
        cuuint64_t strides[1] = {(cuuint64_t)N_ * 2};
        cuuint32_t box[2] = {64, 16};
        cuuint32_t es[2] = {1, 1};
        encode(&tmo64, CU_TENSOR_MAP_DATA_TYPE_BFLOAT16, 2, d_out, dims, strides, box, es, CU_TENSOR_MAP_INTERLEAVE_NONE,
               CU_TENSOR_MAP_SWIZZLE_128B, CU_TENSOR_MAP_L2_PROMOTION_NONE, CU_TENSOR_MAP_FLOAT_OOB_FILL_NONE);
        box[0] = 32;
        encode(&tmo32, CU_TENSOR_MAP_DATA_TYPE_BFLOAT16, 2, d_out, dims, strides, box, es, CU_TENSOR_MAP_INTERLEAVE_NONE,
               CU_TENSOR_MAP_SWIZZLE_64B, CU_TENSOR_MAP_L2_PROMOTION_NONE, CU_TENSOR_MAP_FLOAT_OOB_FILL_NONE);
    }
    nf4_gemm_kernel<<<128, 256, SMEM_BYTES>>>(qw, cb, absmax, (uint8_t*)wimg, (unsigned*)gflag, tmx, tmq, tmo64, tmo32, tmqp, tmx16);
}
```

```cpp
#include <cuda_runtime.h>
#include <cuda_bf16.h>
#include <cuda.h>
#include <stdint.h>

constexpr int M_ = 2048, K_ = 1024, N_ = 3584;
constexpr int BM = 256, BN = 224;
constexpr int UNIT = 14336;
constexpr int NW = 6, NR = 3;
constexpr int RAW_OFF = 3 * 32768;
constexpr int SC_OFF = RAW_OFF + 2 * UNIT;
constexpr int W_OFF = 127 * 1024;
constexpr int RAW2_OFF = W_OFF + NW * UNIT;
constexpr int BAR_OFF = RAW2_OFF + UNIT;
__host__ __device__ constexpr int roff(int slot) { return slot < 2 ? slot * UNIT : RAW2_OFF - RAW_OFF; }
constexpr int SMEM_BYTES = BAR_OFF + 320;
#define TRAPSTR ""
#define DLEAD 6
#define PFQ 4
#define PFX 3
#define FT 38
#define TSP 2
#define LATE0 12
#define XLATE 1
#define STFIRST 0
#define RAWFIRST 0
#define F0 2
#define RAMP 4
#define C0 2
#define C1 11

#define SPL1 8
#define SPL3 8
#define E1 1
#define E2 1
#define PUBD 1
#define G1 7
#define G3 9
#define E3 0
#define E0 2
#define TLPRO -1
#define LEAD0 0x4345556666666666ull
#define LEAD1 LEAD0
#define HM1 1
#define HM2 4
#define HM3 4
#define PB 5
#define T2 1000
#define T3 1800
#define X2AT 1
#define XLAG 0
#define T2B 1400
#define G2S 0
#define PM 0
#define DEF 4
#define TB 4
#define ORD1 2
#define GS 0
#define GL 0
#define GR 1
#define GUEST 7
#define PFG 1
constexpr int NU = 26;
constexpr int SC_STRIDE = 464;
__device__ __align__(1024) uint8_t g_wimg[16 * 8 * UNIT];
__device__ __align__(128) unsigned g_flag[16 * 32];

#define TSL(i)
#define TL_DUMP()
#define TSW(w, i)
#define TS_INIT()
#define TS_DUMP()

#define TSX(w, i)
__device__ __forceinline__ uint32_t smem_u32(const void* p) { return (uint32_t)__cvta_generic_to_shared(p); }
__device__ __forceinline__ bool elect() {
    uint32_t ok;
    asm volatile("{\n.reg .pred p;\nelect.sync _|p, 0xffffffff;\nselp.u32 %0, 1, 0, p;\n}\n" : "=r"(ok));
    return ok != 0;
}
__device__ __forceinline__ void mbar_init(uint32_t bar, uint32_t cnt) { asm volatile("mbarrier.init.shared::cta.b64 [%0], %1;" ::"r"(bar), "r"(cnt) : "memory"); }
__device__ __forceinline__ void mbar_expect_tx(uint32_t bar, uint32_t bytes) { asm volatile("mbarrier.arrive.expect_tx.shared::cta.b64 _, [%0], %1;" ::"r"(bar), "r"(bytes) : "memory"); }
__device__ __forceinline__ void mbar_arrive(uint32_t bar) { asm volatile("mbarrier.arrive.shared::cta.b64 _, [%0];" ::"r"(bar) : "memory"); }
__device__ __forceinline__ void mbar_arrive_cluster(uint32_t cbar) { asm volatile("mbarrier.arrive.shared::cluster.b64 _, [%0];" ::"r"(cbar) : "memory"); }
__device__ __forceinline__ void mbar_arrive_cluster_if(bool c, uint32_t cbar) {
    asm volatile("{\n.reg .pred p;\nsetp.ne.u32 p, %1, 0;\n@p mbarrier.arrive.shared::cluster.b64 _, [%0];\n}\n" ::"r"(cbar), "r"((uint32_t)c) : "memory");
}
#define BOUNDED
#define WAIT_INIT "mov.u32 n, 0;\n"
#define WAIT_NEXT "@p bra.uni LAB_DONE;\nadd.u32 n, n, 1;\nsetp.lt.u32 p, n, 0x4000;\n@p bra.uni LAB_WAIT;\n"
__device__ __forceinline__ void mbar_wait(uint32_t bar, uint32_t parity) {
    asm volatile(
        "{\n.reg .pred p;\n.reg .u32 n;\n"
        WAIT_INIT
        "LAB_WAIT:\n"
        "mbarrier.try_wait.parity.shared::cta.b64 p, [%0], %1;\n"
        WAIT_NEXT
        "LAB_DONE:\n}\n" ::"r"(bar), "r"(parity) : "memory");
}
__device__ __forceinline__ bool mbar_try(uint32_t bar, uint32_t parity) {
    uint32_t ok;
    asm volatile("{\n.reg .pred p;\nmbarrier.test_wait.parity.shared::cta.b64 p, [%1], %2;\nselp.u32 %0, 1, 0, p;\n}\n" : "=r"(ok) : "r"(bar), "r"(parity) : "memory");
    return ok != 0;
}
__device__ __forceinline__ void mbar_wait1(uint32_t b0, uint32_t p0, bool skip) {
    asm volatile(
        "{\n.reg .pred p;\n.reg .u32 n;\n"
        "setp.ne.u32 p, %2, 0;\n@p bra.uni LAB_DONE;\n"
        WAIT_INIT
        "LAB_WAIT:\n"
        "mbarrier.try_wait.parity.shared::cta.b64 p, [%0], %1;\n"
        WAIT_NEXT
        "LAB_DONE:\n}\n" ::"r"(b0), "r"(p0), "r"((uint32_t)skip) : "memory");
}
__device__ __forceinline__ void mbar_wait2(uint32_t b0, uint32_t p0, uint32_t b1, uint32_t p1, bool skip = false) {
    asm volatile(
        "{\n.reg .pred p, q;\n.reg .u32 n;\n"
        "setp.ne.u32 p, %4, 0;\n@p bra.uni LAB_DONE;\n"
        WAIT_INIT
        "LAB_WAIT:\n"
        "mbarrier.try_wait.parity.shared::cta.b64 p, [%0], %1;\n"
        "mbarrier.try_wait.parity.shared::cta.b64 q, [%2], %3;\n"
        "and.pred p, p, q;\n"
        WAIT_NEXT
        "LAB_DONE:\n}\n" ::"r"(b0), "r"(p0), "r"(b1), "r"(p1), "r"((uint32_t)skip) : "memory");
}
__device__ __forceinline__ void mbar_wait3(uint32_t b0, uint32_t p0, uint32_t b1, uint32_t p1, uint32_t b2, uint32_t p2, bool skip = false) {
    asm volatile(
        "{\n.reg .pred p, q, r;\n.reg .u32 n;\n"
        "setp.ne.u32 p, %6, 0;\n@p bra.uni LAB_DONE;\n"
        WAIT_INIT
        "LAB_WAIT:\n"
        "mbarrier.try_wait.parity.shared::cta.b64 p, [%0], %1;\n"
        "mbarrier.try_wait.parity.shared::cta.b64 q, [%2], %3;\n"
        "mbarrier.try_wait.parity.shared::cta.b64 r, [%4], %5;\n"
        "and.pred p, p, q;\n"
        "and.pred p, p, r;\n"
        WAIT_NEXT
        "LAB_DONE:\n}\n" ::"r"(b0), "r"(p0), "r"(b1), "r"(p1), "r"(b2), "r"(p2), "r"((uint32_t)skip) : "memory");
}
__device__ __forceinline__ void tma_load_2d(uint32_t dst, const CUtensorMap* tm, int c0, int c1, uint32_t bar) {
    asm volatile("cp.async.bulk.tensor.2d.shared::cluster.global.mbarrier::complete_tx::bytes [%0], [%1, {%2, %3}], [%4];"
                 ::"r"(dst), "l"(tm), "r"(c0), "r"(c1), "r"(bar) : "memory");
}
__device__ __forceinline__ void tma_load_4d(uint32_t dst, const CUtensorMap* tm, int c0, int c1, int c2, int c3, uint32_t bar) {
    asm volatile("cp.async.bulk.tensor.4d.shared::cluster.global.mbarrier::complete_tx::bytes [%0], [%1, {%2, %3, %4, %5}], [%6];"
                 ::"r"(dst), "l"(tm), "r"(c0), "r"(c1), "r"(c2), "r"(c3), "r"(bar) : "memory");
}
__device__ __forceinline__ void tma_load_5d(uint32_t dst, const CUtensorMap* tm, int c0, int c1, int c2, int c3, int c4, uint32_t bar) {
    asm volatile("cp.async.bulk.tensor.5d.shared::cluster.global.mbarrier::complete_tx::bytes [%0], [%1, {%2, %3, %4, %5, %6}], [%7];"
                 ::"r"(dst), "l"(tm), "r"(c0), "r"(c1), "r"(c2), "r"(c3), "r"(c4), "r"(bar) : "memory");
}
__device__ __forceinline__ void tma_prefetch_2d(const CUtensorMap* tm, int c0, int c1) {
    asm volatile("cp.async.bulk.prefetch.tensor.2d.L2.global [%0, {%1, %2}];" ::"l"(tm), "r"(c0), "r"(c1) : "memory");
}
__device__ __forceinline__ void bulk_load(uint32_t dst, const void* src, uint32_t bytes, uint32_t bar) {
    asm volatile("cp.async.bulk.shared::cluster.global.mbarrier::complete_tx::bytes [%0], [%1], %2, [%3];"
                 ::"r"(dst), "l"(src), "r"(bytes), "r"(bar) : "memory");
}
__device__ __forceinline__ void tma_store_3d(const CUtensorMap* tm, uint32_t src, int c0, int c1, int c2) {
    asm volatile("cp.async.bulk.tensor.3d.global.shared::cta.bulk_group [%0, {%2, %3, %4}], [%1];"
                 ::"l"(tm), "r"(src), "r"(c0), "r"(c1), "r"(c2) : "memory");
}
__device__ __forceinline__ void cluster_arrive() { asm volatile("barrier.cluster.arrive.relaxed.aligned;" ::: "memory"); }
__device__ __forceinline__ void cluster_wait() { asm volatile("barrier.cluster.wait.acquire.aligned;" ::: "memory"); }
__device__ __forceinline__ uint32_t mapa(uint32_t addr, uint32_t cta) {
    uint32_t r; asm("mapa.shared::cluster.u32 %0, %1, %2;" : "=r"(r) : "r"(addr), "r"(cta)); return r;
}
__device__ __forceinline__ void copy_to_peer(uint32_t cdst, uint32_t src, uint32_t bytes, uint32_t cbar) {
    asm volatile("cp.async.bulk.shared::cluster.shared::cta.mbarrier::complete_tx::bytes [%0], [%1], %2, [%3];"
                 ::"r"(cdst), "r"(src), "r"(bytes), "r"(cbar) : "memory");
}
__device__ __forceinline__ void wgmma_fence() { asm volatile("wgmma.fence.sync.aligned;" ::: "memory"); }
__device__ __forceinline__ void wgmma_commit() { asm volatile("wgmma.commit_group.sync.aligned;" ::: "memory"); }
template <int N> __device__ __forceinline__ void wgmma_wait() { asm volatile("wgmma.wait_group.sync.aligned %0;" ::"n"(N) : "memory"); }
__device__ __forceinline__ uint32_t pack_bf16(float lo, float hi) {
    uint32_t r; asm("cvt.rn.bf16x2.f32 %0, %1, %2;" : "=r"(r) : "f"(hi), "f"(lo)); return r;
}
__device__ __forceinline__ void stmatrix_x4(uint32_t addr, uint32_t a, uint32_t b, uint32_t c, uint32_t d) {
    asm volatile("stmatrix.sync.aligned.m8n8.x4.shared.b16 [%0], {%1, %2, %3, %4};" ::"r"(addr), "r"(a), "r"(b), "r"(c), "r"(d) : "memory");
}
__device__ __forceinline__ uint4 lds128(uint32_t a) {
    uint4 v; asm volatile("ld.shared.v4.b32 {%0, %1, %2, %3}, [%4];" : "=r"(v.x), "=r"(v.y), "=r"(v.z), "=r"(v.w) : "r"(a) : "memory"); return v;
}
__device__ __forceinline__ void sts128(uint32_t a, uint4 v) {
    asm volatile("st.shared.v4.b32 [%0], {%1, %2, %3, %4};" ::"r"(a), "r"(v.x), "r"(v.y), "r"(v.z), "r"(v.w) : "memory");
}
__device__ __forceinline__ void sts128x(uint32_t a, uint4 v) {
    asm volatile("st.shared.v4.b32 [%0], {%1, %2, %3, %4};" ::"r"(a), "r"(v.x), "r"(v.y), "r"(v.z), "r"(v.w) : "memory");
}
__device__ __forceinline__ uint4 ldg128(const void* p) {
    uint4 v; asm volatile("ld.global.nc.v4.b32 {%0, %1, %2, %3}, [%4];" : "=r"(v.x), "=r"(v.y), "=r"(v.z), "=r"(v.w) : "l"(p) : "memory"); return v;
}
__device__ __forceinline__ unsigned clk() { unsigned c; asm volatile("mov.u32 %0, %%clock;" : "=r"(c) :: "memory"); return c; }
__device__ __forceinline__ uint32_t mul_bf16x2(uint32_t a, uint32_t b) { uint32_t r; asm("mul.rn.bf16x2 %0, %1, %2;" : "=r"(r) : "r"(a), "r"(b)); return r; }
struct Lut { uint32_t lo[4], hi[4]; };
__device__ __forceinline__ uint32_t prmt(uint32_t a, uint32_t b, uint32_t s) { uint32_t r; asm("prmt.b32 %0, %1, %2, %3;" : "=r"(r) : "r"(a), "r"(b), "r"(s)); return r; }
__device__ __forceinline__ uint32_t pack4(const uint4& q) {
    uint32_t ab, cd, p;
    asm volatile("mad.lo.u32 %0, %1, 16, %2;" : "=r"(ab) : "r"(q.y), "r"(q.x));
    asm volatile("mad.lo.u32 %0, %1, 16, %2;" : "=r"(cd) : "r"(q.w), "r"(q.z));
    asm volatile("mad.lo.u32 %0, %1, 256, %2;" : "=r"(p) : "r"(cd), "r"(ab));
    return p;
}
__device__ __forceinline__ void lookup4(uint32_t p, const Lut& t, uint32_t& w01, uint32_t& w23) {
    const uint32_t t8 = p & 0x8888u, s7 = p & 0x7777u;
    const uint32_t sel = (t8 >> 1) + 0x3210u;
    const uint32_t lo = prmt(prmt(t.lo[0], t.lo[1], p), prmt(t.lo[2], t.lo[3], s7), sel);
    const uint32_t hi = prmt(prmt(t.hi[0], t.hi[1], p), prmt(t.hi[2], t.hi[3], s7), sel);
    w01 = prmt(lo, hi, 0x5140);
    w23 = prmt(lo, hi, 0x7362);
}
__device__ __forceinline__ uint4 dequant8(uint32_t p0, uint32_t p1, const uint4& sc, const Lut& tu) {
    uint4 r;
    const Lut& t = tu;
    lookup4(p0, t, r.x, r.y);
    lookup4(p1, t, r.z, r.w);
    r.x = mul_bf16x2(r.x, sc.x); r.y = mul_bf16x2(r.y, sc.y); r.z = mul_bf16x2(r.z, sc.z); r.w = mul_bf16x2(r.w, sc.w);
    return r;
}
__device__ __forceinline__ void fence_async_smem() { asm volatile("fence.proxy.async.shared::cta;" ::: "memory"); }

template <int SCALE_D, int BHI>
__device__ __forceinline__ void wgmma224(float (&d)[112], uint32_t descA, uint32_t descB) {
    asm volatile(
        "{\n.reg .pred p;\n.reg .b64 da, db;\nsetp.ne.b32 p, %114, 0;\n"
        "mov.b64 da, {%112, 0x40000040};\nmov.b64 db, {%113, %115};\n"
        "wgmma.mma_async.sync.aligned.m64n224k16.f32.bf16.bf16 "
        "{%0, %1, %2, %3, %4, %5, %6, %7, %8, %9, %10, %11, %12, %13, %14, %15, "
        "%16, %17, %18, %19, %20, %21, %22, %23, %24, %25, %26, %27, %28, %29, %30, %31, "
        "%32, %33, %34, %35, %36, %37, %38, %39, %40, %41, %42, %43, %44, %45, %46, %47, "
        "%48, %49, %50, %51, %52, %53, %54, %55, %56, %57, %58, %59, %60, %61, %62, %63, "
        "%64, %65, %66, %67, %68, %69, %70, %71, %72, %73, %74, %75, %76, %77, %78, %79, "
        "%80, %81, %82, %83, %84, %85, %86, %87, %88, %89, %90, %91, %92, %93, %94, %95, "
        "%96, %97, %98, %99, %100, %101, %102, %103, %104, %105, %106, %107, %108, %109, %110, %111}, "
        "da, db, p, 1, 1, 0, 1;\n}\n"
        : "+f"(d[0]), "+f"(d[1]), "+f"(d[2]), "+f"(d[3]), "+f"(d[4]), "+f"(d[5]), "+f"(d[6]), "+f"(d[7]),
          "+f"(d[8]), "+f"(d[9]), "+f"(d[10]), "+f"(d[11]), "+f"(d[12]), "+f"(d[13]), "+f"(d[14]), "+f"(d[15]),
          "+f"(d[16]), "+f"(d[17]), "+f"(d[18]), "+f"(d[19]), "+f"(d[20]), "+f"(d[21]), "+f"(d[22]), "+f"(d[23]),
          "+f"(d[24]), "+f"(d[25]), "+f"(d[26]), "+f"(d[27]), "+f"(d[28]), "+f"(d[29]), "+f"(d[30]), "+f"(d[31]),
          "+f"(d[32]), "+f"(d[33]), "+f"(d[34]), "+f"(d[35]), "+f"(d[36]), "+f"(d[37]), "+f"(d[38]), "+f"(d[39]),
          "+f"(d[40]), "+f"(d[41]), "+f"(d[42]), "+f"(d[43]), "+f"(d[44]), "+f"(d[45]), "+f"(d[46]), "+f"(d[47]),
          "+f"(d[48]), "+f"(d[49]), "+f"(d[50]), "+f"(d[51]), "+f"(d[52]), "+f"(d[53]), "+f"(d[54]), "+f"(d[55]),
          "+f"(d[56]), "+f"(d[57]), "+f"(d[58]), "+f"(d[59]), "+f"(d[60]), "+f"(d[61]), "+f"(d[62]), "+f"(d[63]),
          "+f"(d[64]), "+f"(d[65]), "+f"(d[66]), "+f"(d[67]), "+f"(d[68]), "+f"(d[69]), "+f"(d[70]), "+f"(d[71]),
          "+f"(d[72]), "+f"(d[73]), "+f"(d[74]), "+f"(d[75]), "+f"(d[76]), "+f"(d[77]), "+f"(d[78]), "+f"(d[79]),
          "+f"(d[80]), "+f"(d[81]), "+f"(d[82]), "+f"(d[83]), "+f"(d[84]), "+f"(d[85]), "+f"(d[86]), "+f"(d[87]),
          "+f"(d[88]), "+f"(d[89]), "+f"(d[90]), "+f"(d[91]), "+f"(d[92]), "+f"(d[93]), "+f"(d[94]), "+f"(d[95]),
          "+f"(d[96]), "+f"(d[97]), "+f"(d[98]), "+f"(d[99]), "+f"(d[100]), "+f"(d[101]), "+f"(d[102]), "+f"(d[103]),
          "+f"(d[104]), "+f"(d[105]), "+f"(d[106]), "+f"(d[107]), "+f"(d[108]), "+f"(d[109]), "+f"(d[110]), "+f"(d[111])
        : "r"(descA), "r"(descB), "n"(SCALE_D), "n"(BHI));
}

template <int SCALE_D, int BHI>
__device__ __forceinline__ void wgmma128(float (&d)[64], uint32_t descA, uint32_t descB) {
    asm volatile(
        "{\n.reg .pred p;\n.reg .b64 da, db;\nsetp.ne.b32 p, %66, 0;\n"
        "mov.b64 da, {%64, 0x40000040};\nmov.b64 db, {%65, %67};\n"
        "wgmma.mma_async.sync.aligned.m64n128k16.f32.bf16.bf16 "
        "{%0, %1, %2, %3, %4, %5, %6, %7, %8, %9, %10, %11, %12, %13, %14, %15, "
        "%16, %17, %18, %19, %20, %21, %22, %23, %24, %25, %26, %27, %28, %29, %30, %31, "
        "%32, %33, %34, %35, %36, %37, %38, %39, %40, %41, %42, %43, %44, %45, %46, %47, "
        "%48, %49, %50, %51, %52, %53, %54, %55, %56, %57, %58, %59, %60, %61, %62, %63}, "
        "da, db, p, 1, 1, 0, 1;\n}\n"
        : "+f"(d[0]), "+f"(d[1]), "+f"(d[2]), "+f"(d[3]), "+f"(d[4]), "+f"(d[5]), "+f"(d[6]), "+f"(d[7]),
          "+f"(d[8]), "+f"(d[9]), "+f"(d[10]), "+f"(d[11]), "+f"(d[12]), "+f"(d[13]), "+f"(d[14]), "+f"(d[15]),
          "+f"(d[16]), "+f"(d[17]), "+f"(d[18]), "+f"(d[19]), "+f"(d[20]), "+f"(d[21]), "+f"(d[22]), "+f"(d[23]),
          "+f"(d[24]), "+f"(d[25]), "+f"(d[26]), "+f"(d[27]), "+f"(d[28]), "+f"(d[29]), "+f"(d[30]), "+f"(d[31]),
          "+f"(d[32]), "+f"(d[33]), "+f"(d[34]), "+f"(d[35]), "+f"(d[36]), "+f"(d[37]), "+f"(d[38]), "+f"(d[39]),
          "+f"(d[40]), "+f"(d[41]), "+f"(d[42]), "+f"(d[43]), "+f"(d[44]), "+f"(d[45]), "+f"(d[46]), "+f"(d[47]),
          "+f"(d[48]), "+f"(d[49]), "+f"(d[50]), "+f"(d[51]), "+f"(d[52]), "+f"(d[53]), "+f"(d[54]), "+f"(d[55]),
          "+f"(d[56]), "+f"(d[57]), "+f"(d[58]), "+f"(d[59]), "+f"(d[60]), "+f"(d[61]), "+f"(d[62]), "+f"(d[63])
        : "r"(descA), "r"(descB), "n"(SCALE_D), "n"(BHI));
}

template <int SCALE_D, int BHI>
__device__ __forceinline__ void wgmma96(float (&d)[48], uint32_t descA, uint32_t descB) {
    asm volatile(
        "{\n.reg .pred p;\n.reg .b64 da, db;\nsetp.ne.b32 p, %50, 0;\n"
        "mov.b64 da, {%48, 0x40000040};\nmov.b64 db, {%49, %51};\n"
        "wgmma.mma_async.sync.aligned.m64n96k16.f32.bf16.bf16 "
        "{%0, %1, %2, %3, %4, %5, %6, %7, %8, %9, %10, %11, %12, %13, %14, %15, "
        "%16, %17, %18, %19, %20, %21, %22, %23, %24, %25, %26, %27, %28, %29, %30, %31, "
        "%32, %33, %34, %35, %36, %37, %38, %39, %40, %41, %42, %43, %44, %45, %46, %47}, "
        "da, db, p, 1, 1, 0, 1;\n}\n"
        : "+f"(d[0]), "+f"(d[1]), "+f"(d[2]), "+f"(d[3]), "+f"(d[4]), "+f"(d[5]), "+f"(d[6]), "+f"(d[7]),
          "+f"(d[8]), "+f"(d[9]), "+f"(d[10]), "+f"(d[11]), "+f"(d[12]), "+f"(d[13]), "+f"(d[14]), "+f"(d[15]),
          "+f"(d[16]), "+f"(d[17]), "+f"(d[18]), "+f"(d[19]), "+f"(d[20]), "+f"(d[21]), "+f"(d[22]), "+f"(d[23]),
          "+f"(d[24]), "+f"(d[25]), "+f"(d[26]), "+f"(d[27]), "+f"(d[28]), "+f"(d[29]), "+f"(d[30]), "+f"(d[31]),
          "+f"(d[32]), "+f"(d[33]), "+f"(d[34]), "+f"(d[35]), "+f"(d[36]), "+f"(d[37]), "+f"(d[38]), "+f"(d[39]),
          "+f"(d[40]), "+f"(d[41]), "+f"(d[42]), "+f"(d[43]), "+f"(d[44]), "+f"(d[45]), "+f"(d[46]), "+f"(d[47])
        : "r"(descA), "r"(descB), "n"(SCALE_D), "n"(BHI));
}

__device__ __forceinline__ uint32_t opq(uint32_t v) { asm volatile("" : "+r"(v)); return v; }
template <int I> struct IC { static constexpr int value = I; };
template <int B, int E, class F> __device__ __forceinline__ void static_for(F&& f) {
    if constexpr (B < E) { f(IC<B>{}); static_for<B + 1, E>(f); }
}

__device__ __forceinline__ void tma_store_2d(const CUtensorMap* tm, uint32_t src, int c0, int c1) {
    asm volatile("cp.async.bulk.tensor.2d.global.shared::cta.bulk_group [%0, {%2, %3}], [%1];" ::"l"(tm), "r"(src), "r"(c0), "r"(c1) : "memory");
}
__device__ __forceinline__ void bulk_store(void* dst, uint32_t src, uint32_t bytes) {
    asm volatile("cp.async.bulk.global.shared::cta.bulk_group [%0], [%1], %2;" ::"l"(dst), "r"(src), "r"(bytes) : "memory");
}
__device__ __forceinline__ void bulk_commit() { asm volatile("cp.async.bulk.commit_group;" ::: "memory"); }
template <int N> __device__ __forceinline__ void bulk_wait_read() { asm volatile("cp.async.bulk.wait_group.read %0;" ::"n"(N) : "memory"); }
__device__ __forceinline__ void bar_arrive(int id) { asm volatile("bar.arrive %0, 256;" ::"r"(id) : "memory"); }
__device__ __forceinline__ void bar_sync(int id) { asm volatile("bar.sync %0, 256;" ::"r"(id) : "memory"); }
template <int NC, int OFF, int N>
__device__ __forceinline__ void stage_cols(const float (&acc)[N], uint32_t stg) {
    int lane; asm volatile("mov.u32 %0, %%laneid;" : "=r"(lane));
    const int r = lane & 15;
    const uint32_t a0 = NC == 64 ? stg + r * 128 + (((lane >> 4) ^ (r & 7)) << 4) : stg + r * 64 + (((lane >> 4) ^ ((r >> 1) & 3)) << 4);
#pragma unroll
    for (int j = 0; j < NC / 16; j++) {
        const int i = OFF + 8 * j;
        stmatrix_x4(a0 ^ (j * 32), pack_bf16(acc[i], acc[i + 1]), pack_bf16(acc[i + 2], acc[i + 3]), pack_bf16(acc[i + 4], acc[i + 5]), pack_bf16(acc[i + 6], acc[i + 7]));
    }
}
__device__ __forceinline__ void send(uint32_t stg, const CUtensorMap* tmo, int col, int row) {
    fence_async_smem();
    __syncwarp();
    if (elect()) { tma_store_2d(tmo, stg, col, row); bulk_commit(); }
    __syncwarp();
}

__host__ __device__ constexpr int fconv(int g, int s) {
    return s + (s < 16 ? (int)(((g ? LEAD1 : LEAD0) >> (60 - 4 * s)) & 15) : 6);
}
__host__ __device__ constexpr int sub_of(int g, int b) { int s = -1; while (fconv(g, s + 1) <= b) s++; return s; }
__host__ __device__ constexpr int sub_min(int b) { return sub_of(0, b) < sub_of(1, b) ? sub_of(0, b) : sub_of(1, b); }
__host__ __device__ constexpr int sub_max(int b) { return sub_of(0, b) > sub_of(1, b) ? sub_of(0, b) : sub_of(1, b); }
__host__ __device__ constexpr int hmode(int u) { return u <= 1 ? 1 : u < HM1 ? 0 : u < HM2 ? 1 : u < HM3 ? 2 : 3; }
__host__ __device__ constexpr int t7(int v) { return sub_max(2 * v + 1) + (hmode(v) == 2 ? 0 : 1); }
__host__ __device__ constexpr int xunit(int i) { int v = 0; while (sub_min(2 * v + 1) < 4 * i - 7) v++; return v; }
__host__ __device__ constexpr int rslot(int u) { return (2 * u) % 3; }
__host__ __device__ constexpr int rpar(int u) { return (u / 3 - (u % 3 == 0)) & 1; }
__host__ __device__ constexpr int sslot(int c) { return c < 3 ? c + 3 : c % 3; }

__global__ void __cluster_dims__(2, 1, 1) __launch_bounds__(256, 1)
nf4_gemm_kernel(const int* __restrict__ qw, const __nv_bfloat16* __restrict__ cb, const __nv_bfloat16* __restrict__ absmax,
                uint8_t* __restrict__ wimg, unsigned* __restrict__ gflag,
                const __grid_constant__ CUtensorMap tmx, const __grid_constant__ CUtensorMap tmq, const __grid_constant__ CUtensorMap tmo64,
                const __grid_constant__ CUtensorMap tmo32, const __grid_constant__ CUtensorMap tmqp, const __grid_constant__ CUtensorMap tmx16,
                const __grid_constant__ CUtensorMap tmx64, const __grid_constant__ CUtensorMap tmq1) {
    extern __shared__ __align__(1024) uint8_t smem[];
    const uint32_t sbase = smem_u32(smem);
    const int rank = blockIdx.x & 1;
    const int mt = (blockIdx.x >> 5) * 2 + rank, nt = (blockIdx.x >> 1) & 15;
    const int lane = threadIdx.x & 31;
    const unsigned tstart = clk();
    uint4 q[4], c0, c1;
    uint2 sf;
    if (threadIdx.x < 224) {
        const int col = nt * BN + (threadIdx.x >> 5) * 32 + (lane & 7) * 4;
        const int* p = qw + (rank * 8 + (lane >> 3)) * N_ + col;
        q[0] = ldg128(p); q[1] = ldg128(p + 4 * N_);
        q[2] = ldg128(p + 16 * N_); q[3] = ldg128(p + 20 * N_);
        asm volatile("ld.global.nc.v2.b32 {%0, %1}, [%2];" : "=r"(sf.x), "=r"(sf.y) : "l"(absmax + col) : "memory");
        c0 = ldg128(cb); c1 = ldg128(cb + 8);
    }
    const int warp = __shfl_sync(~0u, (int)(threadIdx.x >> 5), 0);
    const int wg = warp >> 2;
    const uint32_t bars = sbase + BAR_OFF;
    const uint32_t fullW = bars, rawfull = bars + 48, written = bars + 72, xbar = bars + 96, gbar = bars + 112 + wg * 24;
    const uint32_t x1bar = bars + 160, rawh = bars + 176 - 8, ebar = bars + 200;
    const uint32_t wbase = sbase + W_OFF;
    TS_INIT();
    __syncwarp();
    TSW(0, 0);

    const int pair = mt >> 1;
    auto chunk = [&](int i) { return i < GUEST ? i : i == GUEST ? 12 + pair : i <= 12 ? i - 1 : 12 + ((pair + i) & 3); };
    unsigned* flag = gflag + nt * 32;
    uint8_t* wpan = wimg + nt * 8 * UNIT;
    auto load_x = [&](int i, int slot) {
        tma_load_2d(sbase + slot * 32768, &tmx, chunk(i) * 64, mt * BM, fullW + 16 * slot);
        tma_load_2d(sbase + slot * 32768 + 16384, &tmx, chunk(i) * 64, mt * BM + 128, fullW + 16 * slot);
    };
    auto load_sc = [&](int i, int ss, uint32_t bar) {
        bulk_load(sbase + SC_OFF + ss * SC_STRIDE, absmax + chunk(i) * N_ + nt * BN, 448, bar);
        bulk_load(sbase + SC_OFF + ss * SC_STRIDE + 448, flag, 16, bar);
    };
    auto load_raw = [&](int u, int slot) {
        mbar_expect_tx(rawfull + 8 * slot, UNIT);
        tma_load_5d(sbase + RAW_OFF + roff(slot), &tmq, 0, 0, nt * 7, rank, 4 * chunk(u >> 1) + 2 * (u & 1), rawfull + 8 * slot);
    };
    auto load_half = [&](int b, uint32_t more) {
        const uint32_t bar = (b & 1) ? rawfull + 8 * rslot(b >> 1) : rawh + 8 * (b >> 1);
        mbar_expect_tx(bar, 7168 + more);
        tma_load_5d(sbase + RAW_OFF + roff(rslot(b >> 1)) + (b & 1) * 7168, &tmq1, 0, 0, nt * 7, rank, b, bar);
    };
    auto load_xh = [&](int i, int g, uint32_t bar) {
        mbar_expect_tx(bar, 16384);
        tma_load_2d(sbase + i * 32768 + g * 16384, &tmx, i * 64, mt * BM + g * 128, bar);
    };
    auto prefetch = [&](int c) {
        if (PFQ && c + PFQ < 12) tma_prefetch_2d(&tmqp, nt * BN, (c + PFQ) * 64 + pair * 16 + rank * 8);
        if (PFQ && (unsigned)(c - PFG) < 4) tma_prefetch_2d(&tmqp, nt * BN, (12 + pair) * 64 + (c - PFG) * 16 + rank * 8);
        if (PFX && c + PFX < 16 && c + PFX > 2) tma_prefetch_2d(&tmx16, chunk(c + PFX) * 64, mt * BM + nt * 16);
    };
    if (warp == 7) {
        if (elect()) {
            mbar_init(xbar, 1); mbar_init(rawh + 8, 1); mbar_init(rawfull + 8 * rslot(1), 1); mbar_init(xbar + 8, 1);
            fence_async_smem();
            if (ORD1 == 0) load_xh(0, 0, xbar);
            load_half(2, 448);
            bulk_load(sbase + SC_OFF + sslot(0) * SC_STRIDE, absmax + nt * BN, 448, rawh + 8);
            if (ORD1 == 1) load_xh(0, 0, xbar);
            load_half(3, 0);
            if (ORD1 == 2) load_xh(0, 0, xbar);
            load_xh(0, 1, xbar + 8);
            mbar_init(rawfull + 8 * rslot(2), 1); mbar_init(rawfull + 8 * rslot(3), 1); mbar_init(rawh + 16, 1); mbar_init(rawh + 24, 1);
            mbar_init(x1bar, 1); mbar_init(x1bar + 8, 1);
#pragma unroll
            for (int s = 0; s < 2 * HM2; s++) mbar_init(ebar + 8 * s, 7);
#pragma unroll
            for (int s = 0; s < NW; s++) { mbar_init(fullW + 8 * s, 1); if (s < HM2 && s != 4) mbar_arrive(fullW + 8 * s); }
#pragma unroll
            for (int s = 0; s < NR; s++) mbar_init(written + 8 * s, 7);
#pragma unroll
            for (int s = 0; s < 6; s++) mbar_init(bars + 112 + 8 * s, 4);
            asm volatile("fence.mbarrier_init.release.cluster;" ::: "memory");
            fence_async_smem();
            if ((sbase & 0xffffff) != 0x400) __trap();
        }
        __syncwarp();
        cluster_arrive();
        if (elect()) {
            asm volatile("prefetch.tensormap [%0];" ::"l"(&tmq) : "memory");
            asm volatile("prefetch.tensormap [%0];" ::"l"(&tmqp) : "memory");
            asm volatile("prefetch.tensormap [%0];" ::"l"(&tmx16) : "memory");
            asm volatile("prefetch.tensormap [%0];" ::"l"(&tmx64) : "memory");
            while (clk() - tstart < T2) { }
            load_half(4, 2 * SC_STRIDE); load_sc(1, sslot(1), rawh + 16); load_sc(2, sslot(2), rawh + 16); load_half(5, 0);
            while (clk() - tstart < T2B) { }
            load_xh(1, 0, x1bar);
            if (G2S == 0) { load_half(6, 0); load_half(7, 2 * SC_STRIDE); load_sc(3, sslot(3), rawfull + 8 * rslot(3)); load_sc(4, sslot(4), rawfull + 8 * rslot(3)); load_xh(1, 1, x1bar + 8); }
            while (clk() - tstart < T3) { }
#pragma unroll
            for (int c = 2 - PFQ; c < 0; c++) prefetch(c);
        }
        __syncwarp();
        if (TLPRO > 0) TSL(33);
        cluster_wait();
    } else {
        cluster_arrive();
    }
    const uint32_t rsrc = __shfl_sync(~0u, sbase + RAW_OFF + warp * 1024 + (lane & 7) * 128 + ((((lane >> 3) * 2) ^ (lane & 7)) << 4), lane);
    const uint32_t rsrc2 = __shfl_sync(~0u, rsrc ^ 16, lane);
    const uint32_t ssrc = sbase + SC_OFF + warp * 64;
    const uint32_t wown = wbase + rank * 7168 + warp * 512;
    const uint32_t wdst = __shfl_sync(~0u, wown + lane * 16, lane);
    auto get_sc = [&](int ss) { return lds128(((opq(wdst) >> 3) & 0x30) + ssrc + ss * SC_STRIDE); };
    const uint32_t whalf = wbase + rank * 7168;
    const uint32_t pwhalf = mapa(whalf, rank ^ 1), pfullW = mapa(fullW, rank ^ 1);
    Lut lut;
    uint4 sc;
    uint4 q0, q1;
    auto fetch = [&](int slot, int h) {
        q0 = lds128(rsrc + roff(slot) + h * 7168);
        q1 = lds128(rsrc2 + roff(slot) + h * 7168);
    };
    auto convert0 = [&](int rs, int ws, bool look, uint32_t lbar, uint32_t lpar, int tl = -1) {
        bool ok = true;
        if (look) ok = mbar_try(lbar, lpar);
        const uint32_t p0 = pack4(q0), p1 = pack4(q1);
        if (tl >= 0 && TLPRO == 0 && TSP == 0) TSL(3 * tl + 2);
        uint4 w = dequant8(p0, p1, sc, lut);
        asm volatile("" : "+r"(w.x), "+r"(w.y), "+r"(w.z), "+r"(w.w));
        if (tl >= 0 && TLPRO == 0 && TSP == 1) TSL(3 * tl + 2);
        if (look) mbar_wait1(lbar, lpar, ok);
        if (tl >= 0 && TLPRO == 0 && TSP == 2) TSL(3 * tl + 2);
        fetch(rs, 1);
        sts128x(wdst + ws * UNIT, w);
    };
    auto convert1 = [&](int rs, int ws, bool next, int rsn, int rpn, bool scales, int cs, bool stfirst, bool look, uint32_t lbar, uint32_t lpar, int tl = -1) {
        bool ok = true, ok2 = true;
        if (next) ok = mbar_try(rawfull + 8 * rsn, rpn);
        if (look) ok2 = mbar_try(lbar, lpar);
        const uint32_t p0 = pack4(q0), p1 = pack4(q1);
        if (tl >= 0 && TLPRO == 0 && TSP == 0) TSL(3 * tl + 2);
        uint4 w = dequant8(p0, p1, sc, lut);
        asm volatile("" : "+r"(w.x), "+r"(w.y), "+r"(w.z), "+r"(w.w));
        if (stfirst) {
            sts128x(wdst + ws * UNIT + 3584, w);
            __syncwarp();
            if (elect()) mbar_arrive(written + 8 * rs);
            __syncwarp();
        }
        if (tl >= 0 && TLPRO == 0 && TSP == 1) TSL(3 * tl + 2);
        if (look) mbar_wait2(rawfull + 8 * rsn, rpn, lbar, lpar, ok && ok2);
        else if (next) mbar_wait1(rawfull + 8 * rsn, rpn, ok);
        if (tl >= 0 && TLPRO == 0 && TSP == 2) TSL(3 * tl + 2);
        if (next) fetch(rsn, 0);
        if (!stfirst) {
            sts128x(wdst + ws * UNIT + 3584, w);
            __syncwarp();
            if (elect()) mbar_arrive(written + 8 * rs);
            __syncwarp();
        }
        if (scales) sc = get_sc(cs);
    };
    auto hand_over = [&](int v, int rs, uint32_t par, int ws, uint32_t tx, bool raw) {
        mbar_wait(written + 8 * rs, par);
        fence_async_smem();
        if (elect()) {
            if (raw) load_raw(v + NR, rs);
            copy_to_peer(pwhalf + ws * UNIT, whalf + ws * UNIT, 7168, pfullW + 8 * ws);
            mbar_expect_tx(fullW + 8 * ws, tx);
        }
        __syncwarp();
    };
    auto share = [&](int v, int ws) {
        if ((v >> 1) == GUEST) { bulk_store(wpan + (2 * pair + (v & 1)) * UNIT + rank * 7168, whalf + ws * UNIT, 7168); bulk_commit(); }
    };
    constexpr uint32_t TXO = 7168 + SC_STRIDE, TXE = 7168 + 32768;
    auto hand_over_c = [&](int v) {
        hand_over(v, rslot(v), (v / 3) & 1, v % NW, (v & 1) ? (v < 7 || v == 25 ? 7168 : TXO) : (v < 4 ? 7168 : TXE), v >= 1 && v + NR < NU);
    };
    auto raw_bar = [](int b) { return b < 8 && !(b & 1) ? 168 + 8 * (b >> 1) : b < 8 || !(b & 1) ? 48 + 8 * rslot(b >> 1) : -1; };
    auto raw_par = [](int b) { return b < 8 && !(b & 1) ? 0 : rpar(b >> 1); };
    auto w_bar = [](int s) { return hmode(s >> 1) == 0 ? 200 + 8 * s : (s & 1) ? -1 : hmode(s >> 1) == 1 ? 200 + 8 * s : 8 * ((s >> 1) % NW); };
    auto w_par = [](int s) { return hmode(s >> 1) < 2 ? 0 : ((s >> 1) / NW) & 1; };
    auto wait_slice = [&](int s, bool wok) {
        if (s == 0) { mbar_wait2(xbar + 8 * wg, 0, ebar, 0, wok); if (TLPRO > 0) TSL(32); return; }
        if (s == 4) mbar_wait2(x1bar + 8 * wg, 0, bars + w_bar(s), w_par(s), wok);
        else if (s == 8 && hmode(4) < 2) mbar_wait2(fullW + 32, 0, bars + w_bar(s), w_par(s), wok);
        else if (w_bar(s) >= 0) mbar_wait1(bars + w_bar(s), w_par(s), wok);
    };
    auto pass_on = [&](int b) {
        const int u = b >> 1, n = hmode(u) + 1;
        fence_async_smem();
        __syncwarp();
        if (elect()) {
            const uint32_t o = warp * 512 + u * UNIT, eb = 8 * (n == 1 ? b : 2 * u);
            if (n == 2) copy_to_peer(pwhalf + o, whalf + o, 512, pfullW + 200 + eb);
            copy_to_peer(pwhalf + o + (b & 1) * 3584, whalf + o + (b & 1) * 3584, 512, pfullW + 200 + eb);
            mbar_expect_tx(ebar + eb, n * 512);
        }
        __syncwarp();
    };
    auto passes = [](int b) { return hmode(b >> 1) == 0 || (hmode(b >> 1) == 1 && (b & 1)); };
    auto block = [&](int b, int sn) {
        const int u = b >> 1, h = b & 1;
        const bool pre = b >= PB || ((PM >> b) & 1), pren = (b + 1 >= PB || ((PM >> (b + 1)) & 1)) && b + 1 < 2 * NU;
        const bool war = !h && u >= NW, early_look = sn >= 0 && b - sn >= 2;
        bool ok1 = true, ok2 = true, ok3 = false;
        if (war) ok1 = mbar_try(written + 8 * rslot(u - 2), ((u - 2) / 3) & 1);
        if (pren && raw_bar(b + 1) >= 0) ok2 = mbar_try(bars + raw_bar(b + 1), raw_par(b + 1));
        if (sn >= 0 && w_bar(sn) >= 0) ok3 = mbar_try(bars + w_bar(sn), w_par(sn));
        if (sn == 4) ok3 &= mbar_try(x1bar + 8 * wg, 0);
        if (sn == 8 && hmode(4) < 2) ok3 &= mbar_try(fullW + 32, 0);
        uint4 r0, r1;
        if (pre) { r0 = q0; r1 = q1; }
        else {
            if (raw_bar(b) >= 0) mbar_wait(bars + raw_bar(b), raw_par(b));
            r0 = lds128(rsrc + roff(rslot(u)) + h * 7168); r1 = lds128(rsrc2 + roff(rslot(u)) + h * 7168);
            if (b == 4) sc = get_sc(sslot(1));
        }
        const uint32_t p0 = pack4(r0), p1 = pack4(r1);
        if (TLPRO == 2 && b >= TB && b < TB + 3) TSL(20 + 3 * (b - TB));
        if (b > DEF && passes(b - 1)) pass_on(b - 1);
        uint4 w = dequant8(p0, p1, sc, lut);
        asm volatile("" : "+r"(w.x), "+r"(w.y), "+r"(w.z), "+r"(w.w));
        if (war) mbar_wait1(written + 8 * rslot(u - 2), ((u - 2) / 3) & 1, ok1);
        const bool now = b < DEF && passes(b);
        if (now) { sts128(wdst + (u % NW) * UNIT + h * 3584, w); pass_on(b); }
        if (TLPRO == 2 && b >= TB && b < TB + 3) TSL(21 + 3 * (b - TB));
        if (early_look) wait_slice(sn, ok3);
        if (pren) {
            if (raw_bar(b + 1) >= 0) mbar_wait1(bars + raw_bar(b + 1), raw_par(b + 1), ok2);
            if (TLPRO == 2 && b >= TB && b < TB + 3) TSL(22 + 3 * (b - TB));
            fetch(rslot((b + 1) >> 1), h ^ 1);
        }
        if (!now) sts128(wdst + (u % NW) * UNIT + h * 3584, w);
        if (h) { __syncwarp(); if (elect()) mbar_arrive(written + 8 * rslot(u)); __syncwarp(); }
        if ((b & 3) == 3 && u + 1 < NU) sc = get_sc(sslot((b + 1) >> 2));
        if (sn >= 0 && !early_look) wait_slice(sn, ok3);
    };
    auto blocks = [&](auto A, auto B, int sn) {
        static_for<A.value, B.value>([&](auto I) { block(I.value, I.value == B.value - 1 ? sn : -1); });
        if (A.value == B.value) wait_slice(sn, false);
    };
    auto duties = [&](auto S) {
        constexpr int s = S.value;
        static_for<1, 2 * C0 + 2>([&](auto V) {
            constexpr int v = V.value;
            if constexpr (t7(v) == s || (s == 0 && t7(v) < 0)) {
                if (hmode(v) >= 2) hand_over_c(v);
                else {
                    mbar_wait(written + 8 * rslot(v), (v / 3) & 1);
                    if (elect()) load_raw(v + NR, rslot(v));
                    __syncwarp();
                }
            }
        });
        if (elect()) {
            if (s == 0 && G2S) { load_half(6, 0); load_half(7, 2 * SC_STRIDE); load_sc(3, sslot(3), rawfull + 8 * rslot(3)); load_sc(4, sslot(4), rawfull + 8 * rslot(3)); }
            if (s == G2S - 1) load_xh(1, 1, x1bar + 8);
            if (s == X2AT) { if (HM2 > 4) mbar_expect_tx(fullW + 32, 32768); load_x(2, 2); }
            static_for<3, C0 + 2>([&](auto I) { if constexpr (t7(xunit(I.value)) + XLAG == s) load_x(I.value, I.value % 3); });
            if ((s & 3) == 1) { if (s >= 8) load_sc((s >> 2) + 3, (s >> 2) % 3, fullW + 8 * ((2 * (s >> 2) + 3) % NW)); prefetch(s >> 2); }
        }
        __syncwarp();
    };
    static_assert(HM2 <= 6 && HM1 >= 1 && HM2 >= 3 && C0 < GUEST && t7(2 * C0 + 1) < 4 * C0 && t7(xunit(C0 + 1)) + XLAG < 4 * C0, "");
    bool ok0 = false;
    if (warp < 7) {
        lut.lo[0] = __byte_perm(c0.x, c0.y, 0x6420); lut.hi[0] = __byte_perm(c0.x, c0.y, 0x7531);
        lut.lo[1] = __byte_perm(c0.z, c0.w, 0x6420); lut.hi[1] = __byte_perm(c0.z, c0.w, 0x7531);
        lut.lo[2] = __byte_perm(c1.x, c1.y, 0x6420); lut.hi[2] = __byte_perm(c1.x, c1.y, 0x7531);
        lut.lo[3] = __byte_perm(c1.z, c1.w, 0x6420); lut.hi[3] = __byte_perm(c1.z, c1.w, 0x7531);
        const uint32_t d = wown + ((lane & 7) >> 1) * 128 + (lane >> 3) * 16 + (lane & 1) * 8;
#pragma unroll
        for (int j = 0; j < 4; j++) {
            uint32_t a, b;
            lookup4(pack4(q[j]), lut, a, b);
            asm volatile("st.shared.v2.b32 [%0], {%1, %2};" ::"r"(d + (j >> 1) * 3584 + (j & 1) * 64), "r"(mul_bf16x2(a, sf.x)), "r"(mul_bf16x2(b, sf.y)) : "memory");
        }
        if (TLPRO > 0) TSL(33);
        cluster_wait();
        pass_on(1);
        if (elect()) mbar_arrive(written + 8 * rslot(0));
        __syncwarp();
        if (TLPRO > 0) TSL(34);
        mbar_wait(rawh + 8, 0);
        const uint4 a0 = lds128(rsrc + roff(rslot(1))), a1 = lds128(rsrc2 + roff(rslot(1))), s0 = get_sc(sslot(0));
        mbar_wait(rawfull + 8 * rslot(1), 0);
        if (TLPRO == 2) TSL(29);
        const uint4 a2 = lds128(rsrc + roff(rslot(1)) + 7168), a3 = lds128(rsrc2 + roff(rslot(1)) + 7168);
        sts128(wdst + UNIT, dequant8(pack4(a0), pack4(a1), s0, lut));
        sts128(wdst + UNIT + 3584, dequant8(pack4(a2), pack4(a3), s0, lut));
        ok0 = mbar_try(xbar + 8 * wg, 0) & mbar_try(ebar, 0);
        pass_on(3);
        if (elect()) mbar_arrive(written + 8 * rslot(1));
        __syncwarp();
        if (PB == 4) { mbar_wait(rawh + 16, 0); fetch(rslot(2), 0); sc = get_sc(sslot(1)); }
        static_assert(fconv(0, 0) == 4 && fconv(1, 0) == 4 && PB >= 4 && DEF >= 4, "");
    }
    if (TLPRO > 0) TSL(31);
    wait_slice(0, ok0);

    float acc0[112], acc1[112];
    const uint32_t descA = ((0x400 + wg * 16384) >> 4) | (1u << 16);
    constexpr uint32_t descB = ((0x400 + W_OFF) >> 4) | ((7168u >> 4) << 16);
    auto mma = [&](int slot, int ks, int tl = -1) {
        const uint32_t da = opq(descA) + slot * (32768 >> 4) + ks * 2, db = descB + (2 * slot + (ks >> 1)) * (UNIT >> 4) + (ks & 1) * 224;
        if (tl >= 0 && TLPRO == 0) TSL(3 * tl);
        wgmma_fence();
        wgmma224<1, 8>(acc0, da, db); wgmma224<1, 8>(acc1, da + 512, db);
        wgmma_commit();
        wgmma_wait<2>();
        if (tl >= 0 && TLPRO == 0) TSL(3 * tl + 1);
    };
    static_for<0, 4 * C0>([&](auto S) {
        constexpr int s = S.value;
        constexpr int c = s >> 2;
        if (s == 0) {
            wgmma_fence();
            wgmma224<0, 8>(acc0, descA, descB); wgmma224<0, 8>(acc1, descA + 512, descB);
            wgmma_commit();
        } else mma(c % 3, s & 3);
        if (TLPRO > 0) TSL(s);
        constexpr int a0 = fconv(0, s), b0 = fconv(0, s + 1), a1 = fconv(1, s), b1 = fconv(1, s + 1);
        if (warp == 7) { duties(S); wait_slice(s + 1, false); }
        else if ((a0 == a1 && b0 == b1) || wg == 0) blocks(IC<a0>{}, IC<b0>{}, s + 1);
        else blocks(IC<a1>{}, IC<b1>{}, s + 1);
    });
    auto load_w = [&](int v, uint32_t dst, uint32_t bar) {
        mbar_expect_tx(bar, UNIT);
        bulk_load(dst, wpan + (2 * (chunk(v >> 1) - 12) + (v & 1)) * UNIT, UNIT, bar);
    };
    auto load_l = [&](int i, int slot, int g, uint32_t bar) {
        tma_load_2d(sbase + slot * 32768 + g * 16384, &tmx64, chunk(i) * 64, mt * BM + g * 128, bar);
        tma_load_2d(sbase + slot * 32768 + g * 16384 + 8192, &tmx64, chunk(i + 1) * 64, mt * BM + g * 128, bar);
    };
    static_assert(fconv(0, 4 * C0) == 4 * C0 + 6 && fconv(1, 4 * C0) == 4 * C0 + 6 && PB <= 4 * C0 + 6, "ramp must be over");
    {
        uint32_t ph = (C0 / 3) & 1;
#pragma unroll 1
        for (int cb = C0; cb < C1; cb += 3)
          static_for<0, 3>([&](auto I) {
            constexpr int cc = C0 + I.value;
            constexpr int j0 = cc % 3, j1 = (cc + 1) % 3, j2 = (cc + 2) % 3;
            const int c = cb + I.value;
            if (TLPRO > 0 && I.value == 0) TSL(c < 8 ? 36 : 37);
            mma(j0, 0, 4 * I.value + 0);
            if (warp < 7) convert0(j0, 2 * j1 + 1, true, written + 8 * j2, ((2 * cc + 1) / 3) & 1, 4 * I.value);
            else hand_over(2 * c + 2, j1, ((2 * cc + 2) / 3) & 1, 2 * j1, TXE, true);
            mma(j0, 1, 4 * I.value + 1);
            if (warp < 7) convert1(j0, 2 * j1 + 1, true, j2, rpar(2 * cc + 4), true, j2, STFIRST, true, fullW + 16 * j0 + 8, ph, 4 * I.value + 1);
            else {
                if (elect()) {
                    load_sc(c + 3, j0, fullW + 16 * j1 + 8);
                    prefetch(c);
                    share(2 * c + 2, 2 * j1);
                    if (c == GUEST + PUBD) {
                        asm volatile("cp.async.bulk.wait_group 0;" ::: "memory");
                        asm volatile("red.relaxed.gpu.global.add.u32 [%0], 1;" ::"l"(flag) : "memory");
                    }
                }
                __syncwarp();
                mbar_wait(fullW + 16 * j0 + 8, ph);
            }
            if (j1 == 0) asm volatile("xor.b32 %0, %0, 1;" : "+r"(ph));
            mma(j0, 2, 4 * I.value + 2);
            if (warp < 7) convert0(j2, 2 * j2, true, written + 8 * j1, ((2 * cc + 2) / 3) & 1, 4 * I.value + 2);
            else {
                hand_over(2 * c + 3, j0, ((2 * cc + 3) / 3) & 1, 2 * j1 + 1, TXO, j0 != 1 || c < 10);
                if (j0 == 1 && c == 10) {
                    unsigned f0, f1;
                    asm volatile("ld.shared.u32 %0, [%1];" : "=r"(f0) : "r"(sbase + SC_OFF + sslot(1) * SC_STRIDE + 448) : "memory");
                    asm volatile("ld.shared.u32 %0, [%1];" : "=r"(f1) : "r"(sbase + SC_OFF + sslot(12) * SC_STRIDE + 448) : "memory");
                    asm volatile("{\n.reg .pred p;\n.reg .u32 n, d;\nmov.u32 n, 0;\nLAB_POLL:\nsub.u32 d, %0, %1;\nsetp.ge.u32 p, d, 8;\n@p bra.uni LAB_DONE;\n"
                                 "ld.relaxed.gpu.global.u32 %0, [%2];\nadd.u32 n, n, 1;\nsetp.lt.u32 p, n, 0x10000;\n@p bra.uni LAB_POLL;\nLAB_DONE:\n}\n"
                                 : "+r"(f1) : "r"(f0 & ~7u), "l"(flag) : "memory");
                    if (elect()) load_w(26, sbase + RAW_OFF + roff(rslot(23)), rawfull + 8 * rslot(23));
                    __syncwarp();
                }
            }
            mma(j0, 3, 4 * I.value + 3);
            if (warp < 7) convert1(j2, 2 * j2, true, j1, rpar(2 * cc + 5), false, 0, STFIRST, true, fullW + 16 * j1, ph, 4 * I.value + 3);
            else {
                if (elect()) {
                    if (j0 == 1 && c == 10) { load_l(12, 0, 0, fullW); load_l(12, 0, 1, fullW); }
                    else load_x(c + 2, j2);
                    share(2 * c + 3, 2 * j1 + 1);
                }
                __syncwarp();
                mbar_wait(fullW + 16 * j1, ph);
            }
          });
    }
    static_assert(C1 == 11 && GUEST + PUBD < 9, "");
    mma(2, 0);
    if (warp < 7) block(50, -1);
    else {
        mbar_wait(written + 8 * rslot(24), 0);
        if (elect()) {
            load_w(27, sbase + RAW_OFF + roff(rslot(24)), rawfull + 8 * rslot(24));
            load_w(28, wbase + 2 * UNIT, fullW + 16);
        }
        __syncwarp();
        hand_over_c(24);
        TSX(7, 6);
    }
    mma(2, 1);
    if (warp < 7) block(51, 46);
    else {
        if (elect()) {
            asm volatile("prefetch.tensormap [%0];" ::"l"(&tmo64) : "memory");
            asm volatile("prefetch.tensormap [%0];" ::"l"(&tmo32) : "memory");
        }
        __syncwarp();
        mbar_wait(fullW + 8 * 5, 1);
        hand_over_c(25);
        if (elect()) {
            mbar_expect_tx(xbar, 16384); load_l(14, 1, 0, xbar);
            load_w(29, sbase + RAW_OFF + roff(rslot(25)), rawfull + 8 * rslot(25));
            load_w(30, wbase + 3 * UNIT, fullW + 24);
        }
        __syncwarp();
        TSX(7, 7);
    }
    if (wg == 1) bar_sync(8);
    mma(2, 2);
    if (warp == 7) {
        wgmma_wait<1>();
        mbar_wait(fullW, 0);
        if (elect()) { load_w(31, wbase + 4 * UNIT, fullW + 32); mbar_expect_tx(xbar + 8, 16384); load_l(14, 1, 1, xbar + 8); }
        __syncwarp();
    }
    mma(2, 3);
    if (wg == 0) bar_arrive(8);
    const uint32_t slice0 = sbase + wg * 16384 + (warp & 3) * 2048;
    auto slc = [&](int p) { return slice0 + (p >> 1) * 32768 + (p & 1) * 8192; };
    const int row0 = mt * BM + wg * 128 + (warp & 3) * 16, col0 = nt * BN;
    auto load_s = [&](int i, int p, uint32_t bar) { tma_load_2d(slc(p), &tmx16, chunk(i) * 64, row0 + 64, bar); };
    const uint32_t tA = opq(descA);
    mbar_wait(fullW, 0);
    wgmma_wait<0>();
    TSW(wg * 4, 8 + wg);
    float lo0[64], hi0[48], lo1[64], hi1[48];
#pragma unroll
    for (int i = 0; i < 64; i++) { asm volatile("mov.b32 %0, %1;" : "=f"(lo0[i]) : "f"(acc0[i])); asm volatile("mov.b32 %0, %1;" : "=f"(lo1[i]) : "f"(acc1[i])); }
#pragma unroll
    for (int i = 0; i < 48; i++) { asm volatile("mov.b32 %0, %1;" : "=f"(hi0[i]) : "f"(acc0[64 + i])); asm volatile("mov.b32 %0, %1;" : "=f"(hi1[i]) : "f"(acc1[64 + i])); }
    auto udesc = [](int s) {
        const int v = 24 + (s >> 1);
        const int off = v == 26 ? RAW_OFF + roff(rslot(23)) : v == 27 ? RAW_OFF + roff(rslot(24)) : v == 29 ? RAW_OFF + roff(rslot(25))
                      : W_OFF + (v < 26 ? v - 24 : v == 28 ? 2 : v - 27) * UNIT;
        return (uint32_t)(((0x400 + off) >> 4) | ((7168u >> 4) << 16)) + (s & 1) * 224;
    };
    auto tdesc = [&](int p, int s) { return tA + (p >> 1) * (32768 >> 4) + (p & 1) * 512 + (s & 3) * 2; };
    auto ldesc = [&](int s) { return tdesc(s >> 2, s); };
    auto gdesc = [&](int s) { return tdesc(((s >> 2) + 4) % 6, s); };
    if (wg == 1) { mbar_wait(xbar + 8, 1); bar_sync(1); }
    static_for<0, 8>([&](auto V) {
        constexpr int v = 24 + (V.value == 0 || V.value > 3 ? V.value : V.value == 3 ? 1 : V.value + 1), s = 2 * (v - 24);
        if (v == 26) mbar_wait2(rawfull + 8 * rslot(23), rpar(26), rawfull + 8 * rslot(24), rpar(27), wg);
        else if (v == 29) mbar_wait1(rawfull + 8 * rslot(25), rpar(28), wg);
        else if (v == 28) mbar_wait2(fullW + 16, 0, xbar, 1, wg);
        else if (v != 24 && v != 27) mbar_wait1(fullW + 8 * (v == 25 ? 1 : v - 27), 0, wg);
        if (v == 28) TSX(wg * 4, 12 + wg);
        if (v == 31) TSX(wg * 4, 10 + wg);
        wgmma_fence();
        wgmma96<1, 8>(hi0, ldesc(s), udesc(s) + 128);
        wgmma96<1, 8>(hi0, ldesc(s + 1), udesc(s + 1) + 128);
    });
    wgmma_commit();
    bar_arrive(1 + wg);
    cluster_arrive();
    wgmma_wait<0>();
    TSX(wg * 4, 16 + wg);
    stage_cols<64, 0>(hi0, slc(4)); send(slc(4), &tmo64, col0 + 128, row0);
    stage_cols<32, 32>(hi0, slc(5));
    TSX(wg * 4, 18 + wg);
    bar_sync(2 + wg);
    wgmma_fence();
#pragma unroll
    for (int s = 0; s < G1; s++) wgmma128<1, 8>(lo0, ldesc(s), udesc(s));
    wgmma_commit();
    if (GS) {
        if (elect()) { bulk_wait_read<0>(); mbar_expect_tx(gbar, 2048); load_s(12, 4, gbar); }
        __syncwarp();
    }
    send(slc(5), &tmo32, col0 + 192, row0);
    wgmma_fence();
#pragma unroll
    for (int s = G1; s < 16; s++) wgmma128<1, 8>(lo0, ldesc(s), udesc(s));
    wgmma_commit();
    bar_arrive(3 + wg);
    if (elect()) {
        if (GS) { mbar_expect_tx(gbar + 16, 2048); bulk_wait_read<0>(); load_s(13, 5, gbar + 16); }
        else { mbar_expect_tx(gbar, 4096); bulk_wait_read<0>(); load_s(12, 4, gbar); load_s(13, 5, gbar); }
    }
    __syncwarp();
    TSX(wg * 4, 58 + wg);
    wgmma_wait<0>();
    TSX(wg * 4, 20 + wg);
    stage_cols<64, 0>(lo0, slc(2));
    if (GL == 0) {
        if (elect()) { mbar_expect_tx(gbar + 8, 4096); load_s(14, 0, gbar + 8); load_s(15, 1, gbar + 8); }
        __syncwarp();
    }
    const bool okg = mbar_try(gbar, 0), okg2 = !GS || mbar_try(gbar + 16, 0);
    send(slc(2), &tmo64, col0, row0);
    TSX(wg * 4, 48 + wg);
    if (GR == 0) mbar_wait1(gbar, 0, okg);
    stage_cols<64, 32>(lo0, slc(3));
    if (GL == 1) {
        if (elect()) { mbar_expect_tx(gbar + 8, 4096); load_s(14, 0, gbar + 8); load_s(15, 1, gbar + 8); }
        __syncwarp();
    }
    if (GR == 1) mbar_wait1(gbar, 0, okg);
    if (E1 == 0) send(slc(3), &tmo64, col0 + 64, row0);
    TSX(wg * 4, 22 + wg);
    bar_sync(4 + wg);
    TSX(wg * 4, 44 + wg);
    wgmma_fence();
#pragma unroll
    for (int s = 0; s < 4; s++) wgmma128<1, 8>(lo1, gdesc(s), udesc(s));
    if (GS) { mbar_wait1(gbar + 16, 0, okg2); wgmma_fence(); }
#pragma unroll
    for (int s = 4; s < 8; s++) wgmma128<1, 8>(lo1, gdesc(s), udesc(s));
    wgmma_commit();
    if (E1 == 1) send(slc(3), &tmo64, col0 + 64, row0);
    mbar_wait(gbar + 8, 0);
    TSX(wg * 4, 52 + wg);
    wgmma_fence();
#pragma unroll
    for (int s = 8; s < 16; s++) wgmma128<1, 8>(lo1, gdesc(s), udesc(s));
    wgmma_commit();
    bar_arrive(5 + wg);
    if (elect()) bulk_wait_read<0>();
    __syncwarp();
    wgmma_wait<0>();
    TSX(wg * 4, 24 + wg);
    stage_cols<64, 0>(lo1, slc(2)); send(slc(2), &tmo64, col0, row0 + 64);
    stage_cols<64, 32>(lo1, slc(3));
    if (E2 == 0 && wg == 0) send(slc(3), &tmo64, col0 + 64, row0 + 64);
    TSX(wg * 4, 26 + wg);
    bar_sync(6 + wg);
    wgmma_fence();
#pragma unroll
    for (int s = 0; s < G3; s++) wgmma96<1, 8>(hi1, gdesc(s), udesc(s) + 128);
    wgmma_commit();
    if (E2 == 1 || wg == 1) send(slc(3), &tmo64, col0 + 64, row0 + 64);
    wgmma_fence();
#pragma unroll
    for (int s = G3; s < 16; s++) wgmma96<1, 8>(hi1, gdesc(s), udesc(s) + 128);
    wgmma_commit();
    if (wg == 0) bar_arrive(7);
    wgmma_wait<0>();
    TSW(wg * 4, 34 + wg);
    stage_cols<64, 0>(hi1, slc(1));
    if (E3 == 0) send(slc(1), &tmo64, col0 + 128, row0 + 64);
    stage_cols<32, 32>(hi1, slc(5));
    if (E3 == 0) send(slc(5), &tmo32, col0 + 192, row0 + 64);
    else {
        fence_async_smem();
        __syncwarp();
        if (elect()) { tma_store_2d(&tmo64, slc(1), col0 + 128, row0 + 64); tma_store_2d(&tmo32, slc(5), col0 + 192, row0 + 64); bulk_commit(); }
        __syncwarp();
    }
    TSX(wg * 4, 36 + wg);
    if (elect()) bulk_wait_read<0>();
    __syncwarp();
    TSW(wg * 4, 38 + wg);
    TS_DUMP();
    TL_DUMP();
    cluster_wait();
}

typedef CUresult (*EncodeFn)(CUtensorMap*, CUtensorMapDataType, cuuint32_t, void*, const cuuint64_t*, const cuuint64_t*,
                             const cuuint32_t*, const cuuint32_t*, CUtensorMapInterleave, CUtensorMapSwizzle,
                             CUtensorMapL2promotion, CUtensorMapFloatOOBfill);

extern "C" void kernel_launch(void* const* d_in, const int* in_sizes, int n_in, void* d_out, int out_size) {
    const __nv_bfloat16* x = (const __nv_bfloat16*)d_in[0];
    const int* qw = (const int*)d_in[1];
    const __nv_bfloat16* cb = (const __nv_bfloat16*)d_in[2];
    const __nv_bfloat16* absmax = (const __nv_bfloat16*)d_in[3];
    static EncodeFn encode = nullptr;
    static void *wimg = nullptr, *gflag = nullptr;
    if (!encode) {
        cudaGetSymbolAddress(&wimg, g_wimg);
        cudaGetSymbolAddress(&gflag, g_flag);
        void* fn = nullptr;
        cudaDriverEntryPointQueryResult qr;
        cudaGetDriverEntryPoint("cuTensorMapEncodeTiled", &fn, cudaEnableDefault, &qr);
        encode = (EncodeFn)fn;
        cudaFuncSetAttribute(nf4_gemm_kernel, cudaFuncAttributeMaxDynamicSharedMemorySize, SMEM_BYTES);
    }
    CUtensorMap tmx, tmq, tmo64, tmo32, tmqp, tmx16, tmx64, tmq1;
    {
        cuuint64_t dims[2] = {(cuuint64_t)K_, (cuuint64_t)M_};
        cuuint64_t strides[1] = {(cuuint64_t)K_ * 2};
        cuuint32_t box[2] = {64, 128};
        cuuint32_t es[2] = {1, 1};
        encode(&tmx, CU_TENSOR_MAP_DATA_TYPE_BFLOAT16, 2, (void*)x, dims, strides, box, es, CU_TENSOR_MAP_INTERLEAVE_NONE,
               CU_TENSOR_MAP_SWIZZLE_128B, CU_TENSOR_MAP_L2_PROMOTION_L2_128B, CU_TENSOR_MAP_FLOAT_OOB_FILL_NONE);
        box[1] = 64;
        encode(&tmx64, CU_TENSOR_MAP_DATA_TYPE_BFLOAT16, 2, (void*)x, dims, strides, box, es, CU_TENSOR_MAP_INTERLEAVE_NONE,
               CU_TENSOR_MAP_SWIZZLE_128B, CU_TENSOR_MAP_L2_PROMOTION_L2_128B, CU_TENSOR_MAP_FLOAT_OOB_FILL_NONE);
        box[1] = 16;
        encode(&tmx16, CU_TENSOR_MAP_DATA_TYPE_BFLOAT16, 2, (void*)x, dims, strides, box, es, CU_TENSOR_MAP_INTERLEAVE_NONE,
               CU_TENSOR_MAP_SWIZZLE_128B, CU_TENSOR_MAP_L2_PROMOTION_L2_128B, CU_TENSOR_MAP_FLOAT_OOB_FILL_NONE);
    }
    {
        cuuint64_t dims[5] = {32, 8, (cuuint64_t)(N_ / 32), 2, (cuuint64_t)(K_ / 16)};
        cuuint64_t strides[4] = {(cuuint64_t)N_ * 4, 128, (cuuint64_t)N_ * 4 * 8, (cuuint64_t)N_ * 4 * 16};
        cuuint32_t box[5] = {32, 8, 7, 1, 2};
        cuuint32_t es[5] = {1, 1, 1, 1, 1};
        encode(&tmq, CU_TENSOR_MAP_DATA_TYPE_INT32, 5, (void*)qw, dims, strides, box, es, CU_TENSOR_MAP_INTERLEAVE_NONE,
               CU_TENSOR_MAP_SWIZZLE_128B, CU_TENSOR_MAP_L2_PROMOTION_L2_128B, CU_TENSOR_MAP_FLOAT_OOB_FILL_NONE);
        box[4] = 1;
        encode(&tmq1, CU_TENSOR_MAP_DATA_TYPE_INT32, 5, (void*)qw, dims, strides, box, es, CU_TENSOR_MAP_INTERLEAVE_NONE,
               CU_TENSOR_MAP_SWIZZLE_128B, CU_TENSOR_MAP_L2_PROMOTION_L2_128B, CU_TENSOR_MAP_FLOAT_OOB_FILL_NONE);
        cuuint64_t dims2[2] = {(cuuint64_t)N_, (cuuint64_t)K_};
        cuuint32_t box2[2] = {224, 8};
        encode(&tmqp, CU_TENSOR_MAP_DATA_TYPE_INT32, 2, (void*)qw, dims2, strides, box2, es, CU_TENSOR_MAP_INTERLEAVE_NONE,
               CU_TENSOR_MAP_SWIZZLE_NONE, CU_TENSOR_MAP_L2_PROMOTION_L2_128B, CU_TENSOR_MAP_FLOAT_OOB_FILL_NONE);
    }
    {
        cuuint64_t dims[2] = {(cuuint64_t)N_, (cuuint64_t)M_};
        cuuint64_t strides[1] = {(cuuint64_t)N_ * 2};
        cuuint32_t box[2] = {64, 16};
        cuuint32_t es[2] = {1, 1};
        encode(&tmo64, CU_TENSOR_MAP_DATA_TYPE_BFLOAT16, 2, d_out, dims, strides, box, es, CU_TENSOR_MAP_INTERLEAVE_NONE,
               CU_TENSOR_MAP_SWIZZLE_128B, CU_TENSOR_MAP_L2_PROMOTION_NONE, CU_TENSOR_MAP_FLOAT_OOB_FILL_NONE);
        box[0] = 32;
        encode(&tmo32, CU_TENSOR_MAP_DATA_TYPE_BFLOAT16, 2, d_out, dims, strides, box, es, CU_TENSOR_MAP_INTERLEAVE_NONE,
               CU_TENSOR_MAP_SWIZZLE_64B, CU_TENSOR_MAP_L2_PROMOTION_NONE, CU_TENSOR_MAP_FLOAT_OOB_FILL_NONE);
    }
    nf4_gemm_kernel<<<128, 256, SMEM_BYTES>>>(qw, cb, absmax, (uint8_t*)wimg, (unsigned*)gflag, tmx, tmq, tmo64, tmo32, tmqp, tmx16, tmx64, tmq1);
}
```

```cpp
#include <cuda_runtime.h>
#include <cuda_bf16.h>
#include <cuda.h>
#include <stdint.h>

constexpr int M_ = 2048, K_ = 1024, N_ = 3584;
constexpr int BM = 256, BN = 224;
constexpr int UNIT = 14336;
constexpr int NW = 6, NR = 3;
constexpr int RAW_OFF = 3 * 32768;
constexpr int SC_OFF = RAW_OFF + 2 * UNIT;
constexpr int W_OFF = 127 * 1024;
constexpr int RAW2_OFF = W_OFF + NW * UNIT;
constexpr int BAR_OFF = RAW2_OFF + UNIT;
__host__ __device__ constexpr int roff(int slot) { return slot < 2 ? slot * UNIT : RAW2_OFF - RAW_OFF; }
constexpr int SMEM_BYTES = BAR_OFF + 320;
#define TRAPSTR ""
#define DLEAD 6
#define PFQ 4
#define PFX 3
#define FT 38
#define TSP 2
#define LATE0 12
#define XLATE 1
#define STFIRST 0
#define RAWFIRST 0
#define F0 2
#define RAMP 4
#define C0 2
#define C1 11

#define SPL1 8
#define SPL3 8
#define E1 1
#define E2 1
#define PUBD 1
#define G1 7
#define G3 9
#define E3 0
#define E0 2
#define TLPRO -2
#define LEAD0 0x4345556666666666ull
#define LEAD1 LEAD0
#define HM1 4
#define HM2 4
#define HM3 4
#define PB 5
#define T2 1000
#define T3 1800
#define X2AT 1
#define XLAG 0
#define T2B 1400
#define G2S 0
#define PM 0
#define DEF 4
#define TB 4
#define ORD1 2
#define GS 0
#define GL 0
#define GR 1
#define MAPM 0
#define HO 0
#define SG0 0
#define SG1 0
#define SG2 0
#define SG3 0
#define SG4 0
#define ALIGNO 1
#define TLIT 2
#define GUEST 7
#define PFG 1
constexpr int NU = 26;
constexpr int SC_STRIDE = 464;
__device__ __align__(1024) uint8_t g_wimg[16 * 8 * UNIT];
__device__ __align__(128) unsigned g_flag[16 * 32];

#define TSL(i)
#define TL_DUMP()
#define TSW(w, i)
#define TS_INIT()
#define TS_DUMP()

#define TSX(w, i)
#define RT(i)
__device__ __forceinline__ uint32_t smem_u32(const void* p) { return (uint32_t)__cvta_generic_to_shared(p); }
__device__ __forceinline__ bool elect() {
    uint32_t ok;
    asm volatile("{\n.reg .pred p;\nelect.sync _|p, 0xffffffff;\nselp.u32 %0, 1, 0, p;\n}\n" : "=r"(ok));
    return ok != 0;
}
__device__ __forceinline__ void mbar_init(uint32_t bar, uint32_t cnt) { asm volatile("mbarrier.init.shared::cta.b64 [%0], %1;" ::"r"(bar), "r"(cnt) : "memory"); }
__device__ __forceinline__ void mbar_expect_tx(uint32_t bar, uint32_t bytes) { asm volatile("mbarrier.arrive.expect_tx.shared::cta.b64 _, [%0], %1;" ::"r"(bar), "r"(bytes) : "memory"); }
__device__ __forceinline__ void mbar_arrive(uint32_t bar) { asm volatile("mbarrier.arrive.shared::cta.b64 _, [%0];" ::"r"(bar) : "memory"); }
__device__ __forceinline__ void mbar_arrive_cluster(uint32_t cbar) { asm volatile("mbarrier.arrive.shared::cluster.b64 _, [%0];" ::"r"(cbar) : "memory"); }
__device__ __forceinline__ void mbar_arrive_cluster_if(bool c, uint32_t cbar) {
    asm volatile("{\n.reg .pred p;\nsetp.ne.u32 p, %1, 0;\n@p mbarrier.arrive.shared::cluster.b64 _, [%0];\n}\n" ::"r"(cbar), "r"((uint32_t)c) : "memory");
}
#define BOUNDED
#define WAIT_INIT "mov.u32 n, 0;\n"
#define WAIT_NEXT "@p bra.uni LAB_DONE;\nadd.u32 n, n, 1;\nsetp.lt.u32 p, n, 0x4000;\n@p bra.uni LAB_WAIT;\n"
__device__ __forceinline__ void mbar_wait(uint32_t bar, uint32_t parity) {
    asm volatile(
        "{\n.reg .pred p;\n.reg .u32 n;\n"
        WAIT_INIT
        "LAB_WAIT:\n"
        "mbarrier.try_wait.parity.shared::cta.b64 p, [%0], %1;\n"
        WAIT_NEXT
        "LAB_DONE:\n}\n" ::"r"(bar), "r"(parity) : "memory");
}
__device__ __forceinline__ bool mbar_try(uint32_t bar, uint32_t parity) {
    uint32_t ok;
    asm volatile("{\n.reg .pred p;\nmbarrier.test_wait.parity.shared::cta.b64 p, [%1], %2;\nselp.u32 %0, 1, 0, p;\n}\n" : "=r"(ok) : "r"(bar), "r"(parity) : "memory");
    return ok != 0;
}
__device__ __forceinline__ void mbar_wait1(uint32_t b0, uint32_t p0, bool skip) {
    asm volatile(
        "{\n.reg .pred p;\n.reg .u32 n;\n"
        "setp.ne.u32 p, %2, 0;\n@p bra.uni LAB_DONE;\n"
        WAIT_INIT
        "LAB_WAIT:\n"
        "mbarrier.try_wait.parity.shared::cta.b64 p, [%0], %1;\n"
        WAIT_NEXT
        "LAB_DONE:\n}\n" ::"r"(b0), "r"(p0), "r"((uint32_t)skip) : "memory");
}
__device__ __forceinline__ void mbar_wait2(uint32_t b0, uint32_t p0, uint32_t b1, uint32_t p1, bool skip = false) {
    asm volatile(
        "{\n.reg .pred p, q;\n.reg .u32 n;\n"
        "setp.ne.u32 p, %4, 0;\n@p bra.uni LAB_DONE;\n"
        WAIT_INIT
        "LAB_WAIT:\n"
        "mbarrier.try_wait.parity.shared::cta.b64 p, [%0], %1;\n"
        "mbarrier.try_wait.parity.shared::cta.b64 q, [%2], %3;\n"
        "and.pred p, p, q;\n"
        WAIT_NEXT
        "LAB_DONE:\n}\n" ::"r"(b0), "r"(p0), "r"(b1), "r"(p1), "r"((uint32_t)skip) : "memory");
}
__device__ __forceinline__ void mbar_wait3(uint32_t b0, uint32_t p0, uint32_t b1, uint32_t p1, uint32_t b2, uint32_t p2, bool skip = false) {
    asm volatile(
        "{\n.reg .pred p, q, r;\n.reg .u32 n;\n"
        "setp.ne.u32 p, %6, 0;\n@p bra.uni LAB_DONE;\n"
        WAIT_INIT
        "LAB_WAIT:\n"
        "mbarrier.try_wait.parity.shared::cta.b64 p, [%0], %1;\n"
        "mbarrier.try_wait.parity.shared::cta.b64 q, [%2], %3;\n"
        "mbarrier.try_wait.parity.shared::cta.b64 r, [%4], %5;\n"
        "and.pred p, p, q;\n"
        "and.pred p, p, r;\n"
        WAIT_NEXT
        "LAB_DONE:\n}\n" ::"r"(b0), "r"(p0), "r"(b1), "r"(p1), "r"(b2), "r"(p2), "r"((uint32_t)skip) : "memory");
}
__device__ __forceinline__ void tma_load_2d(uint32_t dst, const CUtensorMap* tm, int c0, int c1, uint32_t bar) {
    asm volatile("cp.async.bulk.tensor.2d.shared::cluster.global.mbarrier::complete_tx::bytes [%0], [%1, {%2, %3}], [%4];"
                 ::"r"(dst), "l"(tm), "r"(c0), "r"(c1), "r"(bar) : "memory");
}
__device__ __forceinline__ void tma_load_4d(uint32_t dst, const CUtensorMap* tm, int c0, int c1, int c2, int c3, uint32_t bar) {
    asm volatile("cp.async.bulk.tensor.4d.shared::cluster.global.mbarrier::complete_tx::bytes [%0], [%1, {%2, %3, %4, %5}], [%6];"
                 ::"r"(dst), "l"(tm), "r"(c0), "r"(c1), "r"(c2), "r"(c3), "r"(bar) : "memory");
}
__device__ __forceinline__ void tma_load_5d(uint32_t dst, const CUtensorMap* tm, int c0, int c1, int c2, int c3, int c4, uint32_t bar) {
    asm volatile("cp.async.bulk.tensor.5d.shared::cluster.global.mbarrier::complete_tx::bytes [%0], [%1, {%2, %3, %4, %5, %6}], [%7];"
                 ::"r"(dst), "l"(tm), "r"(c0), "r"(c1), "r"(c2), "r"(c3), "r"(c4), "r"(bar) : "memory");
}
__device__ __forceinline__ void tma_prefetch_2d(const CUtensorMap* tm, int c0, int c1) {
    asm volatile("cp.async.bulk.prefetch.tensor.2d.L2.global [%0, {%1, %2}];" ::"l"(tm), "r"(c0), "r"(c1) : "memory");
}
__device__ __forceinline__ void bulk_load(uint32_t dst, const void* src, uint32_t bytes, uint32_t bar) {
    asm volatile("cp.async.bulk.shared::cluster.global.mbarrier::complete_tx::bytes [%0], [%1], %2, [%3];"
                 ::"r"(dst), "l"(src), "r"(bytes), "r"(bar) : "memory");
}
__device__ __forceinline__ void tma_store_3d(const CUtensorMap* tm, uint32_t src, int c0, int c1, int c2) {
    asm volatile("cp.async.bulk.tensor.3d.global.shared::cta.bulk_group [%0, {%2, %3, %4}], [%1];"
                 ::"l"(tm), "r"(src), "r"(c0), "r"(c1), "r"(c2) : "memory");
}
__device__ __forceinline__ void cluster_arrive() { asm volatile("barrier.cluster.arrive.relaxed.aligned;" ::: "memory"); }
__device__ __forceinline__ void cluster_wait() { asm volatile("barrier.cluster.wait.acquire.aligned;" ::: "memory"); }
__device__ __forceinline__ uint32_t mapa(uint32_t addr, uint32_t cta) {
    uint32_t r; asm("mapa.shared::cluster.u32 %0, %1, %2;" : "=r"(r) : "r"(addr), "r"(cta)); return r;
}
__device__ __forceinline__ void copy_to_peer(uint32_t cdst, uint32_t src, uint32_t bytes, uint32_t cbar) {
    asm volatile("cp.async.bulk.shared::cluster.shared::cta.mbarrier::complete_tx::bytes [%0], [%1], %2, [%3];"
                 ::"r"(cdst), "r"(src), "r"(bytes), "r"(cbar) : "memory");
}
__device__ __forceinline__ void wgmma_fence() { asm volatile("wgmma.fence.sync.aligned;" ::: "memory"); }
__device__ __forceinline__ void wgmma_commit() { asm volatile("wgmma.commit_group.sync.aligned;" ::: "memory"); }
template <int N> __device__ __forceinline__ void wgmma_wait() { asm volatile("wgmma.wait_group.sync.aligned %0;" ::"n"(N) : "memory"); }
__device__ __forceinline__ uint32_t pack_bf16(float lo, float hi) {
    uint32_t r; asm("cvt.rn.bf16x2.f32 %0, %1, %2;" : "=r"(r) : "f"(hi), "f"(lo)); return r;
}
__device__ __forceinline__ void stmatrix_x4(uint32_t addr, uint32_t a, uint32_t b, uint32_t c, uint32_t d) {
    asm volatile("stmatrix.sync.aligned.m8n8.x4.shared.b16 [%0], {%1, %2, %3, %4};" ::"r"(addr), "r"(a), "r"(b), "r"(c), "r"(d) : "memory");
}
__device__ __forceinline__ uint4 lds128(uint32_t a) {
    uint4 v; asm volatile("ld.shared.v4.b32 {%0, %1, %2, %3}, [%4];" : "=r"(v.x), "=r"(v.y), "=r"(v.z), "=r"(v.w) : "r"(a) : "memory"); return v;
}
__device__ __forceinline__ void sts128(uint32_t a, uint4 v) {
    asm volatile("st.shared.v4.b32 [%0], {%1, %2, %3, %4};" ::"r"(a), "r"(v.x), "r"(v.y), "r"(v.z), "r"(v.w) : "memory");
}
__device__ __forceinline__ void sts128x(uint32_t a, uint4 v) {
    asm volatile("st.shared.v4.b32 [%0], {%1, %2, %3, %4};" ::"r"(a), "r"(v.x), "r"(v.y), "r"(v.z), "r"(v.w) : "memory");
}
__device__ __forceinline__ uint4 ldg128(const void* p) {
    uint4 v; asm volatile("ld.global.nc.v4.b32 {%0, %1, %2, %3}, [%4];" : "=r"(v.x), "=r"(v.y), "=r"(v.z), "=r"(v.w) : "l"(p) : "memory"); return v;
}
__device__ __forceinline__ unsigned clk() { unsigned c; asm volatile("mov.u32 %0, %%clock;" : "=r"(c) :: "memory"); return c; }
__device__ __forceinline__ uint32_t mul_bf16x2(uint32_t a, uint32_t b) { uint32_t r; asm("mul.rn.bf16x2 %0, %1, %2;" : "=r"(r) : "r"(a), "r"(b)); return r; }
struct Lut { uint32_t lo[4], hi[4]; };
__device__ __forceinline__ uint32_t prmt(uint32_t a, uint32_t b, uint32_t s) { uint32_t r; asm("prmt.b32 %0, %1, %2, %3;" : "=r"(r) : "r"(a), "r"(b), "r"(s)); return r; }
__device__ __forceinline__ uint32_t pack4(const uint4& q) {
    uint32_t ab, cd, p;
    asm volatile("mad.lo.u32 %0, %1, 16, %2;" : "=r"(ab) : "r"(q.y), "r"(q.x));
    asm volatile("mad.lo.u32 %0, %1, 16, %2;" : "=r"(cd) : "r"(q.w), "r"(q.z));
    asm volatile("mad.lo.u32 %0, %1, 256, %2;" : "=r"(p) : "r"(cd), "r"(ab));
    return p;
}
__device__ __forceinline__ void lookup4(uint32_t p, const Lut& t, uint32_t& w01, uint32_t& w23) {
    const uint32_t t8 = p & 0x8888u, s7 = p & 0x7777u;
    const uint32_t sel = (t8 >> 1) + 0x3210u;
    const uint32_t lo = prmt(prmt(t.lo[0], t.lo[1], p), prmt(t.lo[2], t.lo[3], s7), sel);
    const uint32_t hi = prmt(prmt(t.hi[0], t.hi[1], p), prmt(t.hi[2], t.hi[3], s7), sel);
    w01 = prmt(lo, hi, 0x5140);
    w23 = prmt(lo, hi, 0x7362);
}
__device__ __forceinline__ uint4 dequant8(uint32_t p0, uint32_t p1, const uint4& sc, const Lut& tu) {
    uint4 r;
    const Lut& t = tu;
    lookup4(p0, t, r.x, r.y);
    lookup4(p1, t, r.z, r.w);
    r.x = mul_bf16x2(r.x, sc.x); r.y = mul_bf16x2(r.y, sc.y); r.z = mul_bf16x2(r.z, sc.z); r.w = mul_bf16x2(r.w, sc.w);
    return r;
}
__device__ __forceinline__ void fence_async_smem() { asm volatile("fence.proxy.async.shared::cta;" ::: "memory"); }

template <int SCALE_D, int BHI>
__device__ __forceinline__ void wgmma224(float (&d)[112], uint32_t descA, uint32_t descB) {
    asm volatile(
        "{\n.reg .pred p;\n.reg .b64 da, db;\nsetp.ne.b32 p, %114, 0;\n"
        "mov.b64 da, {%112, 0x40000040};\nmov.b64 db, {%113, %115};\n"
        "wgmma.mma_async.sync.aligned.m64n224k16.f32.bf16.bf16 "
        "{%0, %1, %2, %3, %4, %5, %6, %7, %8, %9, %10, %11, %12, %13, %14, %15, "
        "%16, %17, %18, %19, %20, %21, %22, %23, %24, %25, %26, %27, %28, %29, %30, %31, "
        "%32, %33, %34, %35, %36, %37, %38, %39, %40, %41, %42, %43, %44, %45, %46, %47, "
        "%48, %49, %50, %51, %52, %53, %54, %55, %56, %57, %58, %59, %60, %61, %62, %63, "
        "%64, %65, %66, %67, %68, %69, %70, %71, %72, %73, %74, %75, %76, %77, %78, %79, "
        "%80, %81, %82, %83, %84, %85, %86, %87, %88, %89, %90, %91, %92, %93, %94, %95, "
        "%96, %97, %98, %99, %100, %101, %102, %103, %104, %105, %106, %107, %108, %109, %110, %111}, "
        "da, db, p, 1, 1, 0, 1;\n}\n"
        : "+f"(d[0]), "+f"(d[1]), "+f"(d[2]), "+f"(d[3]), "+f"(d[4]), "+f"(d[5]), "+f"(d[6]), "+f"(d[7]),
          "+f"(d[8]), "+f"(d[9]), "+f"(d[10]), "+f"(d[11]), "+f"(d[12]), "+f"(d[13]), "+f"(d[14]), "+f"(d[15]),
          "+f"(d[16]), "+f"(d[17]), "+f"(d[18]), "+f"(d[19]), "+f"(d[20]), "+f"(d[21]), "+f"(d[22]), "+f"(d[23]),
          "+f"(d[24]), "+f"(d[25]), "+f"(d[26]), "+f"(d[27]), "+f"(d[28]), "+f"(d[29]), "+f"(d[30]), "+f"(d[31]),
          "+f"(d[32]), "+f"(d[33]), "+f"(d[34]), "+f"(d[35]), "+f"(d[36]), "+f"(d[37]), "+f"(d[38]), "+f"(d[39]),
          "+f"(d[40]), "+f"(d[41]), "+f"(d[42]), "+f"(d[43]), "+f"(d[44]), "+f"(d[45]), "+f"(d[46]), "+f"(d[47]),
          "+f"(d[48]), "+f"(d[49]), "+f"(d[50]), "+f"(d[51]), "+f"(d[52]), "+f"(d[53]), "+f"(d[54]), "+f"(d[55]),
          "+f"(d[56]), "+f"(d[57]), "+f"(d[58]), "+f"(d[59]), "+f"(d[60]), "+f"(d[61]), "+f"(d[62]), "+f"(d[63]),
          "+f"(d[64]), "+f"(d[65]), "+f"(d[66]), "+f"(d[67]), "+f"(d[68]), "+f"(d[69]), "+f"(d[70]), "+f"(d[71]),
          "+f"(d[72]), "+f"(d[73]), "+f"(d[74]), "+f"(d[75]), "+f"(d[76]), "+f"(d[77]), "+f"(d[78]), "+f"(d[79]),
          "+f"(d[80]), "+f"(d[81]), "+f"(d[82]), "+f"(d[83]), "+f"(d[84]), "+f"(d[85]), "+f"(d[86]), "+f"(d[87]),
          "+f"(d[88]), "+f"(d[89]), "+f"(d[90]), "+f"(d[91]), "+f"(d[92]), "+f"(d[93]), "+f"(d[94]), "+f"(d[95]),
          "+f"(d[96]), "+f"(d[97]), "+f"(d[98]), "+f"(d[99]), "+f"(d[100]), "+f"(d[101]), "+f"(d[102]), "+f"(d[103]),
          "+f"(d[104]), "+f"(d[105]), "+f"(d[106]), "+f"(d[107]), "+f"(d[108]), "+f"(d[109]), "+f"(d[110]), "+f"(d[111])
        : "r"(descA), "r"(descB), "n"(SCALE_D), "n"(BHI));
}

template <int SCALE_D, int BHI>
__device__ __forceinline__ void wgmma128(float (&d)[64], uint32_t descA, uint32_t descB) {
    asm volatile(
        "{\n.reg .pred p;\n.reg .b64 da, db;\nsetp.ne.b32 p, %66, 0;\n"
        "mov.b64 da, {%64, 0x40000040};\nmov.b64 db, {%65, %67};\n"
        "wgmma.mma_async.sync.aligned.m64n128k16.f32.bf16.bf16 "
        "{%0, %1, %2, %3, %4, %5, %6, %7, %8, %9, %10, %11, %12, %13, %14, %15, "
        "%16, %17, %18, %19, %20, %21, %22, %23, %24, %25, %26, %27, %28, %29, %30, %31, "
        "%32, %33, %34, %35, %36, %37, %38, %39, %40, %41, %42, %43, %44, %45, %46, %47, "
        "%48, %49, %50, %51, %52, %53, %54, %55, %56, %57, %58, %59, %60, %61, %62, %63}, "
        "da, db, p, 1, 1, 0, 1;\n}\n"
        : "+f"(d[0]), "+f"(d[1]), "+f"(d[2]), "+f"(d[3]), "+f"(d[4]), "+f"(d[5]), "+f"(d[6]), "+f"(d[7]),
          "+f"(d[8]), "+f"(d[9]), "+f"(d[10]), "+f"(d[11]), "+f"(d[12]), "+f"(d[13]), "+f"(d[14]), "+f"(d[15]),
          "+f"(d[16]), "+f"(d[17]), "+f"(d[18]), "+f"(d[19]), "+f"(d[20]), "+f"(d[21]), "+f"(d[22]), "+f"(d[23]),
          "+f"(d[24]), "+f"(d[25]), "+f"(d[26]), "+f"(d[27]), "+f"(d[28]), "+f"(d[29]), "+f"(d[30]), "+f"(d[31]),
          "+f"(d[32]), "+f"(d[33]), "+f"(d[34]), "+f"(d[35]), "+f"(d[36]), "+f"(d[37]), "+f"(d[38]), "+f"(d[39]),
          "+f"(d[40]), "+f"(d[41]), "+f"(d[42]), "+f"(d[43]), "+f"(d[44]), "+f"(d[45]), "+f"(d[46]), "+f"(d[47]),
          "+f"(d[48]), "+f"(d[49]), "+f"(d[50]), "+f"(d[51]), "+f"(d[52]), "+f"(d[53]), "+f"(d[54]), "+f"(d[55]),
          "+f"(d[56]), "+f"(d[57]), "+f"(d[58]), "+f"(d[59]), "+f"(d[60]), "+f"(d[61]), "+f"(d[62]), "+f"(d[63])
        : "r"(descA), "r"(descB), "n"(SCALE_D), "n"(BHI));
}

template <int SCALE_D, int BHI>
__device__ __forceinline__ void wgmma96(float (&d)[48], uint32_t descA, uint32_t descB) {
    asm volatile(
        "{\n.reg .pred p;\n.reg .b64 da, db;\nsetp.ne.b32 p, %50, 0;\n"
        "mov.b64 da, {%48, 0x40000040};\nmov.b64 db, {%49, %51};\n"
        "wgmma.mma_async.sync.aligned.m64n96k16.f32.bf16.bf16 "
        "{%0, %1, %2, %3, %4, %5, %6, %7, %8, %9, %10, %11, %12, %13, %14, %15, "
        "%16, %17, %18, %19, %20, %21, %22, %23, %24, %25, %26, %27, %28, %29, %30, %31, "
        "%32, %33, %34, %35, %36, %37, %38, %39, %40, %41, %42, %43, %44, %45, %46, %47}, "
        "da, db, p, 1, 1, 0, 1;\n}\n"
        : "+f"(d[0]), "+f"(d[1]), "+f"(d[2]), "+f"(d[3]), "+f"(d[4]), "+f"(d[5]), "+f"(d[6]), "+f"(d[7]),
          "+f"(d[8]), "+f"(d[9]), "+f"(d[10]), "+f"(d[11]), "+f"(d[12]), "+f"(d[13]), "+f"(d[14]), "+f"(d[15]),
          "+f"(d[16]), "+f"(d[17]), "+f"(d[18]), "+f"(d[19]), "+f"(d[20]), "+f"(d[21]), "+f"(d[22]), "+f"(d[23]),
          "+f"(d[24]), "+f"(d[25]), "+f"(d[26]), "+f"(d[27]), "+f"(d[28]), "+f"(d[29]), "+f"(d[30]), "+f"(d[31]),
          "+f"(d[32]), "+f"(d[33]), "+f"(d[34]), "+f"(d[35]), "+f"(d[36]), "+f"(d[37]), "+f"(d[38]), "+f"(d[39]),
          "+f"(d[40]), "+f"(d[41]), "+f"(d[42]), "+f"(d[43]), "+f"(d[44]), "+f"(d[45]), "+f"(d[46]), "+f"(d[47])
        : "r"(descA), "r"(descB), "n"(SCALE_D), "n"(BHI));
}

__device__ __forceinline__ uint32_t opq(uint32_t v) { asm volatile("" : "+r"(v)); return v; }
template <int I> struct IC { static constexpr int value = I; };
template <int B, int E, class F> __device__ __forceinline__ void static_for(F&& f) {
    if constexpr (B < E) { f(IC<B>{}); static_for<B + 1, E>(f); }
}

__device__ __forceinline__ void tma_store_2d(const CUtensorMap* tm, uint32_t src, int c0, int c1) {
    asm volatile("cp.async.bulk.tensor.2d.global.shared::cta.bulk_group [%0, {%2, %3}], [%1];" ::"l"(tm), "r"(src), "r"(c0), "r"(c1) : "memory");
}
__device__ __forceinline__ void bulk_store(void* dst, uint32_t src, uint32_t bytes) {
    asm volatile("cp.async.bulk.global.shared::cta.bulk_group [%0], [%1], %2;" ::"l"(dst), "r"(src), "r"(bytes) : "memory");
}
__device__ __forceinline__ void bulk_commit() { asm volatile("cp.async.bulk.commit_group;" ::: "memory"); }
template <int N> __device__ __forceinline__ void bulk_wait_read() { asm volatile("cp.async.bulk.wait_group.read %0;" ::"n"(N) : "memory"); }
__device__ __forceinline__ void bar_arrive(int id) { asm volatile("bar.arrive %0, 256;" ::"r"(id) : "memory"); }
__device__ __forceinline__ void bar_sync(int id) { asm volatile("bar.sync %0, 256;" ::"r"(id) : "memory"); }
template <int NC, int OFF, int N>
__device__ __forceinline__ void stage_cols(const float (&acc)[N], uint32_t stg) {
    int lane; asm volatile("mov.u32 %0, %%laneid;" : "=r"(lane));
    const int r = lane & 15;
    const uint32_t a0 = NC == 64 ? stg + r * 128 + (((lane >> 4) ^ (r & 7)) << 4) : stg + r * 64 + (((lane >> 4) ^ ((r >> 1) & 3)) << 4);
#pragma unroll
    for (int j = 0; j < NC / 16; j++) {
        const int i = OFF + 8 * j;
        stmatrix_x4(a0 ^ (j * 32), pack_bf16(acc[i], acc[i + 1]), pack_bf16(acc[i + 2], acc[i + 3]), pack_bf16(acc[i + 4], acc[i + 5]), pack_bf16(acc[i + 6], acc[i + 7]));
    }
}
__device__ __forceinline__ void send(uint32_t stg, const CUtensorMap* tmo, int col, int row) {
    fence_async_smem();
    __syncwarp();
    if (elect()) { tma_store_2d(tmo, stg, col, row); bulk_commit(); }
    __syncwarp();
}

__host__ __device__ constexpr int fconv(int g, int s) {
    return s + (s < 16 ? (int)(((g ? LEAD1 : LEAD0) >> (60 - 4 * s)) & 15) : 6);
}
__host__ __device__ constexpr int sub_of(int g, int b) { int s = -1; while (fconv(g, s + 1) <= b) s++; return s; }
__host__ __device__ constexpr int sub_min(int b) { return sub_of(0, b) < sub_of(1, b) ? sub_of(0, b) : sub_of(1, b); }
__host__ __device__ constexpr int sub_max(int b) { return sub_of(0, b) > sub_of(1, b) ? sub_of(0, b) : sub_of(1, b); }
__host__ __device__ constexpr int hmode(int u) { return u <= 1 ? 1 : u < HM1 ? 0 : u < HM2 ? 1 : u < HM3 ? 2 : 3; }
__host__ __device__ constexpr int t7(int v) { return sub_max(2 * v + 1) + (hmode(v) == 2 ? 0 : 1); }
__host__ __device__ constexpr int t7b(int b) { return sub_max(b) + (sub_min(b + 1) == sub_max(b) ? 0 : 1); }
__host__ __device__ constexpr int xunit(int i) { int v = 0; while (sub_min(2 * v + 1) < 4 * i - 7) v++; return v; }
__host__ __device__ constexpr int rslot(int u) { return (2 * u) % 3; }
__host__ __device__ constexpr int rpar(int u) { return (u / 3 - (u % 3 == 0)) & 1; }
__host__ __device__ constexpr int sslot(int c) { return c < 3 ? c + 3 : c % 3; }

__global__ void __cluster_dims__(2, 1, 1) __launch_bounds__(256, 1)
nf4_gemm_kernel(const int* __restrict__ qw, const __nv_bfloat16* __restrict__ cb, const __nv_bfloat16* __restrict__ absmax,
                uint8_t* __restrict__ wimg, unsigned* __restrict__ gflag,
                const __grid_constant__ CUtensorMap tmx, const __grid_constant__ CUtensorMap tmq, const __grid_constant__ CUtensorMap tmo64,
                const __grid_constant__ CUtensorMap tmo32, const __grid_constant__ CUtensorMap tmqp, const __grid_constant__ CUtensorMap tmx16,
                const __grid_constant__ CUtensorMap tmx64, const __grid_constant__ CUtensorMap tmq1) {
    extern __shared__ __align__(1024) uint8_t smem[];
    const uint32_t sbase = smem_u32(smem);
    const int rank = blockIdx.x & 1;
    const int cid = blockIdx.x >> 1;
    const int mt = (MAPM == 0 ? cid >> 4 : MAPM == 1 ? cid & 3 : MAPM == 2 ? (cid >> 1) & 3 : MAPM == 3 ? (cid >> 2) & 3 : (cid >> 3) & 3) * 2 + rank;
    const int nt = MAPM == 0 ? cid & 15 : MAPM == 1 ? cid >> 2 : MAPM == 2 ? (cid & 1) + (cid >> 3) * 2 : MAPM == 3 ? (cid & 3) + (cid >> 4) * 4 : (cid & 7) + (cid >> 5) * 8;
    const int lane = threadIdx.x & 31;
    const unsigned tstart = clk();
    uint4 q[4], c0, c1;
    uint2 sf;
    if (threadIdx.x < 224) {
        const int col = nt * BN + (threadIdx.x >> 5) * 32 + (lane & 7) * 4;
        const int* p = qw + (rank * 8 + (lane >> 3)) * N_ + col;
        q[0] = ldg128(p); q[1] = ldg128(p + 4 * N_);
        q[2] = ldg128(p + 16 * N_); q[3] = ldg128(p + 20 * N_);
        asm volatile("ld.global.nc.v2.b32 {%0, %1}, [%2];" : "=r"(sf.x), "=r"(sf.y) : "l"(absmax + col) : "memory");
        c0 = ldg128(cb); c1 = ldg128(cb + 8);
    }
    const int warp = __shfl_sync(~0u, (int)(threadIdx.x >> 5), 0);
    const int wg = warp >> 2;
    const uint32_t bars = sbase + BAR_OFF;
    const uint32_t fullW = bars, rawfull = bars + 48, written = bars + 72, xbar = bars + 96, gbar = bars + 112 + wg * 24;
    const uint32_t x1bar = bars + 160, rawh = bars + 176 - 8, ebar = bars + 200;
    const uint32_t wbase = sbase + W_OFF;
    TS_INIT();
    __syncwarp();
    TSW(0, 0);

    const int pair = mt >> 1;
    auto chunk = [&](int i) { return i < GUEST ? i : i == GUEST ? 12 + pair : i <= 12 ? i - 1 : 12 + ((pair + i) & 3); };
    unsigned* flag = gflag + nt * 32;
    uint8_t* wpan = wimg + nt * 8 * UNIT;
    auto load_x = [&](int i, int slot) {
        tma_load_2d(sbase + slot * 32768, &tmx, chunk(i) * 64, mt * BM, fullW + 16 * slot);
        tma_load_2d(sbase + slot * 32768 + 16384, &tmx, chunk(i) * 64, mt * BM + 128, fullW + 16 * slot);
    };
    auto load_sc = [&](int i, int ss, uint32_t bar) {
        bulk_load(sbase + SC_OFF + ss * SC_STRIDE, absmax + chunk(i) * N_ + nt * BN, 448, bar);
        bulk_load(sbase + SC_OFF + ss * SC_STRIDE + 448, flag, 16, bar);
    };
    auto load_raw = [&](int u, int slot) {
        mbar_expect_tx(rawfull + 8 * slot, UNIT);
        tma_load_5d(sbase + RAW_OFF + roff(slot), &tmq, 0, 0, nt * 7, rank, 4 * chunk(u >> 1) + 2 * (u & 1), rawfull + 8 * slot);
    };
    auto load_half = [&](int b, uint32_t more) {
        const uint32_t bar = (b & 1) ? rawfull + 8 * rslot(b >> 1) : rawh + 8 * (b >> 1);
        mbar_expect_tx(bar, 7168 + more);
        tma_load_5d(sbase + RAW_OFF + roff(rslot(b >> 1)) + (b & 1) * 7168, &tmq1, 0, 0, nt * 7, rank, b, bar);
    };
    auto load_xh = [&](int i, int g, uint32_t bar) {
        mbar_expect_tx(bar, 16384);
        tma_load_2d(sbase + i * 32768 + g * 16384, &tmx, i * 64, mt * BM + g * 128, bar);
    };
    auto prefetch = [&](int c) {
        if (PFQ && c + PFQ < 12) tma_prefetch_2d(&tmqp, nt * BN, (c + PFQ) * 64 + pair * 16 + rank * 8);
        if (PFQ && (unsigned)(c - PFG) < 4) tma_prefetch_2d(&tmqp, nt * BN, (12 + pair) * 64 + (c - PFG) * 16 + rank * 8);
        if (PFX && c + PFX < 16 && c + PFX > 2) tma_prefetch_2d(&tmx16, chunk(c + PFX) * 64, mt * BM + nt * 16);
    };
    if (warp == 7) {
        if (elect()) {
            mbar_init(xbar, 1); mbar_init(rawh + 8, 1); mbar_init(rawfull + 8 * rslot(1), 1); mbar_init(xbar + 8, 1);
            fence_async_smem();
            if (ORD1 == 0) load_xh(0, 0, xbar);
            load_half(2, 448);
            bulk_load(sbase + SC_OFF + sslot(0) * SC_STRIDE, absmax + nt * BN, 448, rawh + 8);
            if (ORD1 == 1) load_xh(0, 0, xbar);
            load_half(3, 0);
            if (ORD1 == 2) load_xh(0, 0, xbar);
            load_xh(0, 1, xbar + 8);
            mbar_init(rawfull + 8 * rslot(2), 1); mbar_init(rawfull + 8 * rslot(3), 1); mbar_init(rawh + 16, 1); mbar_init(rawh + 24, 1);
            mbar_init(x1bar, 1); mbar_init(x1bar + 8, 1);
#pragma unroll
            for (int s = 0; s < 2 * HM2; s++) if (hmode(s >> 1) == 0 || !(s & 1)) mbar_init(ebar + 8 * s, hmode(s >> 1) == 0 ? 1 : 7);
#pragma unroll
            for (int s = 2; s < HM1; s++) mbar_init(bars + 280 + 8 * s, 7);
            static_assert(HM1 <= 5 && HO == 0, "");
#pragma unroll
            for (int s = 0; s < NW; s++) { mbar_init(fullW + 8 * s, 1); if (s < HM2 && s != 4) mbar_arrive(fullW + 8 * s); }
#pragma unroll
            for (int s = 0; s < NR; s++) mbar_init(written + 8 * s, 7);
#pragma unroll
            for (int s = 0; s < 6; s++) mbar_init(bars + 112 + 8 * s, 4);
            asm volatile("fence.mbarrier_init.release.cluster;" ::: "memory");
            fence_async_smem();
            if ((sbase & 0xffffff) != 0x400) __trap();
        }
        __syncwarp();
        cluster_arrive();
        if (elect()) {
            asm volatile("prefetch.tensormap [%0];" ::"l"(&tmq) : "memory");
            asm volatile("prefetch.tensormap [%0];" ::"l"(&tmqp) : "memory");
            asm volatile("prefetch.tensormap [%0];" ::"l"(&tmx16) : "memory");
            asm volatile("prefetch.tensormap [%0];" ::"l"(&tmx64) : "memory");
            while (clk() - tstart < T2) { }
            load_half(4, 2 * SC_STRIDE); load_sc(1, sslot(1), rawh + 16); load_sc(2, sslot(2), rawh + 16); load_half(5, 0);
            while (clk() - tstart < T2B) { }
            load_xh(1, 0, x1bar);
            if (G2S == 0) { load_half(6, 0); load_half(7, 2 * SC_STRIDE); load_sc(3, sslot(3), rawfull + 8 * rslot(3)); load_sc(4, sslot(4), rawfull + 8 * rslot(3)); load_xh(1, 1, x1bar + 8); }
            while (clk() - tstart < T3) { }
#pragma unroll
            for (int c = 2 - PFQ; c < 0; c++) prefetch(c);
        }
        __syncwarp();
        if (TLPRO > 0) TSL(33);
        cluster_wait();
    } else {
        cluster_arrive();
    }
    const uint32_t rsrc = __shfl_sync(~0u, sbase + RAW_OFF + warp * 1024 + (lane & 7) * 128 + ((((lane >> 3) * 2) ^ (lane & 7)) << 4), lane);
    const uint32_t rsrc2 = __shfl_sync(~0u, rsrc ^ 16, lane);
    const uint32_t ssrc = sbase + SC_OFF + warp * 64;
    const int wpos = (ALIGNO && (nt & 1)) ? (0x73210546 >> (4 * warp)) & 7 : warp;
    const uint32_t wown = wbase + rank * 7168 + wpos * 512;
    const uint32_t wdst = __shfl_sync(~0u, wown + lane * 16, lane);
    auto get_sc = [&](int ss) { return lds128(((opq(wdst) >> 3) & 0x30) + ssrc + ss * SC_STRIDE); };
    const uint32_t whalf = wbase + rank * 7168;
    const uint32_t pwhalf = mapa(whalf, rank ^ 1), pfullW = mapa(fullW, rank ^ 1);
    Lut lut;
    uint4 sc;
    uint4 q0, q1;
    auto fetch = [&](int slot, int h) {
        q0 = lds128(rsrc + roff(slot) + h * 7168);
        q1 = lds128(rsrc2 + roff(slot) + h * 7168);
    };
    auto convert0 = [&](int rs, int ws, bool look, uint32_t lbar, uint32_t lpar, int tl = -1) {
        bool ok = true;
        if (look) ok = mbar_try(lbar, lpar);
        const uint32_t p0 = pack4(q0), p1 = pack4(q1);
        if (tl >= 0 && TLPRO == 0 && TSP == 0) TSL(3 * tl + 2);
        uint4 w = dequant8(p0, p1, sc, lut);
        asm volatile("" : "+r"(w.x), "+r"(w.y), "+r"(w.z), "+r"(w.w));
        if (tl >= 0 && TLPRO == 0 && TSP == 1) TSL(3 * tl + 2);
        if (look) mbar_wait1(lbar, lpar, ok);
        if (tl >= 0 && TLPRO == 0 && TSP == 2) TSL(3 * tl + 2);
        fetch(rs, 1);
        sts128x(wdst + ws * UNIT, w);
    };
    auto convert1 = [&](int rs, int ws, bool next, int rsn, int rpn, bool scales, int cs, bool stfirst, bool look, uint32_t lbar, uint32_t lpar, int tl = -1) {
        bool ok = true, ok2 = true;
        if (next) ok = mbar_try(rawfull + 8 * rsn, rpn);
        if (look) ok2 = mbar_try(lbar, lpar);
        const uint32_t p0 = pack4(q0), p1 = pack4(q1);
        if (tl >= 0 && TLPRO == 0 && TSP == 0) TSL(3 * tl + 2);
        uint4 w = dequant8(p0, p1, sc, lut);
        asm volatile("" : "+r"(w.x), "+r"(w.y), "+r"(w.z), "+r"(w.w));
        if (stfirst) {
            sts128x(wdst + ws * UNIT + 3584, w);
            __syncwarp();
            if (elect()) mbar_arrive(written + 8 * rs);
            __syncwarp();
        }
        if (tl >= 0 && TLPRO == 0 && TSP == 1) TSL(3 * tl + 2);
        if (look) mbar_wait2(rawfull + 8 * rsn, rpn, lbar, lpar, ok && ok2);
        else if (next) mbar_wait1(rawfull + 8 * rsn, rpn, ok);
        if (tl >= 0 && TLPRO == 0 && TSP == 2) TSL(3 * tl + 2);
        if (next) fetch(rsn, 0);
        if (!stfirst) {
            sts128x(wdst + ws * UNIT + 3584, w);
            __syncwarp();
            if (elect()) mbar_arrive(written + 8 * rs);
            __syncwarp();
        }
        if (scales) sc = get_sc(cs);
    };
    auto hand_over = [&](int v, int rs, uint32_t par, int ws, uint32_t tx, bool raw) {
        mbar_wait(written + 8 * rs, par);
        fence_async_smem();
        if (elect()) {
            if (raw) load_raw(v + NR, rs);
            copy_to_peer(pwhalf + ws * UNIT, whalf + ws * UNIT, 7168, pfullW + 8 * ws);
            mbar_expect_tx(fullW + 8 * ws, tx);
        }
        __syncwarp();
    };
    auto share = [&](int v, int ws) {
        if ((v >> 1) == GUEST) { bulk_store(wpan + (2 * pair + (v & 1)) * UNIT + rank * 7168, whalf + ws * UNIT, 7168); bulk_commit(); }
    };
    constexpr uint32_t TXO = 7168 + SC_STRIDE, TXE = 7168 + 32768;
    auto hand_over_c = [&](int v) {
        hand_over(v, rslot(v), (v / 3) & 1, v % NW, (v & 1) ? (v < 7 || v == 25 ? 7168 : TXO) : (v < 4 ? 7168 : TXE), v >= 1 && v + NR < NU);
    };
    auto raw_bar = [](int b) { return b < 8 && !(b & 1) ? 168 + 8 * (b >> 1) : b < 8 || !(b & 1) ? 48 + 8 * rslot(b >> 1) : -1; };
    auto raw_par = [](int b) { return b < 8 && !(b & 1) ? 0 : rpar(b >> 1); };
    auto w_bar = [](int s) { return hmode(s >> 1) == 0 ? 200 + 8 * s : (s & 1) ? -1 : hmode(s >> 1) == 1 ? 200 + 8 * s : 8 * ((s >> 1) % NW); };
    auto w_par = [](int s) { return hmode(s >> 1) < 2 ? 0 : ((s >> 1) / NW) & 1; };
    auto wait_slice = [&](int s, bool wok) {
        if (s == 0) { mbar_wait2(xbar + 8 * wg, 0, ebar, 0, wok); if (TLPRO > 0) TSL(32); return; }
        if (s == 4) mbar_wait2(x1bar + 8 * wg, 0, bars + w_bar(s), w_par(s), wok);
        else if (s == 8 && hmode(4) < 2) mbar_wait2(fullW + 32, 0, bars + w_bar(s), w_par(s), wok);
        else if (w_bar(s) >= 0) mbar_wait1(bars + w_bar(s), w_par(s), wok);
    };
    auto pass_on = [&](int b) {
        const int u = b >> 1, n = hmode(u) + 1;
        fence_async_smem();
        __syncwarp();
        if (elect()) {
            const uint32_t o = wpos * 512 + u * UNIT, eb = 8 * (n == 1 ? b : 2 * u);
            if (n == 2) copy_to_peer(pwhalf + o, whalf + o, 512, pfullW + 200 + eb);
            copy_to_peer(pwhalf + o + (b & 1) * 3584, whalf + o + (b & 1) * 3584, 512, pfullW + 200 + eb);
            mbar_expect_tx(ebar + eb, n * 512);
        }
        __syncwarp();
    };
    auto passes = [](int b) { return hmode(b >> 1) == 1 && (b & 1); };
    auto block = [&](int b, int sn) {
        const int u = b >> 1, h = b & 1;
        const bool pre = b >= PB || ((PM >> b) & 1), pren = (b + 1 >= PB || ((PM >> (b + 1)) & 1)) && b + 1 < 2 * NU;
        const bool war = !h && u >= NW, early_look = sn >= 0 && b - sn >= 2;
        bool ok1 = true, ok2 = true, ok3 = false;
        if (war) ok1 = mbar_try(written + 8 * rslot(u - 2), ((u - 2) / 3) & 1);
        if (pren && raw_bar(b + 1) >= 0) ok2 = mbar_try(bars + raw_bar(b + 1), raw_par(b + 1));
        if (sn >= 0 && w_bar(sn) >= 0) ok3 = mbar_try(bars + w_bar(sn), w_par(sn));
        if (sn == 4) ok3 &= mbar_try(x1bar + 8 * wg, 0);
        if (sn == 8 && hmode(4) < 2) ok3 &= mbar_try(fullW + 32, 0);
        uint4 r0, r1;
        if (pre) { r0 = q0; r1 = q1; }
        else {
            if (raw_bar(b) >= 0) mbar_wait(bars + raw_bar(b), raw_par(b));
            r0 = lds128(rsrc + roff(rslot(u)) + h * 7168); r1 = lds128(rsrc2 + roff(rslot(u)) + h * 7168);
            if (b == 4) sc = get_sc(sslot(1));
        }
        const uint32_t p0 = pack4(r0), p1 = pack4(r1);
        if (TLPRO == 2 && b >= TB && b < TB + 3) TSL(20 + 3 * (b - TB));
        if (b > DEF && passes(b - 1)) pass_on(b - 1);
        uint4 w = dequant8(p0, p1, sc, lut);
        asm volatile("" : "+r"(w.x), "+r"(w.y), "+r"(w.z), "+r"(w.w));
        if (war) mbar_wait1(written + 8 * rslot(u - 2), ((u - 2) / 3) & 1, ok1);
        const bool now = b < DEF && passes(b);
        if (now) { sts128(wdst + (u % NW) * UNIT + h * 3584, w); pass_on(b); }
        if (TLPRO == 2 && b >= TB && b < TB + 3) TSL(21 + 3 * (b - TB));
        if (early_look) wait_slice(sn, ok3);
        if (pren) {
            if (raw_bar(b + 1) >= 0) mbar_wait1(bars + raw_bar(b + 1), raw_par(b + 1), ok2);
            if (TLPRO == 2 && b >= TB && b < TB + 3) TSL(22 + 3 * (b - TB));
            fetch(rslot((b + 1) >> 1), h ^ 1);
        }
        if (!now) sts128(wdst + (u % NW) * UNIT + h * 3584, w);
        if (h || hmode(u) == 0) { __syncwarp(); if (elect()) mbar_arrive(h ? written + 8 * rslot(u) : bars + 280 + 8 * u); __syncwarp(); }
        if ((b & 3) == 3 && u + 1 < NU) sc = get_sc(sslot((b + 1) >> 2));
        if (sn >= 0 && !early_look) wait_slice(sn, ok3);
    };
    auto blocks = [&](auto A, auto B, int sn) {
        static_for<A.value, B.value>([&](auto I) { block(I.value, I.value == B.value - 1 ? sn : -1); });
        if (A.value == B.value) wait_slice(sn, false);
    };
    auto duties = [&](auto S) {
        constexpr int s = S.value;
        auto slab = [&](auto B) {
            constexpr int b = B.value, u = b >> 1;
            mbar_wait((b & 1) ? written + 8 * rslot(u) : bars + 280 + 8 * u, (b & 1) ? (u / 3) & 1 : 0);
            fence_async_smem();
            if (elect()) {
                copy_to_peer(pwhalf + u * UNIT + (b & 1) * 3584, whalf + u * UNIT + (b & 1) * 3584, 3584, pfullW + 200 + 8 * b);
                mbar_expect_tx(ebar + 8 * b, 3584);
                if (b & 1) load_raw(u + NR, rslot(u));
            }
            __syncwarp();
        };
        static_for<4, 2 * HM1>([&](auto B) { if constexpr (t7b(B.value) == s && sub_max(B.value) < s) slab(B); });
        static_for<1, 2 * C0 + 2>([&](auto V) {
            constexpr int v = V.value;
            if constexpr (hmode(v) != 0 && (t7(v) == s || (s == 0 && t7(v) < 0))) {
                if (hmode(v) >= 2) hand_over_c(v);
                else {
                    mbar_wait(written + 8 * rslot(v), (v / 3) & 1);
                    if (elect()) load_raw(v + NR, rslot(v));
                    __syncwarp();
                }
            }
        });
        if (elect()) {
            if (s == 0 && G2S) { load_half(6, 0); load_half(7, 2 * SC_STRIDE); load_sc(3, sslot(3), rawfull + 8 * rslot(3)); load_sc(4, sslot(4), rawfull + 8 * rslot(3)); }
            if (s == G2S - 1) load_xh(1, 1, x1bar + 8);
            if (s == X2AT) { if (HM2 > 4) mbar_expect_tx(fullW + 32, 32768); load_x(2, 2); }
            static_for<3, C0 + 2>([&](auto I) { if constexpr (t7(xunit(I.value)) + XLAG == s) load_x(I.value, I.value % 3); });
            if ((s & 3) == 1) { if (s >= 8) load_sc((s >> 2) + 3, (s >> 2) % 3, fullW + 8 * ((2 * (s >> 2) + 3) % NW)); prefetch(s >> 2); }
        }
        __syncwarp();
        static_for<4, 2 * HM1>([&](auto B) { if constexpr (t7b(B.value) == s && sub_max(B.value) == s) slab(B); });
    };
    static_assert(HM2 <= 6 && HM1 >= 1 && HM2 >= 3 && C0 < GUEST && t7(2 * C0 + 1) < 4 * C0 && t7(xunit(C0 + 1)) + XLAG < 4 * C0, "");
    bool ok0 = false;
    if (warp < 7) {
        lut.lo[0] = __byte_perm(c0.x, c0.y, 0x6420); lut.hi[0] = __byte_perm(c0.x, c0.y, 0x7531);
        lut.lo[1] = __byte_perm(c0.z, c0.w, 0x6420); lut.hi[1] = __byte_perm(c0.z, c0.w, 0x7531);
        lut.lo[2] = __byte_perm(c1.x, c1.y, 0x6420); lut.hi[2] = __byte_perm(c1.x, c1.y, 0x7531);
        lut.lo[3] = __byte_perm(c1.z, c1.w, 0x6420); lut.hi[3] = __byte_perm(c1.z, c1.w, 0x7531);
        const uint32_t d = wown + ((lane & 7) >> 1) * 128 + (lane >> 3) * 16 + (lane & 1) * 8;
#pragma unroll
        for (int j = 0; j < 4; j++) {
            uint32_t a, b;
            lookup4(pack4(q[j]), lut, a, b);
            asm volatile("st.shared.v2.b32 [%0], {%1, %2};" ::"r"(d + (j >> 1) * 3584 + (j & 1) * 64), "r"(mul_bf16x2(a, sf.x)), "r"(mul_bf16x2(b, sf.y)) : "memory");
        }
        if (TLPRO > 0) TSL(33);
        cluster_wait();
        pass_on(1);
        if (elect()) mbar_arrive(written + 8 * rslot(0));
        __syncwarp();
        if (TLPRO > 0) TSL(34);
        mbar_wait(rawh + 8, 0);
        const uint4 a0 = lds128(rsrc + roff(rslot(1))), a1 = lds128(rsrc2 + roff(rslot(1))), s0 = get_sc(sslot(0));
        mbar_wait(rawfull + 8 * rslot(1), 0);
        if (TLPRO == 2) TSL(29);
        const uint4 a2 = lds128(rsrc + roff(rslot(1)) + 7168), a3 = lds128(rsrc2 + roff(rslot(1)) + 7168);
        sts128(wdst + UNIT, dequant8(pack4(a0), pack4(a1), s0, lut));
        sts128(wdst + UNIT + 3584, dequant8(pack4(a2), pack4(a3), s0, lut));
        ok0 = mbar_try(xbar + 8 * wg, 0) & mbar_try(ebar, 0);
        pass_on(3);
        if (elect()) mbar_arrive(written + 8 * rslot(1));
        __syncwarp();
        if (PB == 4) { mbar_wait(rawh + 16, 0); fetch(rslot(2), 0); sc = get_sc(sslot(1)); }
        static_assert(fconv(0, 0) == 4 && fconv(1, 0) == 4 && PB >= 4 && DEF >= 4, "");
    }
    if (TLPRO > 0) TSL(31);
    wait_slice(0, ok0);

    float acc0[112], acc1[112];
    const uint32_t descA = ((0x400 + wg * 16384) >> 4) | (1u << 16);
    constexpr uint32_t descB = ((0x400 + W_OFF) >> 4) | ((7168u >> 4) << 16);
    auto mma = [&](int slot, int ks, int tl = -1) {
        const uint32_t da = opq(descA) + slot * (32768 >> 4) + ks * 2, db = descB + (2 * slot + (ks >> 1)) * (UNIT >> 4) + (ks & 1) * 224;
        if (tl >= 0 && TLPRO == 0) TSL(3 * tl);
        wgmma_fence();
        wgmma224<1, 8>(acc0, da, db); wgmma224<1, 8>(acc1, da + 512, db);
        wgmma_commit();
        wgmma_wait<2>();
        if (tl >= 0 && TLPRO == 0) TSL(3 * tl + 1);
    };
    static_for<0, 4 * C0>([&](auto S) {
        constexpr int s = S.value;
        constexpr int c = s >> 2;
        if (s == 0) {
            wgmma_fence();
            wgmma224<0, 8>(acc0, descA, descB); wgmma224<0, 8>(acc1, descA + 512, descB);
            wgmma_commit();
        } else mma(c % 3, s & 3);
        if (TLPRO > 0) TSL(s);
        constexpr int a0 = fconv(0, s), b0 = fconv(0, s + 1), a1 = fconv(1, s), b1 = fconv(1, s + 1);
        if (warp == 7) { duties(S); wait_slice(s + 1, false); }
        else if ((a0 == a1 && b0 == b1) || wg == 0) blocks(IC<a0>{}, IC<b0>{}, s + 1);
        else blocks(IC<a1>{}, IC<b1>{}, s + 1);
    });
    auto load_w = [&](int v, uint32_t dst, uint32_t bar) {
        mbar_expect_tx(bar, UNIT);
        bulk_load(dst, wpan + (2 * (chunk(v >> 1) - 12) + (v & 1)) * UNIT, UNIT, bar);
    };
    auto load_l = [&](int i, int slot, int g, uint32_t bar) {
        tma_load_2d(sbase + slot * 32768 + g * 16384, &tmx64, chunk(i) * 64, mt * BM + g * 128, bar);
        tma_load_2d(sbase + slot * 32768 + g * 16384 + 8192, &tmx64, chunk(i + 1) * 64, mt * BM + g * 128, bar);
    };
    static_assert(fconv(0, 4 * C0) == 4 * C0 + 6 && fconv(1, 4 * C0) == 4 * C0 + 6 && PB <= 4 * C0 + 6, "ramp must be over");
    {
        uint32_t ph = (C0 / 3) & 1;
#pragma unroll 1
        for (int cb = C0; cb < C1; cb += 3)
          static_for<0, 3>([&](auto I) {
            constexpr int cc = C0 + I.value;
            constexpr int j0 = cc % 3, j1 = (cc + 1) % 3, j2 = (cc + 2) % 3;
            const int c = cb + I.value;
            if (TLPRO > 0 && I.value == 0) TSL(c < 8 ? 36 : 37);
            mma(j0, 0, 4 * I.value + 0);
            if (TLPRO > 0) TSL(cb == TLIT ? 8 + 4 * I.value + 0 : 30);
            if (warp < 7) convert0(j0, 2 * j1 + 1, true, written + 8 * j2, ((2 * cc + 1) / 3) & 1, 4 * I.value);
            else hand_over(2 * c + 2, j1, ((2 * cc + 2) / 3) & 1, 2 * j1, TXE, true);
            mma(j0, 1, 4 * I.value + 1);
            if (TLPRO > 0) TSL(cb == TLIT ? 8 + 4 * I.value + 1 : 30);
            if (warp < 7) convert1(j0, 2 * j1 + 1, true, j2, rpar(2 * cc + 4), true, j2, STFIRST, true, fullW + 16 * j0 + 8, ph, 4 * I.value + 1);
            else {
                if (elect()) {
                    load_sc(c + 3, j0, fullW + 16 * j1 + 8);
                    prefetch(c);
                    share(2 * c + 2, 2 * j1);
                    if (c == GUEST + PUBD) {
                        asm volatile("cp.async.bulk.wait_group 0;" ::: "memory");
                        asm volatile("red.relaxed.gpu.global.add.u32 [%0], 1;" ::"l"(flag) : "memory");
                    }
                }
                __syncwarp();
                mbar_wait(fullW + 16 * j0 + 8, ph);
            }
            if (j1 == 0) asm volatile("xor.b32 %0, %0, 1;" : "+r"(ph));
            mma(j0, 2, 4 * I.value + 2);
            if (TLPRO > 0) TSL(cb == TLIT ? 8 + 4 * I.value + 2 : 30);
            if (warp < 7) convert0(j2, 2 * j2, true, written + 8 * j1, ((2 * cc + 2) / 3) & 1, 4 * I.value + 2);
            else {
                hand_over(2 * c + 3, j0, ((2 * cc + 3) / 3) & 1, 2 * j1 + 1, TXO, j0 != 1 || c < 10);
                if (j0 == 1 && c == 10) {
                    unsigned f0, f1;
                    asm volatile("ld.shared.u32 %0, [%1];" : "=r"(f0) : "r"(sbase + SC_OFF + sslot(1) * SC_STRIDE + 448) : "memory");
                    asm volatile("ld.shared.u32 %0, [%1];" : "=r"(f1) : "r"(sbase + SC_OFF + sslot(12) * SC_STRIDE + 448) : "memory");
                    asm volatile("{\n.reg .pred p;\n.reg .u32 n, d;\nmov.u32 n, 0;\nLAB_POLL:\nsub.u32 d, %0, %1;\nsetp.ge.u32 p, d, 8;\n@p bra.uni LAB_DONE;\n"
                                 "ld.relaxed.gpu.global.u32 %0, [%2];\nadd.u32 n, n, 1;\nsetp.lt.u32 p, n, 0x10000;\n@p bra.uni LAB_POLL;\nLAB_DONE:\n}\n"
                                 : "+r"(f1) : "r"(f0 & ~7u), "l"(flag) : "memory");
                    if (elect()) load_w(26, sbase + RAW_OFF + roff(rslot(23)), rawfull + 8 * rslot(23));
                    __syncwarp();
                }
            }
            mma(j0, 3, 4 * I.value + 3);
            if (TLPRO > 0) TSL(cb == TLIT ? 8 + 4 * I.value + 3 : 30);
            if (warp < 7) convert1(j2, 2 * j2, true, j1, rpar(2 * cc + 5), false, 0, STFIRST, true, fullW + 16 * j1, ph, 4 * I.value + 3);
            else {
                if (elect()) {
                    if (j0 == 1 && c == 10) { load_l(12, 0, 0, fullW); load_l(12, 0, 1, fullW); }
                    else load_x(c + 2, j2);
                    share(2 * c + 3, 2 * j1 + 1);
                }
                __syncwarp();
                mbar_wait(fullW + 16 * j1, ph);
            }
          });
    }
    static_assert(C1 == 11 && GUEST + PUBD < 9, "");
    mma(2, 0);
    if (warp < 7) block(50, -1);
    else {
        mbar_wait(written + 8 * rslot(24), 0);
        if (elect()) {
            load_w(27, sbase + RAW_OFF + roff(rslot(24)), rawfull + 8 * rslot(24));
            load_w(28, wbase + 2 * UNIT, fullW + 16);
        }
        __syncwarp();
        hand_over_c(24);
        TSX(7, 6);
    }
    mma(2, 1);
    if (warp < 7) block(51, 46);
    else {
        if (elect()) {
            asm volatile("prefetch.tensormap [%0];" ::"l"(&tmo64) : "memory");
            asm volatile("prefetch.tensormap [%0];" ::"l"(&tmo32) : "memory");
        }
        __syncwarp();
        mbar_wait(fullW + 8 * 5, 1);
        hand_over_c(25);
        if (elect()) {
            mbar_expect_tx(xbar, 16384); load_l(14, 1, 0, xbar);
            load_w(29, sbase + RAW_OFF + roff(rslot(25)), rawfull + 8 * rslot(25));
            load_w(30, wbase + 3 * UNIT, fullW + 24);
        }
        __syncwarp();
        TSX(7, 7);
    }
    if (wg == 1) bar_sync(8);
    mma(2, 2);
    if (warp == 7) {
        wgmma_wait<1>();
        mbar_wait(fullW, 0);
        if (elect()) { load_w(31, wbase + 4 * UNIT, fullW + 32); mbar_expect_tx(xbar + 8, 16384); load_l(14, 1, 1, xbar + 8); }
        __syncwarp();
    }
    mma(2, 3);
    if (wg == 0) bar_arrive(8);
    const uint32_t slice0 = sbase + wg * 16384 + (warp & 3) * 2048;
    auto slc = [&](int p) { return slice0 + (p >> 1) * 32768 + (p & 1) * 8192; };
    const int row0 = mt * BM + wg * 128 + (warp & 3) * 16, odd = ALIGNO ? nt & 1 : 0;
    const int colL = nt * BN + odd * 96, colA = nt * BN + (odd ? 32 : 128), colB = nt * BN + (odd ? 0 : 192);
    auto load_s = [&](int i, int p, uint32_t bar) { tma_load_2d(slc(p), &tmx16, chunk(i) * 64, row0 + 64, bar); };
    const uint32_t tA = opq(descA);
    auto stagger = [&](unsigned d) { if (d) { const unsigned t = clk() + (warp & 3) * d; while ((int)(clk() - t) < 0) { } } };
    unsigned rt[16];
    mbar_wait(fullW, 0);
    wgmma_wait<0>();
    RT(0);
    TSX(wg * 4, 8 + wg);
    float lo0[64], hi0[48], lo1[64], hi1[48];
#pragma unroll
    for (int i = 0; i < 64; i++) { asm volatile("mov.b32 %0, %1;" : "=f"(lo0[i]) : "f"(acc0[i])); asm volatile("mov.b32 %0, %1;" : "=f"(lo1[i]) : "f"(acc1[i])); }
#pragma unroll
    for (int i = 0; i < 48; i++) { asm volatile("mov.b32 %0, %1;" : "=f"(hi0[i]) : "f"(acc0[64 + i])); asm volatile("mov.b32 %0, %1;" : "=f"(hi1[i]) : "f"(acc1[64 + i])); }
    auto udesc = [](int s) {
        const int v = 24 + (s >> 1);
        const int off = v == 26 ? RAW_OFF + roff(rslot(23)) : v == 27 ? RAW_OFF + roff(rslot(24)) : v == 29 ? RAW_OFF + roff(rslot(25))
                      : W_OFF + (v < 26 ? v - 24 : v == 28 ? 2 : v - 27) * UNIT;
        return (uint32_t)(((0x400 + off) >> 4) | ((7168u >> 4) << 16)) + (s & 1) * 224;
    };
    auto tdesc = [&](int p, int s) { return tA + (p >> 1) * (32768 >> 4) + (p & 1) * 512 + (s & 3) * 2; };
    auto ldesc = [&](int s) { return tdesc(s >> 2, s); };
    auto gdesc = [&](int s) { return tdesc(((s >> 2) + 4) % 6, s); };
    if (wg == 1) { mbar_wait(xbar + 8, 1); bar_sync(1); }
    static_for<0, 8>([&](auto V) {
        constexpr int v = 24 + (V.value == 0 || V.value > 3 ? V.value : V.value == 3 ? 1 : V.value + 1), s = 2 * (v - 24);
        if (v == 26) mbar_wait2(rawfull + 8 * rslot(23), rpar(26), rawfull + 8 * rslot(24), rpar(27), wg);
        else if (v == 29) mbar_wait1(rawfull + 8 * rslot(25), rpar(28), wg);
        else if (v == 28) mbar_wait2(fullW + 16, 0, xbar, 1, wg);
        else if (v != 24 && v != 27) mbar_wait1(fullW + 8 * (v == 25 ? 1 : v - 27), 0, wg);
        if (v == 28) TSX(wg * 4, 12 + wg);
        if (v == 31) TSX(wg * 4, 10 + wg);
        wgmma_fence();
        wgmma96<1, 8>(hi0, ldesc(s), udesc(s) + 128);
        wgmma96<1, 8>(hi0, ldesc(s + 1), udesc(s + 1) + 128);
    });
    wgmma_commit();
    bar_arrive(1 + wg);
    cluster_arrive();
    wgmma_wait<0>();
    RT(1);
    stagger(SG0);
    stage_cols<64, 0>(hi0, slc(4)); send(slc(4), &tmo64, colA, row0);
    stage_cols<32, 32>(hi0, slc(5));
    RT(2);
    bar_sync(2 + wg);
    RT(3);
    wgmma_fence();
#pragma unroll
    for (int s = 0; s < G1; s++) wgmma128<1, 8>(lo0, ldesc(s), udesc(s));
    wgmma_commit();
    if (GS) {
        if (elect()) { bulk_wait_read<0>(); mbar_expect_tx(gbar, 2048); load_s(12, 4, gbar); }
        __syncwarp();
    }
    send(slc(5), &tmo32, colB, row0);
    wgmma_fence();
#pragma unroll
    for (int s = G1; s < 16; s++) wgmma128<1, 8>(lo0, ldesc(s), udesc(s));
    wgmma_commit();
    bar_arrive(3 + wg);
    RT(4);
    if (elect()) {
        if (GS) { mbar_expect_tx(gbar + 16, 2048); bulk_wait_read<0>(); load_s(13, 5, gbar + 16); }
        else { mbar_expect_tx(gbar, 4096); bulk_wait_read<0>(); load_s(12, 4, gbar); load_s(13, 5, gbar); }
    }
    __syncwarp();
    TSX(wg * 4, 58 + wg);
    wgmma_wait<0>();
    RT(5);
    stagger(SG1);
    stage_cols<64, 0>(lo0, slc(2));
    if (GL == 0) {
        if (elect()) { mbar_expect_tx(gbar + 8, 4096); load_s(14, 0, gbar + 8); load_s(15, 1, gbar + 8); }
        __syncwarp();
    }
    const bool okg = mbar_try(gbar, 0), okg2 = !GS || mbar_try(gbar + 16, 0);
    send(slc(2), &tmo64, colL, row0);
    TSX(wg * 4, 48 + wg);
    if (GR == 0) mbar_wait1(gbar, 0, okg);
    stage_cols<64, 32>(lo0, slc(3));
    if (GL == 1) {
        if (elect()) { mbar_expect_tx(gbar + 8, 4096); load_s(14, 0, gbar + 8); load_s(15, 1, gbar + 8); }
        __syncwarp();
    }
    if (GR == 1) mbar_wait1(gbar, 0, okg);
    if (E1 == 0) send(slc(3), &tmo64, colL + 64, row0);
    RT(6);
    bar_sync(4 + wg);
    RT(7);
    wgmma_fence();
#pragma unroll
    for (int s = 0; s < 4; s++) wgmma128<1, 8>(lo1, gdesc(s), udesc(s));
    if (GS) { mbar_wait1(gbar + 16, 0, okg2); wgmma_fence(); }
#pragma unroll
    for (int s = 4; s < 8; s++) wgmma128<1, 8>(lo1, gdesc(s), udesc(s));
    wgmma_commit();
    if (E1 == 1) send(slc(3), &tmo64, colL + 64, row0);
    mbar_wait(gbar + 8, 0);
    TSX(wg * 4, 52 + wg);
    wgmma_fence();
#pragma unroll
    for (int s = 8; s < 16; s++) wgmma128<1, 8>(lo1, gdesc(s), udesc(s));
    wgmma_commit();
    bar_arrive(5 + wg);
    RT(8);
    if (elect()) bulk_wait_read<0>();
    __syncwarp();
    if (E1 == 2) send(slc(3), &tmo64, colL + 64, row0);
    wgmma_wait<0>();
    RT(9);
    stagger(SG2);
    stage_cols<64, 0>(lo1, slc(2)); send(slc(2), &tmo64, colL, row0 + 64);
    if (E1 == 2) { if (elect()) bulk_wait_read<1>(); __syncwarp(); }
    stage_cols<64, 32>(lo1, slc(3));
    if (HO && wg == 1) { __syncwarp(); if (elect()) mbar_arrive(ebar + 8 * (2 * (warp & 3) + 1)); __syncwarp(); }
    if (E2 == 0 && wg == 0) send(slc(3), &tmo64, colL + 64, row0 + 64);
    RT(10);
    bar_sync(6 + wg);
    RT(11);
    wgmma_fence();
#pragma unroll
    for (int s = 0; s < G3; s++) wgmma96<1, 8>(hi1, gdesc(s), udesc(s) + 128);
    wgmma_commit();
    if (HO ? wg == 0 : (E2 == 1 || wg == 1)) send(slc(3), &tmo64, colL + 64, row0 + 64);
    wgmma_fence();
#pragma unroll
    for (int s = G3; s < 16; s++) wgmma96<1, 8>(hi1, gdesc(s), udesc(s) + 128);
    wgmma_commit();
    if (wg == 0) bar_arrive(7);
    RT(12);
    wgmma_wait<0>();
    RT(13);
    stagger(wg ? SG4 : SG3);
    if (HO == 1 && wg == 0) { mbar_wait(ebar + 8 * (2 * warp + 1), 0); send(slc(3) + 16384, &tmo64, colL + 64, row0 + 64 + 128); }
    stage_cols<64, 0>(hi1, slc(1));
    if (HO == 2 && wg == 0) { mbar_wait(ebar + 8 * (2 * warp + 1), 0); send(slc(3) + 16384, &tmo64, colL + 64, row0 + 64 + 128); }
    if (E3 == 0) send(slc(1), &tmo64, colA, row0 + 64);
    stage_cols<32, 32>(hi1, slc(5));
    if (E3 == 0) send(slc(5), &tmo32, colB, row0 + 64);
    else {
        fence_async_smem();
        __syncwarp();
        if (elect()) { tma_store_2d(&tmo64, slc(1), colA, row0 + 64); tma_store_2d(&tmo32, slc(5), colB, row0 + 64); bulk_commit(); }
        __syncwarp();
    }
    RT(14);
    if (elect()) bulk_wait_read<0>();
    __syncwarp();
    RT(15);
    TSW(wg * 4, 38 + wg);
    TS_DUMP();
    TL_DUMP();
    cluster_wait();
}

typedef CUresult (*EncodeFn)(CUtensorMap*, CUtensorMapDataType, cuuint32_t, void*, const cuuint64_t*, const cuuint64_t*,
                             const cuuint32_t*, const cuuint32_t*, CUtensorMapInterleave, CUtensorMapSwizzle,
                             CUtensorMapL2promotion, CUtensorMapFloatOOBfill);

extern "C" void kernel_launch(void* const* d_in, const int* in_sizes, int n_in, void* d_out, int out_size) {
    const __nv_bfloat16* x = (const __nv_bfloat16*)d_in[0];
    const int* qw = (const int*)d_in[1];
    const __nv_bfloat16* cb = (const __nv_bfloat16*)d_in[2];
    const __nv_bfloat16* absmax = (const __nv_bfloat16*)d_in[3];
    static EncodeFn encode = nullptr;
    static void *wimg = nullptr, *gflag = nullptr;
    if (!encode) {
        cudaGetSymbolAddress(&wimg, g_wimg);
        cudaGetSymbolAddress(&gflag, g_flag);
        void* fn = nullptr;
        cudaDriverEntryPointQueryResult qr;
        cudaGetDriverEntryPoint("cuTensorMapEncodeTiled", &fn, cudaEnableDefault, &qr);
        encode = (EncodeFn)fn;
        cudaFuncSetAttribute(nf4_gemm_kernel, cudaFuncAttributeMaxDynamicSharedMemorySize, SMEM_BYTES);
    }
    CUtensorMap tmx, tmq, tmo64, tmo32, tmqp, tmx16, tmx64, tmq1;
    {
        cuuint64_t dims[2] = {(cuuint64_t)K_, (cuuint64_t)M_};
        cuuint64_t strides[1] = {(cuuint64_t)K_ * 2};
        cuuint32_t box[2] = {64, 128};
        cuuint32_t es[2] = {1, 1};
        encode(&tmx, CU_TENSOR_MAP_DATA_TYPE_BFLOAT16, 2, (void*)x, dims, strides, box, es, CU_TENSOR_MAP_INTERLEAVE_NONE,
               CU_TENSOR_MAP_SWIZZLE_128B, CU_TENSOR_MAP_L2_PROMOTION_L2_128B, CU_TENSOR_MAP_FLOAT_OOB_FILL_NONE);
        box[1] = 64;
        encode(&tmx64, CU_TENSOR_MAP_DATA_TYPE_BFLOAT16, 2, (void*)x, dims, strides, box, es, CU_TENSOR_MAP_INTERLEAVE_NONE,
               CU_TENSOR_MAP_SWIZZLE_128B, CU_TENSOR_MAP_L2_PROMOTION_L2_128B, CU_TENSOR_MAP_FLOAT_OOB_FILL_NONE);
        box[1] = 16;
        encode(&tmx16, CU_TENSOR_MAP_DATA_TYPE_BFLOAT16, 2, (void*)x, dims, strides, box, es, CU_TENSOR_MAP_INTERLEAVE_NONE,
               CU_TENSOR_MAP_SWIZZLE_128B, CU_TENSOR_MAP_L2_PROMOTION_L2_128B, CU_TENSOR_MAP_FLOAT_OOB_FILL_NONE);
    }
    {
        cuuint64_t dims[5] = {32, 8, (cuuint64_t)(N_ / 32), 2, (cuuint64_t)(K_ / 16)};
        cuuint64_t strides[4] = {(cuuint64_t)N_ * 4, 128, (cuuint64_t)N_ * 4 * 8, (cuuint64_t)N_ * 4 * 16};
        cuuint32_t box[5] = {32, 8, 7, 1, 2};
        cuuint32_t es[5] = {1, 1, 1, 1, 1};
        encode(&tmq, CU_TENSOR_MAP_DATA_TYPE_INT32, 5, (void*)qw, dims, strides, box, es, CU_TENSOR_MAP_INTERLEAVE_NONE,
               CU_TENSOR_MAP_SWIZZLE_128B, CU_TENSOR_MAP_L2_PROMOTION_L2_128B, CU_TENSOR_MAP_FLOAT_OOB_FILL_NONE);
        box[4] = 1;
        encode(&tmq1, CU_TENSOR_MAP_DATA_TYPE_INT32, 5, (void*)qw, dims, strides, box, es, CU_TENSOR_MAP_INTERLEAVE_NONE,
               CU_TENSOR_MAP_SWIZZLE_128B, CU_TENSOR_MAP_L2_PROMOTION_L2_128B, CU_TENSOR_MAP_FLOAT_OOB_FILL_NONE);
        cuuint64_t dims2[2] = {(cuuint64_t)N_, (cuuint64_t)K_};
        cuuint32_t box2[2] = {224, 8};
        encode(&tmqp, CU_TENSOR_MAP_DATA_TYPE_INT32, 2, (void*)qw, dims2, strides, box2, es, CU_TENSOR_MAP_INTERLEAVE_NONE,
               CU_TENSOR_MAP_SWIZZLE_NONE, CU_TENSOR_MAP_L2_PROMOTION_L2_128B, CU_TENSOR_MAP_FLOAT_OOB_FILL_NONE);
    }
    {
        cuuint64_t dims[2] = {(cuuint64_t)N_, (cuuint64_t)M_};
        cuuint64_t strides[1] = {(cuuint64_t)N_ * 2};
        cuuint32_t box[2] = {64, 16};
        cuuint32_t es[2] = {1, 1};
        encode(&tmo64, CU_TENSOR_MAP_DATA_TYPE_BFLOAT16, 2, d_out, dims, strides, box, es, CU_TENSOR_MAP_INTERLEAVE_NONE,
               CU_TENSOR_MAP_SWIZZLE_128B, CU_TENSOR_MAP_L2_PROMOTION_NONE, CU_TENSOR_MAP_FLOAT_OOB_FILL_NONE);
        box[0] = 32;
        encode(&tmo32, CU_TENSOR_MAP_DATA_TYPE_BFLOAT16, 2, d_out, dims, strides, box, es, CU_TENSOR_MAP_INTERLEAVE_NONE,
               CU_TENSOR_MAP_SWIZZLE_64B, CU_TENSOR_MAP_L2_PROMOTION_NONE, CU_TENSOR_MAP_FLOAT_OOB_FILL_NONE);
    }
    nf4_gemm_kernel<<<128, 256, SMEM_BYTES>>>(qw, cb, absmax, (uint8_t*)wimg, (unsigned*)gflag, tmx, tmq, tmo64, tmo32, tmqp, tmx16, tmx64, tmq1);
}
```

```cpp
#include <cuda_runtime.h>
#include <cuda_bf16.h>
#include <cuda.h>
#include <stdint.h>

constexpr int M_ = 2048, K_ = 1024, N_ = 3584;
constexpr int BM = 256, BN = 224;
constexpr int UNIT = 14336;
constexpr int NW = 6, NR = 3;
constexpr int RAW_OFF = 3 * 32768;
constexpr int SC_OFF = RAW_OFF + 2 * UNIT;
constexpr int W_OFF = 127 * 1024;
constexpr int RAW2_OFF = W_OFF + NW * UNIT;
constexpr int BAR_OFF = RAW2_OFF + UNIT;
__host__ __device__ constexpr int roff(int slot) { return slot < 2 ? slot * UNIT : RAW2_OFF - RAW_OFF; }
constexpr int SMEM_BYTES = BAR_OFF + 320;
#define TRAPSTR ""
#define DLEAD 6
#define PFQ 4
#define PFX 3
#define FT 38
#define TSP 2
#define LATE0 12
#define XLATE 1
#define STFIRST 0
#define RAWFIRST 0
#define F0 2
#define RAMP 4
#define C0 2
#define C1 11

#define SPL1 8
#define SPL3 8
#define E1 1
#define E2 1
#define PUBD 1
#define G1 7
#define G3 9
#define E3 0
#define E0 2
#define TLPRO -2
#define LEAD0 0x4345556666666666ull
#define LEAD1 LEAD0
#define HM1 4
#define HM2 4
#define HM3 4
#define PB 5
#define T2 1000
#define T3 1800
#define X2AT 1
#define XLAG 0
#define T2B 1400
#define G2S 0
#define PM 0
#define DEF 4
#define TB 4
#define ORD1 2
#define GS 0
#define GL 0
#define GR 1
#define MAPM 0
#define HO 0
#define SG0 0
#define SG1 0
#define SG2 0
#define SG3 0
#define SG4 0
#define ALIGNO 1
#define TLIT 2
#define PFL 1
#define GUEST 7
#define PFG 1
constexpr int NU = 26;
constexpr int SC_STRIDE = 464;
__device__ __align__(1024) uint8_t g_wimg[16 * 8 * UNIT];
__device__ __align__(128) unsigned g_flag[16 * 32];

#define TSL(i)
#define TL_DUMP()
#define TSW(w, i)
#define TS_INIT()
#define TS_DUMP()

#define TSX(w, i)
#define RT(i)
__device__ __forceinline__ uint32_t smem_u32(const void* p) { return (uint32_t)__cvta_generic_to_shared(p); }
__device__ __forceinline__ bool elect() {
    uint32_t ok;
    asm volatile("{\n.reg .pred p;\nelect.sync _|p, 0xffffffff;\nselp.u32 %0, 1, 0, p;\n}\n" : "=r"(ok));
    return ok != 0;
}
__device__ __forceinline__ void mbar_init(uint32_t bar, uint32_t cnt) { asm volatile("mbarrier.init.shared::cta.b64 [%0], %1;" ::"r"(bar), "r"(cnt) : "memory"); }
__device__ __forceinline__ void mbar_expect_tx(uint32_t bar, uint32_t bytes) { asm volatile("mbarrier.arrive.expect_tx.shared::cta.b64 _, [%0], %1;" ::"r"(bar), "r"(bytes) : "memory"); }
__device__ __forceinline__ void mbar_arrive(uint32_t bar) { asm volatile("mbarrier.arrive.shared::cta.b64 _, [%0];" ::"r"(bar) : "memory"); }
__device__ __forceinline__ void mbar_arrive_cluster(uint32_t cbar) { asm volatile("mbarrier.arrive.shared::cluster.b64 _, [%0];" ::"r"(cbar) : "memory"); }
__device__ __forceinline__ void mbar_arrive_cluster_if(bool c, uint32_t cbar) {
    asm volatile("{\n.reg .pred p;\nsetp.ne.u32 p, %1, 0;\n@p mbarrier.arrive.shared::cluster.b64 _, [%0];\n}\n" ::"r"(cbar), "r"((uint32_t)c) : "memory");
}
#define BOUNDED
#define WAIT_INIT "mov.u32 n, 0;\n"
#define WAIT_NEXT "@p bra.uni LAB_DONE;\nadd.u32 n, n, 1;\nsetp.lt.u32 p, n, 0x4000;\n@p bra.uni LAB_WAIT;\n"
__device__ __forceinline__ void mbar_wait(uint32_t bar, uint32_t parity) {
    asm volatile(
        "{\n.reg .pred p;\n.reg .u32 n;\n"
        WAIT_INIT
        "LAB_WAIT:\n"
        "mbarrier.try_wait.parity.shared::cta.b64 p, [%0], %1;\n"
        WAIT_NEXT
        "LAB_DONE:\n}\n" ::"r"(bar), "r"(parity) : "memory");
}
__device__ __forceinline__ bool mbar_try(uint32_t bar, uint32_t parity) {
    uint32_t ok;
    asm volatile("{\n.reg .pred p;\nmbarrier.test_wait.parity.shared::cta.b64 p, [%1], %2;\nselp.u32 %0, 1, 0, p;\n}\n" : "=r"(ok) : "r"(bar), "r"(parity) : "memory");
    return ok != 0;
}
__device__ __forceinline__ void mbar_wait1(uint32_t b0, uint32_t p0, bool skip) {
    asm volatile(
        "{\n.reg .pred p;\n.reg .u32 n;\n"
        "setp.ne.u32 p, %2, 0;\n@p bra.uni LAB_DONE;\n"
        WAIT_INIT
        "LAB_WAIT:\n"
        "mbarrier.try_wait.parity.shared::cta.b64 p, [%0], %1;\n"
        WAIT_NEXT
        "LAB_DONE:\n}\n" ::"r"(b0), "r"(p0), "r"((uint32_t)skip) : "memory");
}
__device__ __forceinline__ void mbar_wait2(uint32_t b0, uint32_t p0, uint32_t b1, uint32_t p1, bool skip = false) {
    asm volatile(
        "{\n.reg .pred p, q;\n.reg .u32 n;\n"
        "setp.ne.u32 p, %4, 0;\n@p bra.uni LAB_DONE;\n"
        WAIT_INIT
        "LAB_WAIT:\n"
        "mbarrier.try_wait.parity.shared::cta.b64 p, [%0], %1;\n"
        "mbarrier.try_wait.parity.shared::cta.b64 q, [%2], %3;\n"
        "and.pred p, p, q;\n"
        WAIT_NEXT
        "LAB_DONE:\n}\n" ::"r"(b0), "r"(p0), "r"(b1), "r"(p1), "r"((uint32_t)skip) : "memory");
}
__device__ __forceinline__ void mbar_wait3(uint32_t b0, uint32_t p0, uint32_t b1, uint32_t p1, uint32_t b2, uint32_t p2, bool skip = false) {
    asm volatile(
        "{\n.reg .pred p, q, r;\n.reg .u32 n;\n"
        "setp.ne.u32 p, %6, 0;\n@p bra.uni LAB_DONE;\n"
        WAIT_INIT
        "LAB_WAIT:\n"
        "mbarrier.try_wait.parity.shared::cta.b64 p, [%0], %1;\n"
        "mbarrier.try_wait.parity.shared::cta.b64 q, [%2], %3;\n"
        "mbarrier.try_wait.parity.shared::cta.b64 r, [%4], %5;\n"
        "and.pred p, p, q;\n"
        "and.pred p, p, r;\n"
        WAIT_NEXT
        "LAB_DONE:\n}\n" ::"r"(b0), "r"(p0), "r"(b1), "r"(p1), "r"(b2), "r"(p2), "r"((uint32_t)skip) : "memory");
}
__device__ __forceinline__ void tma_load_2d(uint32_t dst, const CUtensorMap* tm, int c0, int c1, uint32_t bar) {
    asm volatile("cp.async.bulk.tensor.2d.shared::cluster.global.mbarrier::complete_tx::bytes [%0], [%1, {%2, %3}], [%4];"
                 ::"r"(dst), "l"(tm), "r"(c0), "r"(c1), "r"(bar) : "memory");
}
__device__ __forceinline__ void tma_load_4d(uint32_t dst, const CUtensorMap* tm, int c0, int c1, int c2, int c3, uint32_t bar) {
    asm volatile("cp.async.bulk.tensor.4d.shared::cluster.global.mbarrier::complete_tx::bytes [%0], [%1, {%2, %3, %4, %5}], [%6];"
                 ::"r"(dst), "l"(tm), "r"(c0), "r"(c1), "r"(c2), "r"(c3), "r"(bar) : "memory");
}
__device__ __forceinline__ void tma_load_5d(uint32_t dst, const CUtensorMap* tm, int c0, int c1, int c2, int c3, int c4, uint32_t bar) {
    asm volatile("cp.async.bulk.tensor.5d.shared::cluster.global.mbarrier::complete_tx::bytes [%0], [%1, {%2, %3, %4, %5, %6}], [%7];"
                 ::"r"(dst), "l"(tm), "r"(c0), "r"(c1), "r"(c2), "r"(c3), "r"(c4), "r"(bar) : "memory");
}
__device__ __forceinline__ void tma_prefetch_2d(const CUtensorMap* tm, int c0, int c1) {
    asm volatile("cp.async.bulk.prefetch.tensor.2d.L2.global [%0, {%1, %2}];" ::"l"(tm), "r"(c0), "r"(c1) : "memory");
}
__device__ __forceinline__ void bulk_load(uint32_t dst, const void* src, uint32_t bytes, uint32_t bar) {
    asm volatile("cp.async.bulk.shared::cluster.global.mbarrier::complete_tx::bytes [%0], [%1], %2, [%3];"
                 ::"r"(dst), "l"(src), "r"(bytes), "r"(bar) : "memory");
}
__device__ __forceinline__ void tma_store_3d(const CUtensorMap* tm, uint32_t src, int c0, int c1, int c2) {
    asm volatile("cp.async.bulk.tensor.3d.global.shared::cta.bulk_group [%0, {%2, %3, %4}], [%1];"
                 ::"l"(tm), "r"(src), "r"(c0), "r"(c1), "r"(c2) : "memory");
}
__device__ __forceinline__ void cluster_arrive() { asm volatile("barrier.cluster.arrive.relaxed.aligned;" ::: "memory"); }
__device__ __forceinline__ void cluster_wait() { asm volatile("barrier.cluster.wait.acquire.aligned;" ::: "memory"); }
__device__ __forceinline__ uint32_t mapa(uint32_t addr, uint32_t cta) {
    uint32_t r; asm("mapa.shared::cluster.u32 %0, %1, %2;" : "=r"(r) : "r"(addr), "r"(cta)); return r;
}
__device__ __forceinline__ void copy_to_peer(uint32_t cdst, uint32_t src, uint32_t bytes, uint32_t cbar) {
    asm volatile("cp.async.bulk.shared::cluster.shared::cta.mbarrier::complete_tx::bytes [%0], [%1], %2, [%3];"
                 ::"r"(cdst), "r"(src), "r"(bytes), "r"(cbar) : "memory");
}
__device__ __forceinline__ void wgmma_fence() { asm volatile("wgmma.fence.sync.aligned;" ::: "memory"); }
__device__ __forceinline__ void wgmma_commit() { asm volatile("wgmma.commit_group.sync.aligned;" ::: "memory"); }
template <int N> __device__ __forceinline__ void wgmma_wait() { asm volatile("wgmma.wait_group.sync.aligned %0;" ::"n"(N) : "memory"); }
__device__ __forceinline__ uint32_t pack_bf16(float lo, float hi) {
    uint32_t r; asm("cvt.rn.bf16x2.f32 %0, %1, %2;" : "=r"(r) : "f"(hi), "f"(lo)); return r;
}
__device__ __forceinline__ void stmatrix_x4(uint32_t addr, uint32_t a, uint32_t b, uint32_t c, uint32_t d) {
    asm volatile("stmatrix.sync.aligned.m8n8.x4.shared.b16 [%0], {%1, %2, %3, %4};" ::"r"(addr), "r"(a), "r"(b), "r"(c), "r"(d) : "memory");
}
__device__ __forceinline__ uint4 lds128(uint32_t a) {
    uint4 v; asm volatile("ld.shared.v4.b32 {%0, %1, %2, %3}, [%4];" : "=r"(v.x), "=r"(v.y), "=r"(v.z), "=r"(v.w) : "r"(a) : "memory"); return v;
}
__device__ __forceinline__ void sts128(uint32_t a, uint4 v) {
    asm volatile("st.shared.v4.b32 [%0], {%1, %2, %3, %4};" ::"r"(a), "r"(v.x), "r"(v.y), "r"(v.z), "r"(v.w) : "memory");
}
__device__ __forceinline__ void sts128x(uint32_t a, uint4 v) {
    asm volatile("st.shared.v4.b32 [%0], {%1, %2, %3, %4};" ::"r"(a), "r"(v.x), "r"(v.y), "r"(v.z), "r"(v.w) : "memory");
}
__device__ __forceinline__ uint4 ldg128(const void* p) {
    uint4 v; asm volatile("ld.global.nc.v4.b32 {%0, %1, %2, %3}, [%4];" : "=r"(v.x), "=r"(v.y), "=r"(v.z), "=r"(v.w) : "l"(p) : "memory"); return v;
}
__device__ __forceinline__ unsigned clk() { unsigned c; asm volatile("mov.u32 %0, %%clock;" : "=r"(c) :: "memory"); return c; }
__device__ __forceinline__ uint32_t mul_bf16x2(uint32_t a, uint32_t b) { uint32_t r; asm("mul.rn.bf16x2 %0, %1, %2;" : "=r"(r) : "r"(a), "r"(b)); return r; }
struct Lut { uint32_t lo[4], hi[4]; };
__device__ __forceinline__ uint32_t prmt(uint32_t a, uint32_t b, uint32_t s) { uint32_t r; asm("prmt.b32 %0, %1, %2, %3;" : "=r"(r) : "r"(a), "r"(b), "r"(s)); return r; }
__device__ __forceinline__ uint32_t pack4(const uint4& q) {
    uint32_t ab, cd, p;
    asm volatile("mad.lo.u32 %0, %1, 16, %2;" : "=r"(ab) : "r"(q.y), "r"(q.x));
    asm volatile("mad.lo.u32 %0, %1, 16, %2;" : "=r"(cd) : "r"(q.w), "r"(q.z));
    asm volatile("mad.lo.u32 %0, %1, 256, %2;" : "=r"(p) : "r"(cd), "r"(ab));
    return p;
}
__device__ __forceinline__ void lookup4(uint32_t p, const Lut& t, uint32_t& w01, uint32_t& w23) {
    const uint32_t t8 = p & 0x8888u, s7 = p & 0x7777u;
    const uint32_t sel = (t8 >> 1) + 0x3210u;
    const uint32_t lo = prmt(prmt(t.lo[0], t.lo[1], p), prmt(t.lo[2], t.lo[3], s7), sel);
    const uint32_t hi = prmt(prmt(t.hi[0], t.hi[1], p), prmt(t.hi[2], t.hi[3], s7), sel);
    w01 = prmt(lo, hi, 0x5140);
    w23 = prmt(lo, hi, 0x7362);
}
__device__ __forceinline__ uint4 dequant8(uint32_t p0, uint32_t p1, const uint4& sc, const Lut& tu) {
    uint4 r;
    const Lut& t = tu;
    lookup4(p0, t, r.x, r.y);
    lookup4(p1, t, r.z, r.w);
    r.x = mul_bf16x2(r.x, sc.x); r.y = mul_bf16x2(r.y, sc.y); r.z = mul_bf16x2(r.z, sc.z); r.w = mul_bf16x2(r.w, sc.w);
    return r;
}
__device__ __forceinline__ void fence_async_smem() { asm volatile("fence.proxy.async.shared::cta;" ::: "memory"); }

template <int SCALE_D, int BHI, uint32_t AHI = 0x40000040u>
__device__ __forceinline__ void wgmma224(float (&d)[112], uint32_t descA, uint32_t descB) {
    asm volatile(
        "{\n.reg .pred p;\n.reg .b64 da, db;\nsetp.ne.b32 p, %114, 0;\n"
        "mov.b64 da, {%112, %116};\nmov.b64 db, {%113, %115};\n"
        "wgmma.mma_async.sync.aligned.m64n224k16.f32.bf16.bf16 "
        "{%0, %1, %2, %3, %4, %5, %6, %7, %8, %9, %10, %11, %12, %13, %14, %15, "
        "%16, %17, %18, %19, %20, %21, %22, %23, %24, %25, %26, %27, %28, %29, %30, %31, "
        "%32, %33, %34, %35, %36, %37, %38, %39, %40, %41, %42, %43, %44, %45, %46, %47, "
        "%48, %49, %50, %51, %52, %53, %54, %55, %56, %57, %58, %59, %60, %61, %62, %63, "
        "%64, %65, %66, %67, %68, %69, %70, %71, %72, %73, %74, %75, %76, %77, %78, %79, "
        "%80, %81, %82, %83, %84, %85, %86, %87, %88, %89, %90, %91, %92, %93, %94, %95, "
        "%96, %97, %98, %99, %100, %101, %102, %103, %104, %105, %106, %107, %108, %109, %110, %111}, "
        "da, db, p, 1, 1, 0, 1;\n}\n"
        : "+f"(d[0]), "+f"(d[1]), "+f"(d[2]), "+f"(d[3]), "+f"(d[4]), "+f"(d[5]), "+f"(d[6]), "+f"(d[7]),
          "+f"(d[8]), "+f"(d[9]), "+f"(d[10]), "+f"(d[11]), "+f"(d[12]), "+f"(d[13]), "+f"(d[14]), "+f"(d[15]),
          "+f"(d[16]), "+f"(d[17]), "+f"(d[18]), "+f"(d[19]), "+f"(d[20]), "+f"(d[21]), "+f"(d[22]), "+f"(d[23]),
          "+f"(d[24]), "+f"(d[25]), "+f"(d[26]), "+f"(d[27]), "+f"(d[28]), "+f"(d[29]), "+f"(d[30]), "+f"(d[31]),
          "+f"(d[32]), "+f"(d[33]), "+f"(d[34]), "+f"(d[35]), "+f"(d[36]), "+f"(d[37]), "+f"(d[38]), "+f"(d[39]),
          "+f"(d[40]), "+f"(d[41]), "+f"(d[42]), "+f"(d[43]), "+f"(d[44]), "+f"(d[45]), "+f"(d[46]), "+f"(d[47]),
          "+f"(d[48]), "+f"(d[49]), "+f"(d[50]), "+f"(d[51]), "+f"(d[52]), "+f"(d[53]), "+f"(d[54]), "+f"(d[55]),
          "+f"(d[56]), "+f"(d[57]), "+f"(d[58]), "+f"(d[59]), "+f"(d[60]), "+f"(d[61]), "+f"(d[62]), "+f"(d[63]),
          "+f"(d[64]), "+f"(d[65]), "+f"(d[66]), "+f"(d[67]), "+f"(d[68]), "+f"(d[69]), "+f"(d[70]), "+f"(d[71]),
          "+f"(d[72]), "+f"(d[73]), "+f"(d[74]), "+f"(d[75]), "+f"(d[76]), "+f"(d[77]), "+f"(d[78]), "+f"(d[79]),
          "+f"(d[80]), "+f"(d[81]), "+f"(d[82]), "+f"(d[83]), "+f"(d[84]), "+f"(d[85]), "+f"(d[86]), "+f"(d[87]),
          "+f"(d[88]), "+f"(d[89]), "+f"(d[90]), "+f"(d[91]), "+f"(d[92]), "+f"(d[93]), "+f"(d[94]), "+f"(d[95]),
          "+f"(d[96]), "+f"(d[97]), "+f"(d[98]), "+f"(d[99]), "+f"(d[100]), "+f"(d[101]), "+f"(d[102]), "+f"(d[103]),
          "+f"(d[104]), "+f"(d[105]), "+f"(d[106]), "+f"(d[107]), "+f"(d[108]), "+f"(d[109]), "+f"(d[110]), "+f"(d[111])
        : "r"(descA), "r"(descB), "n"(SCALE_D), "n"(BHI), "n"(AHI));
}

template <int SCALE_D, int BHI, uint32_t AHI = 0x40000040u>
__device__ __forceinline__ void wgmma128(float (&d)[64], uint32_t descA, uint32_t descB) {
    asm volatile(
        "{\n.reg .pred p;\n.reg .b64 da, db;\nsetp.ne.b32 p, %66, 0;\n"
        "mov.b64 da, {%64, %68};\nmov.b64 db, {%65, %67};\n"
        "wgmma.mma_async.sync.aligned.m64n128k16.f32.bf16.bf16 "
        "{%0, %1, %2, %3, %4, %5, %6, %7, %8, %9, %10, %11, %12, %13, %14, %15, "
        "%16, %17, %18, %19, %20, %21, %22, %23, %24, %25, %26, %27, %28, %29, %30, %31, "
        "%32, %33, %34, %35, %36, %37, %38, %39, %40, %41, %42, %43, %44, %45, %46, %47, "
        "%48, %49, %50, %51, %52, %53, %54, %55, %56, %57, %58, %59, %60, %61, %62, %63}, "
        "da, db, p, 1, 1, 0, 1;\n}\n"
        : "+f"(d[0]), "+f"(d[1]), "+f"(d[2]), "+f"(d[3]), "+f"(d[4]), "+f"(d[5]), "+f"(d[6]), "+f"(d[7]),
          "+f"(d[8]), "+f"(d[9]), "+f"(d[10]), "+f"(d[11]), "+f"(d[12]), "+f"(d[13]), "+f"(d[14]), "+f"(d[15]),
          "+f"(d[16]), "+f"(d[17]), "+f"(d[18]), "+f"(d[19]), "+f"(d[20]), "+f"(d[21]), "+f"(d[22]), "+f"(d[23]),
          "+f"(d[24]), "+f"(d[25]), "+f"(d[26]), "+f"(d[27]), "+f"(d[28]), "+f"(d[29]), "+f"(d[30]), "+f"(d[31]),
          "+f"(d[32]), "+f"(d[33]), "+f"(d[34]), "+f"(d[35]), "+f"(d[36]), "+f"(d[37]), "+f"(d[38]), "+f"(d[39]),
          "+f"(d[40]), "+f"(d[41]), "+f"(d[42]), "+f"(d[43]), "+f"(d[44]), "+f"(d[45]), "+f"(d[46]), "+f"(d[47]),
          "+f"(d[48]), "+f"(d[49]), "+f"(d[50]), "+f"(d[51]), "+f"(d[52]), "+f"(d[53]), "+f"(d[54]), "+f"(d[55]),
          "+f"(d[56]), "+f"(d[57]), "+f"(d[58]), "+f"(d[59]), "+f"(d[60]), "+f"(d[61]), "+f"(d[62]), "+f"(d[63])
        : "r"(descA), "r"(descB), "n"(SCALE_D), "n"(BHI), "n"(AHI));
}

template <int SCALE_D, int BHI, uint32_t AHI = 0x40000040u>
__device__ __forceinline__ void wgmma96(float (&d)[48], uint32_t descA, uint32_t descB) {
    asm volatile(
        "{\n.reg .pred p;\n.reg .b64 da, db;\nsetp.ne.b32 p, %50, 0;\n"
        "mov.b64 da, {%48, %52};\nmov.b64 db, {%49, %51};\n"
        "wgmma.mma_async.sync.aligned.m64n96k16.f32.bf16.bf16 "
        "{%0, %1, %2, %3, %4, %5, %6, %7, %8, %9, %10, %11, %12, %13, %14, %15, "
        "%16, %17, %18, %19, %20, %21, %22, %23, %24, %25, %26, %27, %28, %29, %30, %31, "
        "%32, %33, %34, %35, %36, %37, %38, %39, %40, %41, %42, %43, %44, %45, %46, %47}, "
        "da, db, p, 1, 1, 0, 1;\n}\n"
        : "+f"(d[0]), "+f"(d[1]), "+f"(d[2]), "+f"(d[3]), "+f"(d[4]), "+f"(d[5]), "+f"(d[6]), "+f"(d[7]),
          "+f"(d[8]), "+f"(d[9]), "+f"(d[10]), "+f"(d[11]), "+f"(d[12]), "+f"(d[13]), "+f"(d[14]), "+f"(d[15]),
          "+f"(d[16]), "+f"(d[17]), "+f"(d[18]), "+f"(d[19]), "+f"(d[20]), "+f"(d[21]), "+f"(d[22]), "+f"(d[23]),
          "+f"(d[24]), "+f"(d[25]), "+f"(d[26]), "+f"(d[27]), "+f"(d[28]), "+f"(d[29]), "+f"(d[30]), "+f"(d[31]),
          "+f"(d[32]), "+f"(d[33]), "+f"(d[34]), "+f"(d[35]), "+f"(d[36]), "+f"(d[37]), "+f"(d[38]), "+f"(d[39]),
          "+f"(d[40]), "+f"(d[41]), "+f"(d[42]), "+f"(d[43]), "+f"(d[44]), "+f"(d[45]), "+f"(d[46]), "+f"(d[47])
        : "r"(descA), "r"(descB), "n"(SCALE_D), "n"(BHI), "n"(AHI));
}

__device__ __forceinline__ uint32_t opq(uint32_t v) { asm volatile("" : "+r"(v)); return v; }
template <int I> struct IC { static constexpr int value = I; };
template <int B, int E, class F> __device__ __forceinline__ void static_for(F&& f) {
    if constexpr (B < E) { f(IC<B>{}); static_for<B + 1, E>(f); }
}

__device__ __forceinline__ void tma_store_2d(const CUtensorMap* tm, uint32_t src, int c0, int c1) {
    asm volatile("cp.async.bulk.tensor.2d.global.shared::cta.bulk_group [%0, {%2, %3}], [%1];" ::"l"(tm), "r"(src), "r"(c0), "r"(c1) : "memory");
}
__device__ __forceinline__ void bulk_store(void* dst, uint32_t src, uint32_t bytes) {
    asm volatile("cp.async.bulk.global.shared::cta.bulk_group [%0], [%1], %2;" ::"l"(dst), "r"(src), "r"(bytes) : "memory");
}
__device__ __forceinline__ void bulk_commit() { asm volatile("cp.async.bulk.commit_group;" ::: "memory"); }
template <int N> __device__ __forceinline__ void bulk_wait_read() { asm volatile("cp.async.bulk.wait_group.read %0;" ::"n"(N) : "memory"); }
__device__ __forceinline__ void bar_arrive(int id) { asm volatile("bar.arrive %0, 256;" ::"r"(id) : "memory"); }
__device__ __forceinline__ void bar_sync(int id) { asm volatile("bar.sync %0, 256;" ::"r"(id) : "memory"); }
template <int NC, int OFF, int N>
__device__ __forceinline__ void stage_cols(const float (&acc)[N], uint32_t stg) {
    int lane; asm volatile("mov.u32 %0, %%laneid;" : "=r"(lane));
    const int r = lane & 15;
    const uint32_t a0 = NC == 64 ? stg + r * 128 + (((lane >> 4) ^ (r & 7)) << 4) : stg + r * 64 + (((lane >> 4) ^ ((r >> 1) & 3)) << 4);
#pragma unroll
    for (int j = 0; j < NC / 16; j++) {
        const int i = OFF + 8 * j;
        stmatrix_x4(a0 ^ (j * 32), pack_bf16(acc[i], acc[i + 1]), pack_bf16(acc[i + 2], acc[i + 3]), pack_bf16(acc[i + 4], acc[i + 5]), pack_bf16(acc[i + 6], acc[i + 7]));
    }
}
__device__ __forceinline__ void send(uint32_t stg, const CUtensorMap* tmo, int col, int row) {
    fence_async_smem();
    __syncwarp();
    if (elect()) { tma_store_2d(tmo, stg, col, row); bulk_commit(); }
    __syncwarp();
}

__host__ __device__ constexpr int fconv(int g, int s) {
    return s + (s < 16 ? (int)(((g ? LEAD1 : LEAD0) >> (60 - 4 * s)) & 15) : 6);
}
__host__ __device__ constexpr int sub_of(int g, int b) { int s = -1; while (fconv(g, s + 1) <= b) s++; return s; }
__host__ __device__ constexpr int sub_min(int b) { return sub_of(0, b) < sub_of(1, b) ? sub_of(0, b) : sub_of(1, b); }
__host__ __device__ constexpr int sub_max(int b) { return sub_of(0, b) > sub_of(1, b) ? sub_of(0, b) : sub_of(1, b); }
__host__ __device__ constexpr int hmode(int u) { return u <= 1 ? 1 : u < HM1 ? 0 : u < HM2 ? 1 : u < HM3 ? 2 : 3; }
__host__ __device__ constexpr int t7(int v) { return sub_max(2 * v + 1) + (hmode(v) == 2 ? 0 : 1); }
__host__ __device__ constexpr int t7b(int b) { return sub_max(b) + (sub_min(b + 1) == sub_max(b) ? 0 : 1); }
__host__ __device__ constexpr int xunit(int i) { int v = 0; while (sub_min(2 * v + 1) < 4 * i - 7) v++; return v; }
__host__ __device__ constexpr int rslot(int u) { return (2 * u) % 3; }
__host__ __device__ constexpr int rpar(int u) { return (u / 3 - (u % 3 == 0)) & 1; }
__host__ __device__ constexpr int sslot(int c) { return c < 3 ? c + 3 : c % 3; }

__global__ void __cluster_dims__(2, 1, 1) __launch_bounds__(256, 1)
nf4_gemm_kernel(const int* __restrict__ qw, const __nv_bfloat16* __restrict__ cb, const __nv_bfloat16* __restrict__ absmax,
                uint8_t* __restrict__ wimg, unsigned* __restrict__ gflag,
                const __grid_constant__ CUtensorMap tmx, const __grid_constant__ CUtensorMap tmq, const __grid_constant__ CUtensorMap tmo64,
                const __grid_constant__ CUtensorMap tmo32, const __grid_constant__ CUtensorMap tmqp, const __grid_constant__ CUtensorMap tmx16,
                const __grid_constant__ CUtensorMap tmx64, const __grid_constant__ CUtensorMap tmq1) {
    extern __shared__ __align__(1024) uint8_t smem[];
    const uint32_t sbase = smem_u32(smem);
    const int rank = blockIdx.x & 1;
    const int cid = blockIdx.x >> 1;
    const int mt = (MAPM == 0 ? cid >> 4 : MAPM == 1 ? cid & 3 : MAPM == 2 ? (cid >> 1) & 3 : MAPM == 3 ? (cid >> 2) & 3 : (cid >> 3) & 3) * 2 + rank;
    const int nt = MAPM == 0 ? cid & 15 : MAPM == 1 ? cid >> 2 : MAPM == 2 ? (cid & 1) + (cid >> 3) * 2 : MAPM == 3 ? (cid & 3) + (cid >> 4) * 4 : (cid & 7) + (cid >> 5) * 8;
    const int lane = threadIdx.x & 31;
    const unsigned tstart = clk();
    uint4 q[4], c0, c1;
    uint2 sf;
    if (threadIdx.x < 224) {
        const int col = nt * BN + (threadIdx.x >> 5) * 32 + (lane & 7) * 4;
        const int* p = qw + (rank * 8 + (lane >> 3)) * N_ + col;
        q[0] = ldg128(p); q[1] = ldg128(p + 4 * N_);
        q[2] = ldg128(p + 16 * N_); q[3] = ldg128(p + 20 * N_);
        asm volatile("ld.global.nc.v2.b32 {%0, %1}, [%2];" : "=r"(sf.x), "=r"(sf.y) : "l"(absmax + col) : "memory");
        c0 = ldg128(cb); c1 = ldg128(cb + 8);
    }
    const int warp = __shfl_sync(~0u, (int)(threadIdx.x >> 5), 0);
    const int wg = warp >> 2;
    const uint32_t bars = sbase + BAR_OFF;
    const uint32_t fullW = bars, rawfull = bars + 48, written = bars + 72, xbar = bars + 96, gbar = bars + 112 + wg * 24;
    const uint32_t x1bar = bars + 160, rawh = bars + 176 - 8, ebar = bars + 200;
    const uint32_t wbase = sbase + W_OFF;
    TS_INIT();
    __syncwarp();
    TSW(0, 0);

    const int pair = mt >> 1;
    auto chunk = [&](int i) { return i < GUEST ? i : i == GUEST ? 12 + pair : i <= 12 ? i - 1 : 12 + ((pair + i) & 3); };
    unsigned* flag = gflag + nt * 32;
    uint8_t* wpan = wimg + nt * 8 * UNIT;
    auto load_x = [&](int i, int slot) {
        tma_load_2d(sbase + slot * 32768, &tmx, chunk(i) * 64, mt * BM, fullW + 16 * slot);
        tma_load_2d(sbase + slot * 32768 + 16384, &tmx, chunk(i) * 64, mt * BM + 128, fullW + 16 * slot);
    };
    auto load_sc = [&](int i, int ss, uint32_t bar) {
        bulk_load(sbase + SC_OFF + ss * SC_STRIDE, absmax + chunk(i) * N_ + nt * BN, 448, bar);
        bulk_load(sbase + SC_OFF + ss * SC_STRIDE + 448, flag, 16, bar);
    };
    auto load_raw = [&](int u, int slot) {
        mbar_expect_tx(rawfull + 8 * slot, UNIT);
        tma_load_5d(sbase + RAW_OFF + roff(slot), &tmq, 0, 0, nt * 7, rank, 4 * chunk(u >> 1) + 2 * (u & 1), rawfull + 8 * slot);
    };
    auto load_half = [&](int b, uint32_t more) {
        const uint32_t bar = (b & 1) ? rawfull + 8 * rslot(b >> 1) : rawh + 8 * (b >> 1);
        mbar_expect_tx(bar, 7168 + more);
        tma_load_5d(sbase + RAW_OFF + roff(rslot(b >> 1)) + (b & 1) * 7168, &tmq1, 0, 0, nt * 7, rank, b, bar);
    };
    auto load_xh = [&](int i, int g, uint32_t bar) {
        mbar_expect_tx(bar, 16384);
        tma_load_2d(sbase + i * 32768 + g * 16384, &tmx, i * 64, mt * BM + g * 128, bar);
    };
    auto prefetch = [&](int c) {
        if (PFQ && c + PFQ < 12) tma_prefetch_2d(&tmqp, nt * BN, (c + PFQ) * 64 + pair * 16 + rank * 8);
        if (PFQ && (unsigned)(c - PFG) < 4) tma_prefetch_2d(&tmqp, nt * BN, (12 + pair) * 64 + (c - PFG) * 16 + rank * 8);
        if (PFX && c + PFX < 16 && c + PFX > 2) tma_prefetch_2d(&tmx16, chunk(c + PFX) * 64, mt * BM + nt * 16);
        if (PFL && c >= 9) tma_prefetch_2d(&tmx16, chunk(c + 5) * 64, mt * BM + nt * 16);
    };
    if (warp == 7) {
        if (elect()) {
            mbar_init(xbar, 1); mbar_init(rawh + 8, 1); mbar_init(rawfull + 8 * rslot(1), 1); mbar_init(xbar + 8, 1);
            fence_async_smem();
            if (ORD1 == 0) load_xh(0, 0, xbar);
            load_half(2, 448);
            bulk_load(sbase + SC_OFF + sslot(0) * SC_STRIDE, absmax + nt * BN, 448, rawh + 8);
            if (ORD1 == 1) load_xh(0, 0, xbar);
            load_half(3, 0);
            if (ORD1 == 2) load_xh(0, 0, xbar);
            load_xh(0, 1, xbar + 8);
            mbar_init(rawfull + 8 * rslot(2), 1); mbar_init(rawfull + 8 * rslot(3), 1); mbar_init(rawh + 16, 1); mbar_init(rawh + 24, 1);
            mbar_init(x1bar, 1); mbar_init(x1bar + 8, 1);
#pragma unroll
            for (int s = 0; s < 2 * HM2; s++) if (hmode(s >> 1) == 0 || !(s & 1)) mbar_init(ebar + 8 * s, hmode(s >> 1) == 0 ? 1 : 7);
#pragma unroll
            for (int s = 2; s < HM1; s++) mbar_init(bars + 280 + 8 * s, 7);
            static_assert(HM1 <= 5 && HO == 0, "");
#pragma unroll
            for (int s = 0; s < NW; s++) { mbar_init(fullW + 8 * s, 1); if (s < HM2 && s != 4) mbar_arrive(fullW + 8 * s); }
#pragma unroll
            for (int s = 0; s < NR; s++) mbar_init(written + 8 * s, 7);
#pragma unroll
            for (int s = 0; s < 6; s++) mbar_init(bars + 112 + 8 * s, 4);
            asm volatile("fence.mbarrier_init.release.cluster;" ::: "memory");
            fence_async_smem();
            if ((sbase & 0xffffff) != 0x400) __trap();
        }
        __syncwarp();
        cluster_arrive();
        if (elect()) {
            asm volatile("prefetch.tensormap [%0];" ::"l"(&tmq) : "memory");
            asm volatile("prefetch.tensormap [%0];" ::"l"(&tmqp) : "memory");
            asm volatile("prefetch.tensormap [%0];" ::"l"(&tmx16) : "memory");
            asm volatile("prefetch.tensormap [%0];" ::"l"(&tmx64) : "memory");
            while (clk() - tstart < T2) { }
            load_half(4, 2 * SC_STRIDE); load_sc(1, sslot(1), rawh + 16); load_sc(2, sslot(2), rawh + 16); load_half(5, 0);
            while (clk() - tstart < T2B) { }
            load_xh(1, 0, x1bar);
            if (G2S == 0) { load_half(6, 0); load_half(7, 2 * SC_STRIDE); load_sc(3, sslot(3), rawfull + 8 * rslot(3)); load_sc(4, sslot(4), rawfull + 8 * rslot(3)); load_xh(1, 1, x1bar + 8); }
            while (clk() - tstart < T3) { }
#pragma unroll
            for (int c = 2 - PFQ; c < 0; c++) prefetch(c);
        }
        __syncwarp();
        if (TLPRO > 0) TSL(33);
        cluster_wait();
    } else {
        cluster_arrive();
    }
    const uint32_t rsrc = __shfl_sync(~0u, sbase + RAW_OFF + warp * 1024 + (lane & 7) * 128 + ((((lane >> 3) * 2) ^ (lane & 7)) << 4), lane);
    const uint32_t rsrc2 = __shfl_sync(~0u, rsrc ^ 16, lane);
    const uint32_t ssrc = sbase + SC_OFF + warp * 64;
    const int wpos = (ALIGNO && (nt & 1)) ? (0x73210546 >> (4 * warp)) & 7 : warp;
    const uint32_t wown = wbase + rank * 7168 + wpos * 512;
    const uint32_t wdst = __shfl_sync(~0u, wown + lane * 16, lane);
    auto get_sc = [&](int ss) { return lds128(((opq(wdst) >> 3) & 0x30) + ssrc + ss * SC_STRIDE); };
    const uint32_t whalf = wbase + rank * 7168;
    const uint32_t pwhalf = mapa(whalf, rank ^ 1), pfullW = mapa(fullW, rank ^ 1);
    Lut lut;
    uint4 sc;
    uint4 q0, q1;
    auto fetch = [&](int slot, int h) {
        q0 = lds128(rsrc + roff(slot) + h * 7168);
        q1 = lds128(rsrc2 + roff(slot) + h * 7168);
    };
    auto convert0 = [&](int rs, int ws, bool look, uint32_t lbar, uint32_t lpar, int tl = -1) {
        bool ok = true;
        if (look) ok = mbar_try(lbar, lpar);
        const uint32_t p0 = pack4(q0), p1 = pack4(q1);
        if (tl >= 0 && TLPRO == 0 && TSP == 0) TSL(3 * tl + 2);
        uint4 w = dequant8(p0, p1, sc, lut);
        asm volatile("" : "+r"(w.x), "+r"(w.y), "+r"(w.z), "+r"(w.w));
        if (tl >= 0 && TLPRO == 0 && TSP == 1) TSL(3 * tl + 2);
        if (look) mbar_wait1(lbar, lpar, ok);
        if (tl >= 0 && TLPRO == 0 && TSP == 2) TSL(3 * tl + 2);
        fetch(rs, 1);
        sts128x(wdst + ws * UNIT, w);
    };
    auto convert1 = [&](int rs, int ws, bool next, int rsn, int rpn, bool scales, int cs, bool stfirst, bool look, uint32_t lbar, uint32_t lpar, int tl = -1) {
        bool ok = true, ok2 = true;
        if (next) ok = mbar_try(rawfull + 8 * rsn, rpn);
        if (look) ok2 = mbar_try(lbar, lpar);
        const uint32_t p0 = pack4(q0), p1 = pack4(q1);
        if (tl >= 0 && TLPRO == 0 && TSP == 0) TSL(3 * tl + 2);
        uint4 w = dequant8(p0, p1, sc, lut);
        asm volatile("" : "+r"(w.x), "+r"(w.y), "+r"(w.z), "+r"(w.w));
        if (stfirst) {
            sts128x(wdst + ws * UNIT + 3584, w);
            __syncwarp();
            if (elect()) mbar_arrive(written + 8 * rs);
            __syncwarp();
        }
        if (tl >= 0 && TLPRO == 0 && TSP == 1) TSL(3 * tl + 2);
        if (look) mbar_wait2(rawfull + 8 * rsn, rpn, lbar, lpar, ok && ok2);
        else if (next) mbar_wait1(rawfull + 8 * rsn, rpn, ok);
        if (tl >= 0 && TLPRO == 0 && TSP == 2) TSL(3 * tl + 2);
        if (next) fetch(rsn, 0);
        if (!stfirst) {
            sts128x(wdst + ws * UNIT + 3584, w);
            __syncwarp();
            if (elect()) mbar_arrive(written + 8 * rs);
            __syncwarp();
        }
        if (scales) sc = get_sc(cs);
    };
    auto hand_over = [&](int v, int rs, uint32_t par, int ws, uint32_t tx, bool raw) {
        mbar_wait(written + 8 * rs, par);
        fence_async_smem();
        if (elect()) {
            if (raw) load_raw(v + NR, rs);
            copy_to_peer(pwhalf + ws * UNIT, whalf + ws * UNIT, 7168, pfullW + 8 * ws);
            mbar_expect_tx(fullW + 8 * ws, tx);
        }
        __syncwarp();
    };
    auto share = [&](int v, int ws) {
        if ((v >> 1) == GUEST) { bulk_store(wpan + (2 * pair + (v & 1)) * UNIT + rank * 7168, whalf + ws * UNIT, 7168); bulk_commit(); }
    };
    constexpr uint32_t TXO = 7168 + SC_STRIDE, TXE = 7168 + 32768;
    auto hand_over_c = [&](int v) {
        hand_over(v, rslot(v), (v / 3) & 1, v % NW, (v & 1) ? (v < 7 || v == 25 ? 7168 : TXO) : (v < 4 ? 7168 : TXE), v >= 1 && v + NR < NU);
    };
    auto raw_bar = [](int b) { return b < 8 && !(b & 1) ? 168 + 8 * (b >> 1) : b < 8 || !(b & 1) ? 48 + 8 * rslot(b >> 1) : -1; };
    auto raw_par = [](int b) { return b < 8 && !(b & 1) ? 0 : rpar(b >> 1); };
    auto w_bar = [](int s) { return hmode(s >> 1) == 0 ? 200 + 8 * s : (s & 1) ? -1 : hmode(s >> 1) == 1 ? 200 + 8 * s : 8 * ((s >> 1) % NW); };
    auto w_par = [](int s) { return hmode(s >> 1) < 2 ? 0 : ((s >> 1) / NW) & 1; };
    auto wait_slice = [&](int s, bool wok) {
        if (s == 0) { mbar_wait2(xbar + 8 * wg, 0, ebar, 0, wok); if (TLPRO > 0) TSL(32); return; }
        if (s == 4) mbar_wait2(x1bar + 8 * wg, 0, bars + w_bar(s), w_par(s), wok);
        else if (s == 8 && hmode(4) < 2) mbar_wait2(fullW + 32, 0, bars + w_bar(s), w_par(s), wok);
        else if (w_bar(s) >= 0) mbar_wait1(bars + w_bar(s), w_par(s), wok);
    };
    auto pass_on = [&](int b) {
        const int u = b >> 1, n = hmode(u) + 1;
        fence_async_smem();
        __syncwarp();
        if (elect()) {
            const uint32_t o = wpos * 512 + u * UNIT, eb = 8 * (n == 1 ? b : 2 * u);
            if (n == 2) copy_to_peer(pwhalf + o, whalf + o, 512, pfullW + 200 + eb);
            copy_to_peer(pwhalf + o + (b & 1) * 3584, whalf + o + (b & 1) * 3584, 512, pfullW + 200 + eb);
            mbar_expect_tx(ebar + eb, n * 512);
        }
        __syncwarp();
    };
    auto passes = [](int b) { return hmode(b >> 1) == 1 && (b & 1); };
    auto block = [&](int b, int sn) {
        const int u = b >> 1, h = b & 1;
        const bool pre = b >= PB || ((PM >> b) & 1), pren = (b + 1 >= PB || ((PM >> (b + 1)) & 1)) && b + 1 < 2 * NU;
        const bool war = !h && u >= NW, early_look = sn >= 0 && b - sn >= 2;
        bool ok1 = true, ok2 = true, ok3 = false;
        if (war) ok1 = mbar_try(written + 8 * rslot(u - 2), ((u - 2) / 3) & 1);
        if (pren && raw_bar(b + 1) >= 0) ok2 = mbar_try(bars + raw_bar(b + 1), raw_par(b + 1));
        if (sn >= 0 && w_bar(sn) >= 0) ok3 = mbar_try(bars + w_bar(sn), w_par(sn));
        if (sn == 4) ok3 &= mbar_try(x1bar + 8 * wg, 0);
        if (sn == 8 && hmode(4) < 2) ok3 &= mbar_try(fullW + 32, 0);
        uint4 r0, r1;
        if (pre) { r0 = q0; r1 = q1; }
        else {
            if (raw_bar(b) >= 0) mbar_wait(bars + raw_bar(b), raw_par(b));
            r0 = lds128(rsrc + roff(rslot(u)) + h * 7168); r1 = lds128(rsrc2 + roff(rslot(u)) + h * 7168);
            if (b == 4) sc = get_sc(sslot(1));
        }
        const uint32_t p0 = pack4(r0), p1 = pack4(r1);
        if (TLPRO == 2 && b >= TB && b < TB + 3) TSL(20 + 3 * (b - TB));
        if (b > DEF && passes(b - 1)) pass_on(b - 1);
        uint4 w = dequant8(p0, p1, sc, lut);
        asm volatile("" : "+r"(w.x), "+r"(w.y), "+r"(w.z), "+r"(w.w));
        if (war) mbar_wait1(written + 8 * rslot(u - 2), ((u - 2) / 3) & 1, ok1);
        const bool now = b < DEF && passes(b);
        if (now) { sts128(wdst + (u % NW) * UNIT + h * 3584, w); pass_on(b); }
        if (TLPRO == 2 && b >= TB && b < TB + 3) TSL(21 + 3 * (b - TB));
        if (early_look) wait_slice(sn, ok3);
        if (pren) {
            if (raw_bar(b + 1) >= 0) mbar_wait1(bars + raw_bar(b + 1), raw_par(b + 1), ok2);
            if (TLPRO == 2 && b >= TB && b < TB + 3) TSL(22 + 3 * (b - TB));
            fetch(rslot((b + 1) >> 1), h ^ 1);
        }
        if (!now) sts128(wdst + (u % NW) * UNIT + h * 3584, w);
        if (h || hmode(u) == 0) { __syncwarp(); if (elect()) mbar_arrive(h ? written + 8 * rslot(u) : bars + 280 + 8 * u); __syncwarp(); }
        if ((b & 3) == 3 && u + 1 < NU) sc = get_sc(sslot((b + 1) >> 2));
        if (sn >= 0 && !early_look) wait_slice(sn, ok3);
    };
    auto blocks = [&](auto A, auto B, int sn) {
        static_for<A.value, B.value>([&](auto I) { block(I.value, I.value == B.value - 1 ? sn : -1); });
        if (A.value == B.value) wait_slice(sn, false);
    };
    auto duties = [&](auto S) {
        constexpr int s = S.value;
        auto slab = [&](auto B) {
            constexpr int b = B.value, u = b >> 1;
            mbar_wait((b & 1) ? written + 8 * rslot(u) : bars + 280 + 8 * u, (b & 1) ? (u / 3) & 1 : 0);
            fence_async_smem();
            if (elect()) {
                copy_to_peer(pwhalf + u * UNIT + (b & 1) * 3584, whalf + u * UNIT + (b & 1) * 3584, 3584, pfullW + 200 + 8 * b);
                mbar_expect_tx(ebar + 8 * b, 3584);
                if (b & 1) load_raw(u + NR, rslot(u));
            }
            __syncwarp();
        };
        static_for<4, 2 * HM1>([&](auto B) { if constexpr (t7b(B.value) == s && sub_max(B.value) < s) slab(B); });
        static_for<1, 2 * C0 + 2>([&](auto V) {
            constexpr int v = V.value;
            if constexpr (hmode(v) != 0 && (t7(v) == s || (s == 0 && t7(v) < 0))) {
                if (hmode(v) >= 2) hand_over_c(v);
                else {
                    mbar_wait(written + 8 * rslot(v), (v / 3) & 1);
                    if (elect()) load_raw(v + NR, rslot(v));
                    __syncwarp();
                }
            }
        });
        if (elect()) {
            if (s == 0 && G2S) { load_half(6, 0); load_half(7, 2 * SC_STRIDE); load_sc(3, sslot(3), rawfull + 8 * rslot(3)); load_sc(4, sslot(4), rawfull + 8 * rslot(3)); }
            if (s == G2S - 1) load_xh(1, 1, x1bar + 8);
            if (s == X2AT) { if (HM2 > 4) mbar_expect_tx(fullW + 32, 32768); load_x(2, 2); }
            static_for<3, C0 + 2>([&](auto I) { if constexpr (t7(xunit(I.value)) + XLAG == s) load_x(I.value, I.value % 3); });
            if ((s & 3) == 1) { if (s >= 8) load_sc((s >> 2) + 3, (s >> 2) % 3, fullW + 8 * ((2 * (s >> 2) + 3) % NW)); prefetch(s >> 2); }
        }
        __syncwarp();
        static_for<4, 2 * HM1>([&](auto B) { if constexpr (t7b(B.value) == s && sub_max(B.value) == s) slab(B); });
    };
    static_assert(HM2 <= 6 && HM1 >= 1 && HM2 >= 3 && C0 < GUEST && t7(2 * C0 + 1) < 4 * C0 && t7(xunit(C0 + 1)) + XLAG < 4 * C0, "");
    bool ok0 = false;
    if (warp < 7) {
        lut.lo[0] = __byte_perm(c0.x, c0.y, 0x6420); lut.hi[0] = __byte_perm(c0.x, c0.y, 0x7531);
        lut.lo[1] = __byte_perm(c0.z, c0.w, 0x6420); lut.hi[1] = __byte_perm(c0.z, c0.w, 0x7531);
        lut.lo[2] = __byte_perm(c1.x, c1.y, 0x6420); lut.hi[2] = __byte_perm(c1.x, c1.y, 0x7531);
        lut.lo[3] = __byte_perm(c1.z, c1.w, 0x6420); lut.hi[3] = __byte_perm(c1.z, c1.w, 0x7531);
        const uint32_t d = wown + ((lane & 7) >> 1) * 128 + (lane >> 3) * 16 + (lane & 1) * 8;
#pragma unroll
        for (int j = 0; j < 4; j++) {
            uint32_t a, b;
            lookup4(pack4(q[j]), lut, a, b);
            asm volatile("st.shared.v2.b32 [%0], {%1, %2};" ::"r"(d + (j >> 1) * 3584 + (j & 1) * 64), "r"(mul_bf16x2(a, sf.x)), "r"(mul_bf16x2(b, sf.y)) : "memory");
        }
        if (TLPRO > 0) TSL(33);
        cluster_wait();
        pass_on(1);
        if (elect()) mbar_arrive(written + 8 * rslot(0));
        __syncwarp();
        if (TLPRO > 0) TSL(34);
        mbar_wait(rawh + 8, 0);
        const uint4 a0 = lds128(rsrc + roff(rslot(1))), a1 = lds128(rsrc2 + roff(rslot(1))), s0 = get_sc(sslot(0));
        mbar_wait(rawfull + 8 * rslot(1), 0);
        if (TLPRO == 2) TSL(29);
        const uint4 a2 = lds128(rsrc + roff(rslot(1)) + 7168), a3 = lds128(rsrc2 + roff(rslot(1)) + 7168);
        sts128(wdst + UNIT, dequant8(pack4(a0), pack4(a1), s0, lut));
        sts128(wdst + UNIT + 3584, dequant8(pack4(a2), pack4(a3), s0, lut));
        ok0 = mbar_try(xbar + 8 * wg, 0) & mbar_try(ebar, 0);
        pass_on(3);
        if (elect()) mbar_arrive(written + 8 * rslot(1));
        __syncwarp();
        if (PB == 4) { mbar_wait(rawh + 16, 0); fetch(rslot(2), 0); sc = get_sc(sslot(1)); }
        static_assert(fconv(0, 0) == 4 && fconv(1, 0) == 4 && PB >= 4 && DEF >= 4, "");
    }
    if (TLPRO > 0) TSL(31);
    wait_slice(0, ok0);

    float acc0[112], acc1[112];
    const uint32_t descA = ((0x400 + wg * 16384) >> 4) | (1u << 16);
    constexpr uint32_t descB = ((0x400 + W_OFF) >> 4) | ((7168u >> 4) << 16);
    auto mma = [&](int slot, int ks, int tl = -1) {
        const uint32_t da = opq(descA) + slot * (32768 >> 4) + ks * 2, db = descB + (2 * slot + (ks >> 1)) * (UNIT >> 4) + (ks & 1) * 224;
        if (tl >= 0 && TLPRO == 0) TSL(3 * tl);
        wgmma_fence();
        wgmma224<1, 8>(acc0, da, db); wgmma224<1, 8>(acc1, da + 512, db);
        wgmma_commit();
        wgmma_wait<2>();
        if (tl >= 0 && TLPRO == 0) TSL(3 * tl + 1);
    };
    static_for<0, 4 * C0>([&](auto S) {
        constexpr int s = S.value;
        constexpr int c = s >> 2;
        if (s == 0) {
            wgmma_fence();
            wgmma224<0, 8>(acc0, descA, descB); wgmma224<0, 8>(acc1, descA + 512, descB);
            wgmma_commit();
        } else mma(c % 3, s & 3);
        if (TLPRO > 0) TSL(s);
        constexpr int a0 = fconv(0, s), b0 = fconv(0, s + 1), a1 = fconv(1, s), b1 = fconv(1, s + 1);
        if (warp == 7) { duties(S); wait_slice(s + 1, false); }
        else if ((a0 == a1 && b0 == b1) || wg == 0) blocks(IC<a0>{}, IC<b0>{}, s + 1);
        else blocks(IC<a1>{}, IC<b1>{}, s + 1);
    });
    auto load_w = [&](int v, uint32_t dst, uint32_t bar) {
        mbar_expect_tx(bar, UNIT);
        bulk_load(dst, wpan + (2 * (chunk(v >> 1) - 12) + (v & 1)) * UNIT, UNIT, bar);
    };
    auto load_l = [&](int i, int slot, int g, uint32_t bar) {
        tma_load_2d(sbase + slot * 32768 + g * 16384, &tmx64, chunk(i) * 64, mt * BM + g * 128, bar);
        tma_load_2d(sbase + slot * 32768 + g * 16384 + 8192, &tmx64, chunk(i + 1) * 64, mt * BM + g * 128, bar);
    };
    static_assert(fconv(0, 4 * C0) == 4 * C0 + 6 && fconv(1, 4 * C0) == 4 * C0 + 6 && PB <= 4 * C0 + 6, "ramp must be over");
    {
        uint32_t ph = (C0 / 3) & 1;
#pragma unroll 1
        for (int cb = C0; cb < C1; cb += 3)
          static_for<0, 3>([&](auto I) {
            constexpr int cc = C0 + I.value;
            constexpr int j0 = cc % 3, j1 = (cc + 1) % 3, j2 = (cc + 2) % 3;
            const int c = cb + I.value;
            if (TLPRO > 0 && I.value == 0) TSL(c < 8 ? 36 : 37);
            mma(j0, 0, 4 * I.value + 0);
            if (TLPRO > 0) TSL(cb == TLIT ? 8 + 4 * I.value + 0 : 30);
            if (warp < 7) convert0(j0, 2 * j1 + 1, true, written + 8 * j2, ((2 * cc + 1) / 3) & 1, 4 * I.value);
            else hand_over(2 * c + 2, j1, ((2 * cc + 2) / 3) & 1, 2 * j1, TXE, true);
            mma(j0, 1, 4 * I.value + 1);
            if (TLPRO > 0) TSL(cb == TLIT ? 8 + 4 * I.value + 1 : 30);
            if (warp < 7) convert1(j0, 2 * j1 + 1, true, j2, rpar(2 * cc + 4), true, j2, STFIRST, true, fullW + 16 * j0 + 8, ph, 4 * I.value + 1);
            else {
                if (elect()) {
                    load_sc(c + 3, j0, fullW + 16 * j1 + 8);
                    prefetch(c);
                    share(2 * c + 2, 2 * j1);
                    if (c == GUEST + PUBD) {
                        asm volatile("cp.async.bulk.wait_group 0;" ::: "memory");
                        asm volatile("red.relaxed.gpu.global.add.u32 [%0], 1;" ::"l"(flag) : "memory");
                    }
                }
                __syncwarp();
                mbar_wait(fullW + 16 * j0 + 8, ph);
            }
            if (j1 == 0) asm volatile("xor.b32 %0, %0, 1;" : "+r"(ph));
            mma(j0, 2, 4 * I.value + 2);
            if (TLPRO > 0) TSL(cb == TLIT ? 8 + 4 * I.value + 2 : 30);
            if (warp < 7) convert0(j2, 2 * j2, true, written + 8 * j1, ((2 * cc + 2) / 3) & 1, 4 * I.value + 2);
            else {
                hand_over(2 * c + 3, j0, ((2 * cc + 3) / 3) & 1, 2 * j1 + 1, TXO, j0 != 1 || c < 10);
                if (j0 == 1 && c == 10) {
                    unsigned f0, f1;
                    asm volatile("ld.shared.u32 %0, [%1];" : "=r"(f0) : "r"(sbase + SC_OFF + sslot(1) * SC_STRIDE + 448) : "memory");
                    asm volatile("ld.shared.u32 %0, [%1];" : "=r"(f1) : "r"(sbase + SC_OFF + sslot(12) * SC_STRIDE + 448) : "memory");
                    asm volatile("{\n.reg .pred p;\n.reg .u32 n, d;\nmov.u32 n, 0;\nLAB_POLL:\nsub.u32 d, %0, %1;\nsetp.ge.u32 p, d, 8;\n@p bra.uni LAB_DONE;\n"
                                 "ld.relaxed.gpu.global.u32 %0, [%2];\nadd.u32 n, n, 1;\nsetp.lt.u32 p, n, 0x10000;\n@p bra.uni LAB_POLL;\nLAB_DONE:\n}\n"
                                 : "+r"(f1) : "r"(f0 & ~7u), "l"(flag) : "memory");
                    if (elect()) load_w(26, sbase + RAW_OFF + roff(rslot(23)), rawfull + 8 * rslot(23));
                    __syncwarp();
                }
            }
            mma(j0, 3, 4 * I.value + 3);
            if (TLPRO > 0) TSL(cb == TLIT ? 8 + 4 * I.value + 3 : 30);
            if (warp < 7) convert1(j2, 2 * j2, true, j1, rpar(2 * cc + 5), false, 0, STFIRST, true, fullW + 16 * j1, ph, 4 * I.value + 3);
            else {
                if (elect()) {
                    if (j0 == 1 && c == 10) { load_l(12, 0, 0, fullW); load_l(12, 0, 1, fullW); }
                    else load_x(c + 2, j2);
                    share(2 * c + 3, 2 * j1 + 1);
                }
                __syncwarp();
                mbar_wait(fullW + 16 * j1, ph);
            }
          });
    }
    static_assert(C1 == 11 && GUEST + PUBD < 9, "");
    mma(2, 0);
    if (warp < 7) block(50, -1);
    else {
        mbar_wait(written + 8 * rslot(24), 0);
        if (elect()) {
            load_w(27, sbase + RAW_OFF + roff(rslot(24)), rawfull + 8 * rslot(24));
            load_w(28, wbase + 2 * UNIT, fullW + 16);
        }
        __syncwarp();
        hand_over_c(24);
        TSX(7, 6);
    }
    mma(2, 1);
    if (warp < 7) block(51, 46);
    else {
        if (elect()) {
            asm volatile("prefetch.tensormap [%0];" ::"l"(&tmo64) : "memory");
            asm volatile("prefetch.tensormap [%0];" ::"l"(&tmo32) : "memory");
        }
        __syncwarp();
        mbar_wait(fullW + 8 * 5, 1);
        hand_over_c(25);
        if (elect()) {
            mbar_expect_tx(xbar, 16384); load_l(14, 1, 0, xbar);
            load_w(29, sbase + RAW_OFF + roff(rslot(25)), rawfull + 8 * rslot(25));
            load_w(30, wbase + 3 * UNIT, fullW + 24);
        }
        __syncwarp();
        TSX(7, 7);
    }
    if (wg == 1) bar_sync(8);
    mma(2, 2);
    if (warp == 7) {
        wgmma_wait<1>();
        mbar_wait(fullW, 0);
        if (elect()) { load_w(31, wbase + 4 * UNIT, fullW + 32); mbar_expect_tx(xbar + 8, 16384); load_l(14, 1, 1, xbar + 8); }
        __syncwarp();
    }
    mma(2, 3);
    if (wg == 0) bar_arrive(8);
    const uint32_t slice0 = sbase + wg * 16384 + (warp & 3) * 2048;
    auto slc = [&](int p) { return slice0 + (p >> 1) * 32768 + (p & 1) * 8192; };
    const int row0 = mt * BM + wg * 128 + (warp & 3) * 16, odd = ALIGNO ? nt & 1 : 0;
    const int colL = nt * BN + odd * 96, colA = nt * BN + (odd ? 32 : 128), colB = nt * BN + (odd ? 0 : 192);
    auto load_s = [&](int i, int p, uint32_t bar) { tma_load_2d(slc(p), &tmx16, chunk(i) * 64, row0 + 64, bar); };
    const uint32_t tA = opq(descA);
    auto stagger = [&](unsigned d) { if (d) { const unsigned t = clk() + (warp & 3) * d; while ((int)(clk() - t) < 0) { } } };
    unsigned rt[16];
    mbar_wait(fullW, 0);
    wgmma_wait<0>();
    RT(0);
    TSX(wg * 4, 8 + wg);
    float lo0[64], hi0[48], lo1[64], hi1[48];
#pragma unroll
    for (int i = 0; i < 64; i++) { asm volatile("mov.b32 %0, %1;" : "=f"(lo0[i]) : "f"(acc0[i])); asm volatile("mov.b32 %0, %1;" : "=f"(lo1[i]) : "f"(acc1[i])); }
#pragma unroll
    for (int i = 0; i < 48; i++) { asm volatile("mov.b32 %0, %1;" : "=f"(hi0[i]) : "f"(acc0[64 + i])); asm volatile("mov.b32 %0, %1;" : "=f"(hi1[i]) : "f"(acc1[64 + i])); }
    auto udesc = [](int s) {
        const int v = 24 + (s >> 1);
        const int off = v == 26 ? RAW_OFF + roff(rslot(23)) : v == 27 ? RAW_OFF + roff(rslot(24)) : v == 29 ? RAW_OFF + roff(rslot(25))
                      : W_OFF + (v < 26 ? v - 24 : v == 28 ? 2 : v - 27) * UNIT;
        return (uint32_t)(((0x400 + off) >> 4) | ((7168u >> 4) << 16)) + (s & 1) * 224;
    };
    auto tdesc = [&](int p, int s) { return tA + (p >> 1) * (32768 >> 4) + (p & 1) * 512 + (s & 3) * 2; };
    auto ldesc = [&](int s) { return tdesc(s >> 2, s); };
    auto gdesc = [&](int s) { return tdesc(((s >> 2) + 4) % 6, s); };
    if (wg == 1) { mbar_wait(xbar + 8, 1); bar_sync(1); }
    static_for<0, 8>([&](auto V) {
        constexpr int v = 24 + (V.value == 0 || V.value > 3 ? V.value : V.value == 3 ? 1 : V.value + 1), s = 2 * (v - 24);
        if (v == 26) mbar_wait2(rawfull + 8 * rslot(23), rpar(26), rawfull + 8 * rslot(24), rpar(27), wg);
        else if (v == 29) mbar_wait1(rawfull + 8 * rslot(25), rpar(28), wg);
        else if (v == 28) mbar_wait2(fullW + 16, 0, xbar, 1, wg);
        else if (v != 24 && v != 27) mbar_wait1(fullW + 8 * (v == 25 ? 1 : v - 27), 0, wg);
        if (v == 28) TSX(wg * 4, 12 + wg);
        if (v == 31) TSX(wg * 4, 10 + wg);
        wgmma_fence();
        wgmma96<1, 8>(hi0, ldesc(s), udesc(s) + 128);
        wgmma96<1, 8>(hi0, ldesc(s + 1), udesc(s + 1) + 128);
    });
    wgmma_commit();
    bar_arrive(1 + wg);
    cluster_arrive();
    wgmma_wait<0>();
    RT(1);
    stagger(SG0);
    stage_cols<64, 0>(hi0, slc(4)); send(slc(4), &tmo64, colA, row0);
    stage_cols<32, 32>(hi0, slc(5));
    RT(2);
    bar_sync(2 + wg);
    RT(3);
    wgmma_fence();
#pragma unroll
    for (int s = 0; s < G1; s++) wgmma128<1, 8>(lo0, ldesc(s), udesc(s));
    wgmma_commit();
    if (GS) {
        if (elect()) { bulk_wait_read<0>(); mbar_expect_tx(gbar, 2048); load_s(12, 4, gbar); }
        __syncwarp();
    }
    send(slc(5), &tmo32, colB, row0);
    wgmma_fence();
#pragma unroll
    for (int s = G1; s < 16; s++) wgmma128<1, 8>(lo0, ldesc(s), udesc(s));
    wgmma_commit();
    bar_arrive(3 + wg);
    RT(4);
    if (elect()) {
        if (GS) { mbar_expect_tx(gbar + 16, 2048); bulk_wait_read<0>(); load_s(13, 5, gbar + 16); }
        else { mbar_expect_tx(gbar, 4096); bulk_wait_read<0>(); load_s(12, 4, gbar); load_s(13, 5, gbar); }
    }
    __syncwarp();
    TSX(wg * 4, 58 + wg);
    wgmma_wait<0>();
    RT(5);
    stagger(SG1);
    if (GL == -1) {
        if (elect()) { mbar_expect_tx(gbar + 8, 4096); load_s(14, 0, gbar + 8); load_s(15, 1, gbar + 8); }
        __syncwarp();
    }
    stage_cols<64, 0>(lo0, slc(2));
    if (E1 == 5) stage_cols<64, 32>(lo0, slc(3));
    if (GL == 0) {
        if (elect()) { mbar_expect_tx(gbar + 8, 4096); load_s(14, 0, gbar + 8); load_s(15, 1, gbar + 8); }
        __syncwarp();
    }
    const bool okg = mbar_try(gbar, 0), okg2 = !GS || mbar_try(gbar + 16, 0);
    send(slc(2), &tmo64, colL, row0);
    TSX(wg * 4, 48 + wg);
    if (GR == 0) mbar_wait1(gbar, 0, okg);
    if (E1 == 5) { if (elect()) { tma_store_2d(&tmo64, slc(3), colL + 64, row0); bulk_commit(); } __syncwarp(); }
    if (E1 < 4) stage_cols<64, 32>(lo0, slc(3));
    if (GL == 1) {
        if (elect()) { mbar_expect_tx(gbar + 8, 4096); load_s(14, 0, gbar + 8); load_s(15, 1, gbar + 8); }
        __syncwarp();
    }
    if (GR == 1) mbar_wait1(gbar, 0, okg);
    if (E1 == 0) send(slc(3), &tmo64, colL + 64, row0);
    RT(6);
    bar_sync(4 + wg);
    RT(7);
    wgmma_fence();
#pragma unroll
    for (int s = 0; s < 4; s++) wgmma128<1, 8>(lo1, gdesc(s), udesc(s));
    if (GS) { mbar_wait1(gbar + 16, 0, okg2); wgmma_fence(); }
#pragma unroll
    for (int s = 4; s < 8; s++) wgmma128<1, 8>(lo1, gdesc(s), udesc(s));
    wgmma_commit();
    const bool okg3 = mbar_try(gbar + 8, 0);
    if (E1 == 1) send(slc(3), &tmo64, colL + 64, row0);
    mbar_wait1(gbar + 8, 0, okg3);
    if (E1 == 4) stage_cols<64, 32>(lo0, slc(3));
    TSX(wg * 4, 52 + wg);
    wgmma_fence();
#pragma unroll
    for (int s = 8; s < 12; s++) wgmma128<1, 8>(lo1, gdesc(s), udesc(s));
    if (E1 == 3) { wgmma_commit(); send(slc(3), &tmo64, colL + 64, row0); wgmma_fence(); }
#pragma unroll
    for (int s = 12; s < 16; s++) wgmma128<1, 8>(lo1, gdesc(s), udesc(s));
    wgmma_commit();
    bar_arrive(5 + wg);
    RT(8);
    if (elect()) bulk_wait_read<0>();
    __syncwarp();
    if (E1 == 2 || E1 == 4) send(slc(3), &tmo64, colL + 64, row0);
    wgmma_wait<0>();
    RT(9);
    stagger(SG2);
    stage_cols<64, 0>(lo1, slc(2));
    if (E2 == 2) stage_cols<64, 32>(lo1, slc(3));
    send(slc(2), &tmo64, colL, row0 + 64);
    if (E2 == 2) { if (elect()) { tma_store_2d(&tmo64, slc(3), colL + 64, row0 + 64); bulk_commit(); } __syncwarp(); }
    if (E1 == 2 || E1 == 4) { if (elect()) bulk_wait_read<1>(); __syncwarp(); }
    if (E2 != 2) stage_cols<64, 32>(lo1, slc(3));
    if (HO && wg == 1) { __syncwarp(); if (elect()) mbar_arrive(ebar + 8 * (2 * (warp & 3) + 1)); __syncwarp(); }
    if (E2 == 0 && wg == 0) send(slc(3), &tmo64, colL + 64, row0 + 64);
    RT(10);
    bar_sync(6 + wg);
    RT(11);
    wgmma_fence();
#pragma unroll
    for (int s = 0; s < G3; s++) wgmma96<1, 8>(hi1, gdesc(s), udesc(s) + 128);
    wgmma_commit();
    if (E2 != 2 && (HO ? wg == 0 : (E2 == 1 || wg == 1))) send(slc(3), &tmo64, colL + 64, row0 + 64);
    wgmma_fence();
#pragma unroll
    for (int s = G3; s < 16; s++) wgmma96<1, 8>(hi1, gdesc(s), udesc(s) + 128);
    wgmma_commit();
    if (wg == 0) bar_arrive(7);
    RT(12);
    wgmma_wait<0>();
    RT(13);
    stagger(wg ? SG4 : SG3);
    if (HO == 1 && wg == 0) { mbar_wait(ebar + 8 * (2 * warp + 1), 0); send(slc(3) + 16384, &tmo64, colL + 64, row0 + 64 + 128); }
    stage_cols<64, 0>(hi1, slc(1));
    if (HO == 2 && wg == 0) { mbar_wait(ebar + 8 * (2 * warp + 1), 0); send(slc(3) + 16384, &tmo64, colL + 64, row0 + 64 + 128); }
    if (E3 == 0) send(slc(1), &tmo64, colA, row0 + 64);
    stage_cols<32, 32>(hi1, slc(5));
    if (E3 == 0) send(slc(5), &tmo32, colB, row0 + 64);
    else {
        fence_async_smem();
        __syncwarp();
        if (elect()) { tma_store_2d(&tmo64, slc(1), colA, row0 + 64); tma_store_2d(&tmo32, slc(5), colB, row0 + 64); bulk_commit(); }
        __syncwarp();
    }
    RT(14);
    if (elect()) bulk_wait_read<0>();
    __syncwarp();
    RT(15);
    TSW(wg * 4, 38 + wg);
    TS_DUMP();
    TL_DUMP();
    cluster_wait();
}

typedef CUresult (*EncodeFn)(CUtensorMap*, CUtensorMapDataType, cuuint32_t, void*, const cuuint64_t*, const cuuint64_t*,
                             const cuuint32_t*, const cuuint32_t*, CUtensorMapInterleave, CUtensorMapSwizzle,
                             CUtensorMapL2promotion, CUtensorMapFloatOOBfill);

extern "C" void kernel_launch(void* const* d_in, const int* in_sizes, int n_in, void* d_out, int out_size) {
    const __nv_bfloat16* x = (const __nv_bfloat16*)d_in[0];
    const int* qw = (const int*)d_in[1];
    const __nv_bfloat16* cb = (const __nv_bfloat16*)d_in[2];
    const __nv_bfloat16* absmax = (const __nv_bfloat16*)d_in[3];
    static EncodeFn encode = nullptr;
    static void *wimg = nullptr, *gflag = nullptr;
    if (!encode) {
        cudaGetSymbolAddress(&wimg, g_wimg);
        cudaGetSymbolAddress(&gflag, g_flag);
        void* fn = nullptr;
        cudaDriverEntryPointQueryResult qr;
        cudaGetDriverEntryPoint("cuTensorMapEncodeTiled", &fn, cudaEnableDefault, &qr);
        encode = (EncodeFn)fn;
        cudaFuncSetAttribute(nf4_gemm_kernel, cudaFuncAttributeMaxDynamicSharedMemorySize, SMEM_BYTES);
    }
    CUtensorMap tmx, tmq, tmo64, tmo32, tmqp, tmx16, tmx64, tmq1;
    {
        cuuint64_t dims[2] = {(cuuint64_t)K_, (cuuint64_t)M_};
        cuuint64_t strides[1] = {(cuuint64_t)K_ * 2};
        cuuint32_t box[2] = {64, 128};
        cuuint32_t es[2] = {1, 1};
        encode(&tmx, CU_TENSOR_MAP_DATA_TYPE_BFLOAT16, 2, (void*)x, dims, strides, box, es, CU_TENSOR_MAP_INTERLEAVE_NONE,
               CU_TENSOR_MAP_SWIZZLE_128B, CU_TENSOR_MAP_L2_PROMOTION_L2_128B, CU_TENSOR_MAP_FLOAT_OOB_FILL_NONE);
        box[1] = 64;
        encode(&tmx64, CU_TENSOR_MAP_DATA_TYPE_BFLOAT16, 2, (void*)x, dims, strides, box, es, CU_TENSOR_MAP_INTERLEAVE_NONE,
               CU_TENSOR_MAP_SWIZZLE_128B, CU_TENSOR_MAP_L2_PROMOTION_L2_128B, CU_TENSOR_MAP_FLOAT_OOB_FILL_NONE);
        box[1] = 16;
        encode(&tmx16, CU_TENSOR_MAP_DATA_TYPE_BFLOAT16, 2, (void*)x, dims, strides, box, es, CU_TENSOR_MAP_INTERLEAVE_NONE,
               CU_TENSOR_MAP_SWIZZLE_128B, CU_TENSOR_MAP_L2_PROMOTION_L2_128B, CU_TENSOR_MAP_FLOAT_OOB_FILL_NONE);
    }
    {
        cuuint64_t dims[5] = {32, 8, (cuuint64_t)(N_ / 32), 2, (cuuint64_t)(K_ / 16)};
        cuuint64_t strides[4] = {(cuuint64_t)N_ * 4, 128, (cuuint64_t)N_ * 4 * 8, (cuuint64_t)N_ * 4 * 16};
        cuuint32_t box[5] = {32, 8, 7, 1, 2};
        cuuint32_t es[5] = {1, 1, 1, 1, 1};
        encode(&tmq, CU_TENSOR_MAP_DATA_TYPE_INT32, 5, (void*)qw, dims, strides, box, es, CU_TENSOR_MAP_INTERLEAVE_NONE,
               CU_TENSOR_MAP_SWIZZLE_128B, CU_TENSOR_MAP_L2_PROMOTION_L2_128B, CU_TENSOR_MAP_FLOAT_OOB_FILL_NONE);
        box[4] = 1;
        encode(&tmq1, CU_TENSOR_MAP_DATA_TYPE_INT32, 5, (void*)qw, dims, strides, box, es, CU_TENSOR_MAP_INTERLEAVE_NONE,
               CU_TENSOR_MAP_SWIZZLE_128B, CU_TENSOR_MAP_L2_PROMOTION_L2_128B, CU_TENSOR_MAP_FLOAT_OOB_FILL_NONE);
        cuuint64_t dims2[2] = {(cuuint64_t)N_, (cuuint64_t)K_};
        cuuint32_t box2[2] = {224, 8};
        encode(&tmqp, CU_TENSOR_MAP_DATA_TYPE_INT32, 2, (void*)qw, dims2, strides, box2, es, CU_TENSOR_MAP_INTERLEAVE_NONE,
               CU_TENSOR_MAP_SWIZZLE_NONE, CU_TENSOR_MAP_L2_PROMOTION_L2_128B, CU_TENSOR_MAP_FLOAT_OOB_FILL_NONE);
    }
    {
        cuuint64_t dims[2] = {(cuuint64_t)N_, (cuuint64_t)M_};
        cuuint64_t strides[1] = {(cuuint64_t)N_ * 2};
        cuuint32_t box[2] = {64, 16};
        cuuint32_t es[2] = {1, 1};
        encode(&tmo64, CU_TENSOR_MAP_DATA_TYPE_BFLOAT16, 2, d_out, dims, strides, box, es, CU_TENSOR_MAP_INTERLEAVE_NONE,
               CU_TENSOR_MAP_SWIZZLE_128B, CU_TENSOR_MAP_L2_PROMOTION_NONE, CU_TENSOR_MAP_FLOAT_OOB_FILL_NONE);
        box[0] = 32;
        encode(&tmo32, CU_TENSOR_MAP_DATA_TYPE_BFLOAT16, 2, d_out, dims, strides, box, es, CU_TENSOR_MAP_INTERLEAVE_NONE,
               CU_TENSOR_MAP_SWIZZLE_64B, CU_TENSOR_MAP_L2_PROMOTION_NONE, CU_TENSOR_MAP_FLOAT_OOB_FILL_NONE);
    }
    nf4_gemm_kernel<<<128, 256, SMEM_BYTES>>>(qw, cb, absmax, (uint8_t*)wimg, (unsigned*)gflag, tmx, tmq, tmo64, tmo32, tmqp, tmx16, tmx64, tmq1);
}
```

```cpp
#include <cuda_runtime.h>
#include <cuda_bf16.h>
#include <cuda.h>
#include <stdint.h>

constexpr int M_ = 2048, K_ = 1024, N_ = 3584;
constexpr int BM = 256, BN = 224;
constexpr int UNIT = 14336;
constexpr int NW = 6, NR = 3;
constexpr int RAW_OFF = 3 * 32768;
constexpr int SC_OFF = RAW_OFF + 2 * UNIT;
constexpr int W_OFF = 127 * 1024;
constexpr int RAW2_OFF = W_OFF + NW * UNIT;
constexpr int BAR_OFF = RAW2_OFF + UNIT;
__host__ __device__ constexpr int roff(int slot) { return slot < 2 ? slot * UNIT : RAW2_OFF - RAW_OFF; }
constexpr int SMEM_BYTES = BAR_OFF + 320;
#define TRAPSTR ""
#define DLEAD 6
#define PFQ 4
#define PFX 3
#define FT 38
#define TSP 2
#define LATE0 12
#define XLATE 1
#define STFIRST 0
#define RAWFIRST 0
#define F0 2
#define RAMP 4
#define C0 2
#define C1 11

#define SPL1 8
#define SPL3 8
#define E1 1
#define E2 1
#define PUBD 1
#define G1 7
#define G3 9
#define E3 0
#define E0 2
#define TLPRO -2
#define LEAD0 0x4345556666666666ull
#define LEAD1 LEAD0
#define HM1 4
#define HM2 4
#define HM3 4
#define PB 5
#define T2 900
#define T3 1700
#define X2AT 1
#define XLAG 0
#define T2B 1300
#define G2S 0
#define PM 0
#define DEF 4
#define TB 4
#define ORD1 2
#define GS 0
#define GL 0
#define GR 1
#define MAPM 0
#define HO 0
#define SG0 0
#define SG1 0
#define SG2 0
#define SG3 0
#define SG4 0
#define ALIGNO 1
#define TLIT 2
#define PFL 1
#define WREDUX 1
#define X0B 0
#define GUEST 7
#define PFG 1
constexpr int NU = 26;
constexpr int SC_STRIDE = 464;
__device__ __align__(1024) uint8_t g_wimg[16 * 8 * UNIT];
__device__ __align__(128) unsigned g_flag[16 * 32];

#define TSL(i)
#define TL_DUMP()
#define TSW(w, i)
#define TS_INIT()
#define TS_DUMP()

#define TSX(w, i)
#define RT(i)
__device__ __forceinline__ uint32_t smem_u32(const void* p) { return (uint32_t)__cvta_generic_to_shared(p); }
__device__ __forceinline__ bool elect() {
    uint32_t ok;
    asm volatile("{\n.reg .pred p;\nelect.sync _|p, 0xffffffff;\nselp.u32 %0, 1, 0, p;\n}\n" : "=r"(ok));
    return ok != 0;
}
__device__ __forceinline__ void mbar_init(uint32_t bar, uint32_t cnt) { asm volatile("mbarrier.init.shared::cta.b64 [%0], %1;" ::"r"(bar), "r"(cnt) : "memory"); }
__device__ __forceinline__ void mbar_expect_tx(uint32_t bar, uint32_t bytes) { asm volatile("mbarrier.arrive.expect_tx.shared::cta.b64 _, [%0], %1;" ::"r"(bar), "r"(bytes) : "memory"); }
__device__ __forceinline__ void mbar_arrive(uint32_t bar) { asm volatile("mbarrier.arrive.shared::cta.b64 _, [%0];" ::"r"(bar) : "memory"); }
__device__ __forceinline__ void mbar_arrive_cluster(uint32_t cbar) { asm volatile("mbarrier.arrive.shared::cluster.b64 _, [%0];" ::"r"(cbar) : "memory"); }
__device__ __forceinline__ void mbar_arrive_cluster_if(bool c, uint32_t cbar) {
    asm volatile("{\n.reg .pred p;\nsetp.ne.u32 p, %1, 0;\n@p mbarrier.arrive.shared::cluster.b64 _, [%0];\n}\n" ::"r"(cbar), "r"((uint32_t)c) : "memory");
}
#define BOUNDED
#define WAIT_INIT "mov.u32 n, 0;\n"
#define WAIT_NEXT "@p bra.uni LAB_DONE;\nadd.u32 n, n, 1;\nsetp.lt.u32 p, n, 0x4000;\n@p bra.uni LAB_WAIT;\n"
__device__ __forceinline__ void mbar_wait(uint32_t bar, uint32_t parity) {
    asm volatile(
        "{\n.reg .pred p;\n.reg .u32 n;\n"
        WAIT_INIT
        "LAB_WAIT:\n"
        "mbarrier.try_wait.parity.shared::cta.b64 p, [%0], %1;\n"
        WAIT_NEXT
        "LAB_DONE:\n}\n" ::"r"(bar), "r"(parity) : "memory");
}
__device__ __forceinline__ bool mbar_try(uint32_t bar, uint32_t parity) {
    uint32_t ok;
    asm volatile("{\n.reg .pred p;\nmbarrier.test_wait.parity.shared::cta.b64 p, [%1], %2;\nselp.u32 %0, 1, 0, p;\n}\n" : "=r"(ok) : "r"(bar), "r"(parity) : "memory");
    return ok != 0;
}
__device__ __forceinline__ void mbar_wait1(uint32_t b0, uint32_t p0, bool skip) {
    asm volatile(
        "{\n.reg .pred p;\n.reg .u32 n;\n"
        "setp.ne.u32 p, %2, 0;\n@p bra.uni LAB_DONE;\n"
        WAIT_INIT
        "LAB_WAIT:\n"
        "mbarrier.try_wait.parity.shared::cta.b64 p, [%0], %1;\n"
        WAIT_NEXT
        "LAB_DONE:\n}\n" ::"r"(b0), "r"(p0), "r"((uint32_t)skip) : "memory");
}
__device__ __forceinline__ void mbar_wait2(uint32_t b0, uint32_t p0, uint32_t b1, uint32_t p1, bool skip = false) {
    asm volatile(
        "{\n.reg .pred p, q;\n.reg .u32 n;\n"
        "setp.ne.u32 p, %4, 0;\n@p bra.uni LAB_DONE;\n"
        WAIT_INIT
        "LAB_WAIT:\n"
        "mbarrier.try_wait.parity.shared::cta.b64 p, [%0], %1;\n"
        "mbarrier.try_wait.parity.shared::cta.b64 q, [%2], %3;\n"
        "and.pred p, p, q;\n"
        WAIT_NEXT
        "LAB_DONE:\n}\n" ::"r"(b0), "r"(p0), "r"(b1), "r"(p1), "r"((uint32_t)skip) : "memory");
}
__device__ __forceinline__ void mbar_wait3(uint32_t b0, uint32_t p0, uint32_t b1, uint32_t p1, uint32_t b2, uint32_t p2, bool skip = false) {
    asm volatile(
        "{\n.reg .pred p, q, r;\n.reg .u32 n;\n"
        "setp.ne.u32 p, %6, 0;\n@p bra.uni LAB_DONE;\n"
        WAIT_INIT
        "LAB_WAIT:\n"
        "mbarrier.try_wait.parity.shared::cta.b64 p, [%0], %1;\n"
        "mbarrier.try_wait.parity.shared::cta.b64 q, [%2], %3;\n"
        "mbarrier.try_wait.parity.shared::cta.b64 r, [%4], %5;\n"
        "and.pred p, p, q;\n"
        "and.pred p, p, r;\n"
        WAIT_NEXT
        "LAB_DONE:\n}\n" ::"r"(b0), "r"(p0), "r"(b1), "r"(p1), "r"(b2), "r"(p2), "r"((uint32_t)skip) : "memory");
}
__device__ __forceinline__ void tma_load_2d(uint32_t dst, const CUtensorMap* tm, int c0, int c1, uint32_t bar) {
    asm volatile("cp.async.bulk.tensor.2d.shared::cluster.global.mbarrier::complete_tx::bytes [%0], [%1, {%2, %3}], [%4];"
                 ::"r"(dst), "l"(tm), "r"(c0), "r"(c1), "r"(bar) : "memory");
}
__device__ __forceinline__ void tma_load_4d(uint32_t dst, const CUtensorMap* tm, int c0, int c1, int c2, int c3, uint32_t bar) {
    asm volatile("cp.async.bulk.tensor.4d.shared::cluster.global.mbarrier::complete_tx::bytes [%0], [%1, {%2, %3, %4, %5}], [%6];"
                 ::"r"(dst), "l"(tm), "r"(c0), "r"(c1), "r"(c2), "r"(c3), "r"(bar) : "memory");
}
__device__ __forceinline__ void tma_load_5d(uint32_t dst, const CUtensorMap* tm, int c0, int c1, int c2, int c3, int c4, uint32_t bar) {
    asm volatile("cp.async.bulk.tensor.5d.shared::cluster.global.mbarrier::complete_tx::bytes [%0], [%1, {%2, %3, %4, %5, %6}], [%7];"
                 ::"r"(dst), "l"(tm), "r"(c0), "r"(c1), "r"(c2), "r"(c3), "r"(c4), "r"(bar) : "memory");
}
__device__ __forceinline__ void tma_prefetch_2d(const CUtensorMap* tm, int c0, int c1) {
    asm volatile("cp.async.bulk.prefetch.tensor.2d.L2.global [%0, {%1, %2}];" ::"l"(tm), "r"(c0), "r"(c1) : "memory");
}
__device__ __forceinline__ void bulk_load(uint32_t dst, const void* src, uint32_t bytes, uint32_t bar) {
    asm volatile("cp.async.bulk.shared::cluster.global.mbarrier::complete_tx::bytes [%0], [%1], %2, [%3];"
                 ::"r"(dst), "l"(src), "r"(bytes), "r"(bar) : "memory");
}
__device__ __forceinline__ void tma_store_3d(const CUtensorMap* tm, uint32_t src, int c0, int c1, int c2) {
    asm volatile("cp.async.bulk.tensor.3d.global.shared::cta.bulk_group [%0, {%2, %3, %4}], [%1];"
                 ::"l"(tm), "r"(src), "r"(c0), "r"(c1), "r"(c2) : "memory");
}
__device__ __forceinline__ void cluster_arrive() { asm volatile("barrier.cluster.arrive.relaxed.aligned;" ::: "memory"); }
__device__ __forceinline__ void cluster_wait() { asm volatile("barrier.cluster.wait.acquire.aligned;" ::: "memory"); }
__device__ __forceinline__ uint32_t mapa(uint32_t addr, uint32_t cta) {
    uint32_t r; asm("mapa.shared::cluster.u32 %0, %1, %2;" : "=r"(r) : "r"(addr), "r"(cta)); return r;
}
__device__ __forceinline__ void copy_to_peer(uint32_t cdst, uint32_t src, uint32_t bytes, uint32_t cbar) {
    asm volatile("cp.async.bulk.shared::cluster.shared::cta.mbarrier::complete_tx::bytes [%0], [%1], %2, [%3];"
                 ::"r"(cdst), "r"(src), "r"(bytes), "r"(cbar) : "memory");
}
__device__ __forceinline__ void wgmma_fence() { asm volatile("wgmma.fence.sync.aligned;" ::: "memory"); }
__device__ __forceinline__ void wgmma_commit() { asm volatile("wgmma.commit_group.sync.aligned;" ::: "memory"); }
template <int N> __device__ __forceinline__ void wgmma_wait() { asm volatile("wgmma.wait_group.sync.aligned %0;" ::"n"(N) : "memory"); }
__device__ __forceinline__ uint32_t pack_bf16(float lo, float hi) {
    uint32_t r; asm("cvt.rn.bf16x2.f32 %0, %1, %2;" : "=r"(r) : "f"(hi), "f"(lo)); return r;
}
__device__ __forceinline__ void stmatrix_x4(uint32_t addr, uint32_t a, uint32_t b, uint32_t c, uint32_t d) {
    asm volatile("stmatrix.sync.aligned.m8n8.x4.shared.b16 [%0], {%1, %2, %3, %4};" ::"r"(addr), "r"(a), "r"(b), "r"(c), "r"(d) : "memory");
}
__device__ __forceinline__ uint4 lds128(uint32_t a) {
    uint4 v; asm volatile("ld.shared.v4.b32 {%0, %1, %2, %3}, [%4];" : "=r"(v.x), "=r"(v.y), "=r"(v.z), "=r"(v.w) : "r"(a) : "memory"); return v;
}
__device__ __forceinline__ void sts128(uint32_t a, uint4 v) {
    asm volatile("st.shared.v4.b32 [%0], {%1, %2, %3, %4};" ::"r"(a), "r"(v.x), "r"(v.y), "r"(v.z), "r"(v.w) : "memory");
}
__device__ __forceinline__ void sts128x(uint32_t a, uint4 v) {
    asm volatile("st.shared.v4.b32 [%0], {%1, %2, %3, %4};" ::"r"(a), "r"(v.x), "r"(v.y), "r"(v.z), "r"(v.w) : "memory");
}
__device__ __forceinline__ uint4 ldg128(const void* p) {
    uint4 v; asm volatile("ld.global.nc.v4.b32 {%0, %1, %2, %3}, [%4];" : "=r"(v.x), "=r"(v.y), "=r"(v.z), "=r"(v.w) : "l"(p) : "memory"); return v;
}
__device__ __forceinline__ unsigned clk() { unsigned c; asm volatile("mov.u32 %0, %%clock;" : "=r"(c) :: "memory"); return c; }
__device__ __forceinline__ uint32_t mul_bf16x2(uint32_t a, uint32_t b) { uint32_t r; asm("mul.rn.bf16x2 %0, %1, %2;" : "=r"(r) : "r"(a), "r"(b)); return r; }
struct Lut { uint32_t lo[4], hi[4]; };
__device__ __forceinline__ uint32_t prmt(uint32_t a, uint32_t b, uint32_t s) { uint32_t r; asm("prmt.b32 %0, %1, %2, %3;" : "=r"(r) : "r"(a), "r"(b), "r"(s)); return r; }
__device__ __forceinline__ uint32_t pack4(const uint4& q) {
    uint32_t ab, cd, p;
    asm volatile("mad.lo.u32 %0, %1, 16, %2;" : "=r"(ab) : "r"(q.y), "r"(q.x));
    asm volatile("mad.lo.u32 %0, %1, 16, %2;" : "=r"(cd) : "r"(q.w), "r"(q.z));
    asm volatile("mad.lo.u32 %0, %1, 256, %2;" : "=r"(p) : "r"(cd), "r"(ab));
    return p;
}
__device__ __forceinline__ void lookup4(uint32_t p, const Lut& t, uint32_t& w01, uint32_t& w23) {
    const uint32_t t8 = p & 0x8888u, s7 = p & 0x7777u;
    const uint32_t sel = (t8 >> 1) + 0x3210u;
    const uint32_t lo = prmt(prmt(t.lo[0], t.lo[1], p), prmt(t.lo[2], t.lo[3], s7), sel);
    const uint32_t hi = prmt(prmt(t.hi[0], t.hi[1], p), prmt(t.hi[2], t.hi[3], s7), sel);
    w01 = prmt(lo, hi, 0x5140);
    w23 = prmt(lo, hi, 0x7362);
}
__device__ __forceinline__ uint4 dequant8(uint32_t p0, uint32_t p1, const uint4& sc, const Lut& tu) {
    uint4 r;
    const Lut& t = tu;
    lookup4(p0, t, r.x, r.y);
    lookup4(p1, t, r.z, r.w);
    r.x = mul_bf16x2(r.x, sc.x); r.y = mul_bf16x2(r.y, sc.y); r.z = mul_bf16x2(r.z, sc.z); r.w = mul_bf16x2(r.w, sc.w);
    return r;
}
__device__ __forceinline__ void fence_async_smem() { asm volatile("fence.proxy.async.shared::cta;" ::: "memory"); }

template <int SCALE_D, int BHI, uint32_t AHI = 0x40000040u>
__device__ __forceinline__ void wgmma224(float (&d)[112], uint32_t descA, uint32_t descB) {
    asm volatile(
        "{\n.reg .pred p;\n.reg .b64 da, db;\nsetp.ne.b32 p, %114, 0;\n"
        "mov.b64 da, {%112, %116};\nmov.b64 db, {%113, %115};\n"
        "wgmma.mma_async.sync.aligned.m64n224k16.f32.bf16.bf16 "
        "{%0, %1, %2, %3, %4, %5, %6, %7, %8, %9, %10, %11, %12, %13, %14, %15, "
        "%16, %17, %18, %19, %20, %21, %22, %23, %24, %25, %26, %27, %28, %29, %30, %31, "
        "%32, %33, %34, %35, %36, %37, %38, %39, %40, %41, %42, %43, %44, %45, %46, %47, "
        "%48, %49, %50, %51, %52, %53, %54, %55, %56, %57, %58, %59, %60, %61, %62, %63, "
        "%64, %65, %66, %67, %68, %69, %70, %71, %72, %73, %74, %75, %76, %77, %78, %79, "
        "%80, %81, %82, %83, %84, %85, %86, %87, %88, %89, %90, %91, %92, %93, %94, %95, "
        "%96, %97, %98, %99, %100, %101, %102, %103, %104, %105, %106, %107, %108, %109, %110, %111}, "
        "da, db, p, 1, 1, 0, 1;\n}\n"
        : "+f"(d[0]), "+f"(d[1]), "+f"(d[2]), "+f"(d[3]), "+f"(d[4]), "+f"(d[5]), "+f"(d[6]), "+f"(d[7]),
          "+f"(d[8]), "+f"(d[9]), "+f"(d[10]), "+f"(d[11]), "+f"(d[12]), "+f"(d[13]), "+f"(d[14]), "+f"(d[15]),
          "+f"(d[16]), "+f"(d[17]), "+f"(d[18]), "+f"(d[19]), "+f"(d[20]), "+f"(d[21]), "+f"(d[22]), "+f"(d[23]),
          "+f"(d[24]), "+f"(d[25]), "+f"(d[26]), "+f"(d[27]), "+f"(d[28]), "+f"(d[29]), "+f"(d[30]), "+f"(d[31]),
          "+f"(d[32]), "+f"(d[33]), "+f"(d[34]), "+f"(d[35]), "+f"(d[36]), "+f"(d[37]), "+f"(d[38]), "+f"(d[39]),
          "+f"(d[40]), "+f"(d[41]), "+f"(d[42]), "+f"(d[43]), "+f"(d[44]), "+f"(d[45]), "+f"(d[46]), "+f"(d[47]),
          "+f"(d[48]), "+f"(d[49]), "+f"(d[50]), "+f"(d[51]), "+f"(d[52]), "+f"(d[53]), "+f"(d[54]), "+f"(d[55]),
          "+f"(d[56]), "+f"(d[57]), "+f"(d[58]), "+f"(d[59]), "+f"(d[60]), "+f"(d[61]), "+f"(d[62]), "+f"(d[63]),
          "+f"(d[64]), "+f"(d[65]), "+f"(d[66]), "+f"(d[67]), "+f"(d[68]), "+f"(d[69]), "+f"(d[70]), "+f"(d[71]),
          "+f"(d[72]), "+f"(d[73]), "+f"(d[74]), "+f"(d[75]), "+f"(d[76]), "+f"(d[77]), "+f"(d[78]), "+f"(d[79]),
          "+f"(d[80]), "+f"(d[81]), "+f"(d[82]), "+f"(d[83]), "+f"(d[84]), "+f"(d[85]), "+f"(d[86]), "+f"(d[87]),
          "+f"(d[88]), "+f"(d[89]), "+f"(d[90]), "+f"(d[91]), "+f"(d[92]), "+f"(d[93]), "+f"(d[94]), "+f"(d[95]),
          "+f"(d[96]), "+f"(d[97]), "+f"(d[98]), "+f"(d[99]), "+f"(d[100]), "+f"(d[101]), "+f"(d[102]), "+f"(d[103]),
          "+f"(d[104]), "+f"(d[105]), "+f"(d[106]), "+f"(d[107]), "+f"(d[108]), "+f"(d[109]), "+f"(d[110]), "+f"(d[111])
        : "r"(descA), "r"(descB), "n"(SCALE_D), "n"(BHI), "n"(AHI));
}

template <int SCALE_D, int BHI, uint32_t AHI = 0x40000040u>
__device__ __forceinline__ void wgmma128(float (&d)[64], uint32_t descA, uint32_t descB) {
    asm volatile(
        "{\n.reg .pred p;\n.reg .b64 da, db;\nsetp.ne.b32 p, %66, 0;\n"
        "mov.b64 da, {%64, %68};\nmov.b64 db, {%65, %67};\n"
        "wgmma.mma_async.sync.aligned.m64n128k16.f32.bf16.bf16 "
        "{%0, %1, %2, %3, %4, %5, %6, %7, %8, %9, %10, %11, %12, %13, %14, %15, "
        "%16, %17, %18, %19, %20, %21, %22, %23, %24, %25, %26, %27, %28, %29, %30, %31, "
        "%32, %33, %34, %35, %36, %37, %38, %39, %40, %41, %42, %43, %44, %45, %46, %47, "
        "%48, %49, %50, %51, %52, %53, %54, %55, %56, %57, %58, %59, %60, %61, %62, %63}, "
        "da, db, p, 1, 1, 0, 1;\n}\n"
        : "+f"(d[0]), "+f"(d[1]), "+f"(d[2]), "+f"(d[3]), "+f"(d[4]), "+f"(d[5]), "+f"(d[6]), "+f"(d[7]),
          "+f"(d[8]), "+f"(d[9]), "+f"(d[10]), "+f"(d[11]), "+f"(d[12]), "+f"(d[13]), "+f"(d[14]), "+f"(d[15]),
          "+f"(d[16]), "+f"(d[17]), "+f"(d[18]), "+f"(d[19]), "+f"(d[20]), "+f"(d[21]), "+f"(d[22]), "+f"(d[23]),
          "+f"(d[24]), "+f"(d[25]), "+f"(d[26]), "+f"(d[27]), "+f"(d[28]), "+f"(d[29]), "+f"(d[30]), "+f"(d[31]),
          "+f"(d[32]), "+f"(d[33]), "+f"(d[34]), "+f"(d[35]), "+f"(d[36]), "+f"(d[37]), "+f"(d[38]), "+f"(d[39]),
          "+f"(d[40]), "+f"(d[41]), "+f"(d[42]), "+f"(d[43]), "+f"(d[44]), "+f"(d[45]), "+f"(d[46]), "+f"(d[47]),
          "+f"(d[48]), "+f"(d[49]), "+f"(d[50]), "+f"(d[51]), "+f"(d[52]), "+f"(d[53]), "+f"(d[54]), "+f"(d[55]),
          "+f"(d[56]), "+f"(d[57]), "+f"(d[58]), "+f"(d[59]), "+f"(d[60]), "+f"(d[61]), "+f"(d[62]), "+f"(d[63])
        : "r"(descA), "r"(descB), "n"(SCALE_D), "n"(BHI), "n"(AHI));
}

template <int SCALE_D, int BHI, uint32_t AHI = 0x40000040u>
__device__ __forceinline__ void wgmma96(float (&d)[48], uint32_t descA, uint32_t descB) {
    asm volatile(
        "{\n.reg .pred p;\n.reg .b64 da, db;\nsetp.ne.b32 p, %50, 0;\n"
        "mov.b64 da, {%48, %52};\nmov.b64 db, {%49, %51};\n"
        "wgmma.mma_async.sync.aligned.m64n96k16.f32.bf16.bf16 "
        "{%0, %1, %2, %3, %4, %5, %6, %7, %8, %9, %10, %11, %12, %13, %14, %15, "
        "%16, %17, %18, %19, %20, %21, %22, %23, %24, %25, %26, %27, %28, %29, %30, %31, "
        "%32, %33, %34, %35, %36, %37, %38, %39, %40, %41, %42, %43, %44, %45, %46, %47}, "
        "da, db, p, 1, 1, 0, 1;\n}\n"
        : "+f"(d[0]), "+f"(d[1]), "+f"(d[2]), "+f"(d[3]), "+f"(d[4]), "+f"(d[5]), "+f"(d[6]), "+f"(d[7]),
          "+f"(d[8]), "+f"(d[9]), "+f"(d[10]), "+f"(d[11]), "+f"(d[12]), "+f"(d[13]), "+f"(d[14]), "+f"(d[15]),
          "+f"(d[16]), "+f"(d[17]), "+f"(d[18]), "+f"(d[19]), "+f"(d[20]), "+f"(d[21]), "+f"(d[22]), "+f"(d[23]),
          "+f"(d[24]), "+f"(d[25]), "+f"(d[26]), "+f"(d[27]), "+f"(d[28]), "+f"(d[29]), "+f"(d[30]), "+f"(d[31]),
          "+f"(d[32]), "+f"(d[33]), "+f"(d[34]), "+f"(d[35]), "+f"(d[36]), "+f"(d[37]), "+f"(d[38]), "+f"(d[39]),
          "+f"(d[40]), "+f"(d[41]), "+f"(d[42]), "+f"(d[43]), "+f"(d[44]), "+f"(d[45]), "+f"(d[46]), "+f"(d[47])
        : "r"(descA), "r"(descB), "n"(SCALE_D), "n"(BHI), "n"(AHI));
}

__device__ __forceinline__ uint32_t opq(uint32_t v) { asm volatile("" : "+r"(v)); return v; }
template <int I> struct IC { static constexpr int value = I; };
template <int B, int E, class F> __device__ __forceinline__ void static_for(F&& f) {
    if constexpr (B < E) { f(IC<B>{}); static_for<B + 1, E>(f); }
}

__device__ __forceinline__ void tma_store_2d(const CUtensorMap* tm, uint32_t src, int c0, int c1) {
    asm volatile("cp.async.bulk.tensor.2d.global.shared::cta.bulk_group [%0, {%2, %3}], [%1];" ::"l"(tm), "r"(src), "r"(c0), "r"(c1) : "memory");
}
__device__ __forceinline__ void bulk_store(void* dst, uint32_t src, uint32_t bytes) {
    asm volatile("cp.async.bulk.global.shared::cta.bulk_group [%0], [%1], %2;" ::"l"(dst), "r"(src), "r"(bytes) : "memory");
}
__device__ __forceinline__ void bulk_commit() { asm volatile("cp.async.bulk.commit_group;" ::: "memory"); }
template <int N> __device__ __forceinline__ void bulk_wait_read() { asm volatile("cp.async.bulk.wait_group.read %0;" ::"n"(N) : "memory"); }
__device__ __forceinline__ void bar_arrive(int id) { asm volatile("bar.arrive %0, 256;" ::"r"(id) : "memory"); }
__device__ __forceinline__ void bar_sync(int id) { asm volatile("bar.sync %0, 256;" ::"r"(id) : "memory"); }
template <int NC, int OFF, int N>
__device__ __forceinline__ void stage_cols(const float (&acc)[N], uint32_t stg) {
    int lane; asm volatile("mov.u32 %0, %%laneid;" : "=r"(lane));
    const int r = lane & 15;
    const uint32_t a0 = NC == 64 ? stg + r * 128 + (((lane >> 4) ^ (r & 7)) << 4) : stg + r * 64 + (((lane >> 4) ^ ((r >> 1) & 3)) << 4);
#pragma unroll
    for (int j = 0; j < NC / 16; j++) {
        const int i = OFF + 8 * j;
        stmatrix_x4(a0 ^ (j * 32), pack_bf16(acc[i], acc[i + 1]), pack_bf16(acc[i + 2], acc[i + 3]), pack_bf16(acc[i + 4], acc[i + 5]), pack_bf16(acc[i + 6], acc[i + 7]));
    }
}
__device__ __forceinline__ void send(uint32_t stg, const CUtensorMap* tmo, int col, int row) {
    fence_async_smem();
    __syncwarp();
    if (elect()) { tma_store_2d(tmo, stg, col, row); bulk_commit(); }
    __syncwarp();
}

__host__ __device__ constexpr int fconv(int g, int s) {
    return s + (s < 16 ? (int)(((g ? LEAD1 : LEAD0) >> (60 - 4 * s)) & 15) : 6);
}
__host__ __device__ constexpr int sub_of(int g, int b) { int s = -1; while (fconv(g, s + 1) <= b) s++; return s; }
__host__ __device__ constexpr int sub_min(int b) { return sub_of(0, b) < sub_of(1, b) ? sub_of(0, b) : sub_of(1, b); }
__host__ __device__ constexpr int sub_max(int b) { return sub_of(0, b) > sub_of(1, b) ? sub_of(0, b) : sub_of(1, b); }
__host__ __device__ constexpr int hmode(int u) { return u <= 1 ? 1 : u < HM1 ? 0 : u < HM2 ? 1 : u < HM3 ? 2 : 3; }
__host__ __device__ constexpr int t7(int v) { return sub_max(2 * v + 1) + (hmode(v) == 2 ? 0 : 1); }
__host__ __device__ constexpr int t7b(int b) { return sub_max(b) + (sub_min(b + 1) == sub_max(b) ? 0 : 1); }
__host__ __device__ constexpr int xunit(int i) { int v = 0; while (sub_min(2 * v + 1) < 4 * i - 7) v++; return v; }
__host__ __device__ constexpr int rslot(int u) { return (2 * u) % 3; }
__host__ __device__ constexpr int rpar(int u) { return (u / 3 - (u % 3 == 0)) & 1; }
__host__ __device__ constexpr int sslot(int c) { return c < 3 ? c + 3 : c % 3; }

__global__ void __cluster_dims__(2, 1, 1) __launch_bounds__(256, 1)
nf4_gemm_kernel(const int* __restrict__ qw, const __nv_bfloat16* __restrict__ cb, const __nv_bfloat16* __restrict__ absmax,
                uint8_t* __restrict__ wimg, unsigned* __restrict__ gflag,
                const __grid_constant__ CUtensorMap tmx, const __grid_constant__ CUtensorMap tmq, const __grid_constant__ CUtensorMap tmo64,
                const __grid_constant__ CUtensorMap tmo32, const __grid_constant__ CUtensorMap tmqp, const __grid_constant__ CUtensorMap tmx16,
                const __grid_constant__ CUtensorMap tmx64, const __grid_constant__ CUtensorMap tmq1) {
    extern __shared__ __align__(1024) uint8_t smem[];
    const uint32_t sbase = smem_u32(smem);
    const int rank = blockIdx.x, nt = blockIdx.y;
    uint4 q[4], c0, c1;
    uint2 sf;
    if (threadIdx.x < 224) {
        const uint32_t t = threadIdx.x;
        const int* p = qw + (uint32_t)((t & 3) * (N_ - 1) + t + blockIdx.x * (8 * N_) + blockIdx.y * BN);
        q[0] = ldg128(p); q[1] = ldg128(p + 4 * N_);
        q[2] = ldg128(p + 16 * N_); q[3] = ldg128(p + 20 * N_);
        const void* ps = absmax + (uint32_t)(opq(t & ~3u) + blockIdx.y * BN);
        asm volatile("ld.global.nc.v2.b32 {%0, %1}, [%2];" : "=r"(sf.x), "=r"(sf.y) : "l"(ps) : "memory");
        c0 = ldg128(cb); c1 = ldg128(cb + 8);
    }
    const unsigned tstart = clk();
    const int mt = blockIdx.z * 2 + rank;
    const int lane = threadIdx.x & 31;
    const int warp = WREDUX ? __reduce_max_sync(~0u, threadIdx.x >> 5) : __shfl_sync(~0u, (int)(threadIdx.x >> 5), 0);
    const int wg = warp >> 2;
    const uint32_t bars = sbase + BAR_OFF;
    const uint32_t fullW = bars, rawfull = bars + 48, written = bars + 72, xbar = bars + 96, gbar = bars + 112 + wg * 24;
    const uint32_t x1bar = bars + 160, rawh = bars + 176 - 8, ebar = bars + 200;
    const uint32_t wbase = sbase + W_OFF;
    TS_INIT();
    __syncwarp();
    TSW(0, 0);

    const int pair = mt >> 1;
    auto chunk = [&](int i) { return i < GUEST ? i : i == GUEST ? 12 + pair : i <= 12 ? i - 1 : 12 + ((pair + i) & 3); };
    unsigned* flag = gflag + nt * 32;
    uint8_t* wpan = wimg + nt * 8 * UNIT;
    auto load_x = [&](int i, int slot) {
        tma_load_2d(sbase + slot * 32768, &tmx, chunk(i) * 64, mt * BM, fullW + 16 * slot);
        tma_load_2d(sbase + slot * 32768 + 16384, &tmx, chunk(i) * 64, mt * BM + 128, fullW + 16 * slot);
    };
    auto load_sc = [&](int i, int ss, uint32_t bar) {
        bulk_load(sbase + SC_OFF + ss * SC_STRIDE, absmax + chunk(i) * N_ + nt * BN, 448, bar);
        bulk_load(sbase + SC_OFF + ss * SC_STRIDE + 448, flag, 16, bar);
    };
    auto load_raw = [&](int u, int slot) {
        mbar_expect_tx(rawfull + 8 * slot, UNIT);
        tma_load_5d(sbase + RAW_OFF + roff(slot), &tmq, 0, 0, nt * 7, rank, 4 * chunk(u >> 1) + 2 * (u & 1), rawfull + 8 * slot);
    };
    auto load_half = [&](int b, uint32_t more) {
        const uint32_t bar = (b & 1) ? rawfull + 8 * rslot(b >> 1) : rawh + 8 * (b >> 1);
        mbar_expect_tx(bar, 7168 + more);
        tma_load_5d(sbase + RAW_OFF + roff(rslot(b >> 1)) + (b & 1) * 7168, &tmq1, 0, 0, nt * 7, rank, b, bar);
    };
    auto load_xh = [&](int i, int g, uint32_t bar) {
        mbar_expect_tx(bar, 16384);
        tma_load_2d(sbase + i * 32768 + g * 16384, &tmx, i * 64, mt * BM + g * 128, bar);
    };
    auto prefetch = [&](int c) {
        if (PFQ && c + PFQ < 12) tma_prefetch_2d(&tmqp, nt * BN, (c + PFQ) * 64 + pair * 16 + rank * 8);
        if (PFQ && (unsigned)(c - PFG) < 4) tma_prefetch_2d(&tmqp, nt * BN, (12 + pair) * 64 + (c - PFG) * 16 + rank * 8);
        if (PFX && c + PFX < 16 && c + PFX > 2) tma_prefetch_2d(&tmx16, chunk(c + PFX) * 64, mt * BM + nt * 16);
        if (PFL && c >= 9) tma_prefetch_2d(&tmx16, chunk(c + 5) * 64, mt * BM + nt * 16);
    };
    if (warp == 7) {
        if (elect()) {
            mbar_init(xbar, 1); mbar_init(rawh + 8, 1); mbar_init(rawfull + 8 * rslot(1), 1); mbar_init(xbar + 8, 1);
            fence_async_smem();
            if (ORD1 == 0) load_xh(0, 0, xbar);
            load_half(2, 448);
            bulk_load(sbase + SC_OFF + sslot(0) * SC_STRIDE, absmax + nt * BN, 448, rawh + 8);
            if (ORD1 == 1) load_xh(0, 0, xbar);
            load_half(3, 0);
            if (ORD1 == 2) load_xh(0, 0, xbar);
            if (X0B == 0) load_xh(0, 1, xbar + 8);
            mbar_init(rawfull + 8 * rslot(2), 1); mbar_init(rawfull + 8 * rslot(3), 1); mbar_init(rawh + 16, 1); mbar_init(rawh + 24, 1);
            mbar_init(x1bar, 1); mbar_init(x1bar + 8, 1);
#pragma unroll
            for (int s = 0; s < 2 * HM2; s++) if (hmode(s >> 1) == 0 || !(s & 1)) mbar_init(ebar + 8 * s, hmode(s >> 1) == 0 ? 1 : 7);
#pragma unroll
            for (int s = 2; s < HM1; s++) mbar_init(bars + 280 + 8 * s, 7);
            static_assert(HM1 <= 5 && HO == 0, "");
#pragma unroll
            for (int s = 0; s < NW; s++) { mbar_init(fullW + 8 * s, 1); if (s < HM2 && s != 4) mbar_arrive(fullW + 8 * s); }
#pragma unroll
            for (int s = 0; s < NR; s++) mbar_init(written + 8 * s, 7);
#pragma unroll
            for (int s = 0; s < 6; s++) mbar_init(bars + 112 + 8 * s, 4);
            asm volatile("fence.mbarrier_init.release.cluster;" ::: "memory");
            fence_async_smem();
            if ((sbase & 0xffffff) != 0x400) __trap();
        }
        __syncwarp();
        cluster_arrive();
        if (elect()) {
            asm volatile("prefetch.tensormap [%0];" ::"l"(&tmq) : "memory");
            asm volatile("prefetch.tensormap [%0];" ::"l"(&tmqp) : "memory");
            asm volatile("prefetch.tensormap [%0];" ::"l"(&tmx16) : "memory");
            asm volatile("prefetch.tensormap [%0];" ::"l"(&tmx64) : "memory");
            while (clk() - tstart < T2) { }
            if (X0B == 1) load_xh(0, 1, xbar + 8);
            load_half(4, 2 * SC_STRIDE);
            if (X0B == 2) load_xh(0, 1, xbar + 8);
            load_sc(1, sslot(1), rawh + 16); load_sc(2, sslot(2), rawh + 16); load_half(5, 0);
            if (X0B == 3) load_xh(0, 1, xbar + 8);
            while (clk() - tstart < T2B) { }
            load_xh(1, 0, x1bar);
            if (G2S == 0) { load_half(6, 0); load_half(7, 2 * SC_STRIDE); load_sc(3, sslot(3), rawfull + 8 * rslot(3)); load_sc(4, sslot(4), rawfull + 8 * rslot(3)); load_xh(1, 1, x1bar + 8); }
            while (clk() - tstart < T3) { }
#pragma unroll
            for (int c = 2 - PFQ; c < 0; c++) prefetch(c);
        }
        __syncwarp();
        if (TLPRO > 0) TSL(33);
        cluster_wait();
    } else {
        cluster_arrive();
    }
    const uint32_t rsrc = __shfl_sync(~0u, sbase + RAW_OFF + warp * 1024 + (lane & 7) * 128 + ((((lane >> 3) * 2) ^ (lane & 7)) << 4), lane);
    const uint32_t rsrc2 = __shfl_sync(~0u, rsrc ^ 16, lane);
    const uint32_t ssrc = sbase + SC_OFF + warp * 64;
    const int wpos = (ALIGNO && (nt & 1)) ? (0x73210546 >> (4 * warp)) & 7 : warp;
    const uint32_t wown = wbase + rank * 7168 + wpos * 512;
    const uint32_t wdst = __shfl_sync(~0u, wown + lane * 16, lane);
    auto get_sc = [&](int ss) { return lds128(((opq(wdst) >> 3) & 0x30) + ssrc + ss * SC_STRIDE); };
    const uint32_t whalf = wbase + rank * 7168;
    const uint32_t pwhalf = mapa(whalf, rank ^ 1), pfullW = mapa(fullW, rank ^ 1);
    Lut lut;
    uint4 sc;
    uint4 q0, q1;
    auto fetch = [&](int slot, int h) {
        q0 = lds128(rsrc + roff(slot) + h * 7168);
        q1 = lds128(rsrc2 + roff(slot) + h * 7168);
    };
    auto convert0 = [&](int rs, int ws, bool look, uint32_t lbar, uint32_t lpar, int tl = -1) {
        bool ok = true;
        if (look) ok = mbar_try(lbar, lpar);
        const uint32_t p0 = pack4(q0), p1 = pack4(q1);
        if (tl >= 0 && TLPRO == 0 && TSP == 0) TSL(3 * tl + 2);
        uint4 w = dequant8(p0, p1, sc, lut);
        asm volatile("" : "+r"(w.x), "+r"(w.y), "+r"(w.z), "+r"(w.w));
        if (tl >= 0 && TLPRO == 0 && TSP == 1) TSL(3 * tl + 2);
        if (look) mbar_wait1(lbar, lpar, ok);
        if (tl >= 0 && TLPRO == 0 && TSP == 2) TSL(3 * tl + 2);
        fetch(rs, 1);
        sts128x(wdst + ws * UNIT, w);
    };
    auto convert1 = [&](int rs, int ws, bool next, int rsn, int rpn, bool scales, int cs, bool stfirst, bool look, uint32_t lbar, uint32_t lpar, int tl = -1) {
        bool ok = true, ok2 = true;
        if (next) ok = mbar_try(rawfull + 8 * rsn, rpn);
        if (look) ok2 = mbar_try(lbar, lpar);
        const uint32_t p0 = pack4(q0), p1 = pack4(q1);
        if (tl >= 0 && TLPRO == 0 && TSP == 0) TSL(3 * tl + 2);
        uint4 w = dequant8(p0, p1, sc, lut);
        asm volatile("" : "+r"(w.x), "+r"(w.y), "+r"(w.z), "+r"(w.w));
        if (stfirst) {
            sts128x(wdst + ws * UNIT + 3584, w);
            __syncwarp();
            if (elect()) mbar_arrive(written + 8 * rs);
            __syncwarp();
        }
        if (tl >= 0 && TLPRO == 0 && TSP == 1) TSL(3 * tl + 2);
        if (look) mbar_wait2(rawfull + 8 * rsn, rpn, lbar, lpar, ok && ok2);
        else if (next) mbar_wait1(rawfull + 8 * rsn, rpn, ok);
        if (tl >= 0 && TLPRO == 0 && TSP == 2) TSL(3 * tl + 2);
        if (next) fetch(rsn, 0);
        if (!stfirst) {
            sts128x(wdst + ws * UNIT + 3584, w);
            __syncwarp();
            if (elect()) mbar_arrive(written + 8 * rs);
            __syncwarp();
        }
        if (scales) sc = get_sc(cs);
    };
    auto hand_over = [&](int v, int rs, uint32_t par, int ws, uint32_t tx, bool raw) {
        mbar_wait(written + 8 * rs, par);
        fence_async_smem();
        if (elect()) {
            if (raw) load_raw(v + NR, rs);
            copy_to_peer(pwhalf + ws * UNIT, whalf + ws * UNIT, 7168, pfullW + 8 * ws);
            mbar_expect_tx(fullW + 8 * ws, tx);
        }
        __syncwarp();
    };
    auto share = [&](int v, int ws) {
        if ((v >> 1) == GUEST) { bulk_store(wpan + (2 * pair + (v & 1)) * UNIT + rank * 7168, whalf + ws * UNIT, 7168); bulk_commit(); }
    };
    constexpr uint32_t TXO = 7168 + SC_STRIDE, TXE = 7168 + 32768;
    auto hand_over_c = [&](int v) {
        hand_over(v, rslot(v), (v / 3) & 1, v % NW, (v & 1) ? (v < 7 || v == 25 ? 7168 : TXO) : (v < 4 ? 7168 : TXE), v >= 1 && v + NR < NU);
    };
    auto raw_bar = [](int b) { return b < 8 && !(b & 1) ? 168 + 8 * (b >> 1) : b < 8 || !(b & 1) ? 48 + 8 * rslot(b >> 1) : -1; };
    auto raw_par = [](int b) { return b < 8 && !(b & 1) ? 0 : rpar(b >> 1); };
    auto w_bar = [](int s) { return hmode(s >> 1) == 0 ? 200 + 8 * s : (s & 1) ? -1 : hmode(s >> 1) == 1 ? 200 + 8 * s : 8 * ((s >> 1) % NW); };
    auto w_par = [](int s) { return hmode(s >> 1) < 2 ? 0 : ((s >> 1) / NW) & 1; };
    auto wait_slice = [&](int s, bool wok) {
        if (s == 0) { mbar_wait2(xbar + 8 * wg, 0, ebar, 0, wok); if (TLPRO > 0) TSL(32); return; }
        if (s == 4) mbar_wait2(x1bar + 8 * wg, 0, bars + w_bar(s), w_par(s), wok);
        else if (s == 8 && hmode(4) < 2) mbar_wait2(fullW + 32, 0, bars + w_bar(s), w_par(s), wok);
        else if (w_bar(s) >= 0) mbar_wait1(bars + w_bar(s), w_par(s), wok);
    };
    auto pass_on = [&](int b) {
        const int u = b >> 1, n = hmode(u) + 1;
        fence_async_smem();
        __syncwarp();
        if (elect()) {
            const uint32_t o = wpos * 512 + u * UNIT, eb = 8 * (n == 1 ? b : 2 * u);
            if (n == 2) copy_to_peer(pwhalf + o, whalf + o, 512, pfullW + 200 + eb);
            copy_to_peer(pwhalf + o + (b & 1) * 3584, whalf + o + (b & 1) * 3584, 512, pfullW + 200 + eb);
            mbar_expect_tx(ebar + eb, n * 512);
        }
        __syncwarp();
    };
    auto passes = [](int b) { return hmode(b >> 1) == 1 && (b & 1); };
    auto block = [&](int b, int sn) {
        const int u = b >> 1, h = b & 1;
        const bool pre = b >= PB || ((PM >> b) & 1), pren = (b + 1 >= PB || ((PM >> (b + 1)) & 1)) && b + 1 < 2 * NU;
        const bool war = !h && u >= NW, early_look = sn >= 0 && b - sn >= 2;
        bool ok1 = true, ok2 = true, ok3 = false;
        if (war) ok1 = mbar_try(written + 8 * rslot(u - 2), ((u - 2) / 3) & 1);
        if (pren && raw_bar(b + 1) >= 0) ok2 = mbar_try(bars + raw_bar(b + 1), raw_par(b + 1));
        if (sn >= 0 && w_bar(sn) >= 0) ok3 = mbar_try(bars + w_bar(sn), w_par(sn));
        if (sn == 4) ok3 &= mbar_try(x1bar + 8 * wg, 0);
        if (sn == 8 && hmode(4) < 2) ok3 &= mbar_try(fullW + 32, 0);
        uint4 r0, r1;
        if (pre) { r0 = q0; r1 = q1; }
        else {
            if (raw_bar(b) >= 0) mbar_wait(bars + raw_bar(b), raw_par(b));
            r0 = lds128(rsrc + roff(rslot(u)) + h * 7168); r1 = lds128(rsrc2 + roff(rslot(u)) + h * 7168);
            if (b == 4) sc = get_sc(sslot(1));
        }
        const uint32_t p0 = pack4(r0), p1 = pack4(r1);
        if (TLPRO == 2 && b >= TB && b < TB + 3) TSL(20 + 3 * (b - TB));
        if (b > DEF && passes(b - 1)) pass_on(b - 1);
        uint4 w = dequant8(p0, p1, sc, lut);
        asm volatile("" : "+r"(w.x), "+r"(w.y), "+r"(w.z), "+r"(w.w));
        if (war) mbar_wait1(written + 8 * rslot(u - 2), ((u - 2) / 3) & 1, ok1);
        const bool now = b < DEF && passes(b);
        if (now) { sts128(wdst + (u % NW) * UNIT + h * 3584, w); pass_on(b); }
        if (TLPRO == 2 && b >= TB && b < TB + 3) TSL(21 + 3 * (b - TB));
        if (early_look) wait_slice(sn, ok3);
        if (pren) {
            if (raw_bar(b + 1) >= 0) mbar_wait1(bars + raw_bar(b + 1), raw_par(b + 1), ok2);
            if (TLPRO == 2 && b >= TB && b < TB + 3) TSL(22 + 3 * (b - TB));
            fetch(rslot((b + 1) >> 1), h ^ 1);
        }
        if (!now) sts128(wdst + (u % NW) * UNIT + h * 3584, w);
        if (h || hmode(u) == 0) { __syncwarp(); if (elect()) mbar_arrive(h ? written + 8 * rslot(u) : bars + 280 + 8 * u); __syncwarp(); }
        if ((b & 3) == 3 && u + 1 < NU) sc = get_sc(sslot((b + 1) >> 2));
        if (sn >= 0 && !early_look) wait_slice(sn, ok3);
    };
    auto blocks = [&](auto A, auto B, int sn) {
        static_for<A.value, B.value>([&](auto I) { block(I.value, I.value == B.value - 1 ? sn : -1); });
        if (A.value == B.value) wait_slice(sn, false);
    };
    auto duties = [&](auto S) {
        constexpr int s = S.value;
        auto slab = [&](auto B) {
            constexpr int b = B.value, u = b >> 1;
            mbar_wait((b & 1) ? written + 8 * rslot(u) : bars + 280 + 8 * u, (b & 1) ? (u / 3) & 1 : 0);
            fence_async_smem();
            if (elect()) {
                copy_to_peer(pwhalf + u * UNIT + (b & 1) * 3584, whalf + u * UNIT + (b & 1) * 3584, 3584, pfullW + 200 + 8 * b);
                mbar_expect_tx(ebar + 8 * b, 3584);
                if (b & 1) load_raw(u + NR, rslot(u));
            }
            __syncwarp();
        };
        static_for<4, 2 * HM1>([&](auto B) { if constexpr (t7b(B.value) == s && sub_max(B.value) < s) slab(B); });
        static_for<1, 2 * C0 + 2>([&](auto V) {
            constexpr int v = V.value;
            if constexpr (hmode(v) != 0 && (t7(v) == s || (s == 0 && t7(v) < 0))) {
                if (hmode(v) >= 2) hand_over_c(v);
                else {
                    mbar_wait(written + 8 * rslot(v), (v / 3) & 1);
                    if (elect()) load_raw(v + NR, rslot(v));
                    __syncwarp();
                }
            }
        });
        if (elect()) {
            if (s == 0 && G2S) { load_half(6, 0); load_half(7, 2 * SC_STRIDE); load_sc(3, sslot(3), rawfull + 8 * rslot(3)); load_sc(4, sslot(4), rawfull + 8 * rslot(3)); }
            if (s == G2S - 1) load_xh(1, 1, x1bar + 8);
            if (s == X2AT) { if (HM2 > 4) mbar_expect_tx(fullW + 32, 32768); load_x(2, 2); }
            static_for<3, C0 + 2>([&](auto I) { if constexpr (t7(xunit(I.value)) + XLAG == s) load_x(I.value, I.value % 3); });
            if ((s & 3) == 1) { if (s >= 8) load_sc((s >> 2) + 3, (s >> 2) % 3, fullW + 8 * ((2 * (s >> 2) + 3) % NW)); prefetch(s >> 2); }
        }
        __syncwarp();
        static_for<4, 2 * HM1>([&](auto B) { if constexpr (t7b(B.value) == s && sub_max(B.value) == s) slab(B); });
    };
    static_assert(HM2 <= 6 && HM1 >= 1 && HM2 >= 3 && C0 < GUEST && t7(2 * C0 + 1) < 4 * C0 && t7(xunit(C0 + 1)) + XLAG < 4 * C0, "");
    bool ok0 = false;
    if (warp < 7) {
        lut.lo[0] = __byte_perm(c0.x, c0.y, 0x6420); lut.hi[0] = __byte_perm(c0.x, c0.y, 0x7531);
        lut.lo[1] = __byte_perm(c0.z, c0.w, 0x6420); lut.hi[1] = __byte_perm(c0.z, c0.w, 0x7531);
        lut.lo[2] = __byte_perm(c1.x, c1.y, 0x6420); lut.hi[2] = __byte_perm(c1.x, c1.y, 0x7531);
        lut.lo[3] = __byte_perm(c1.z, c1.w, 0x6420); lut.hi[3] = __byte_perm(c1.z, c1.w, 0x7531);
        const uint32_t d = wown + (lane >> 3) * 128 + (lane & 3) * 16 + (lane & 4) * 2;
#pragma unroll
        for (int j = 0; j < 4; j++) {
            uint32_t a, b;
            lookup4(pack4(q[j]), lut, a, b);
            asm volatile("st.shared.v2.b32 [%0], {%1, %2};" ::"r"(d + (j >> 1) * 3584 + (j & 1) * 64), "r"(mul_bf16x2(a, sf.x)), "r"(mul_bf16x2(b, sf.y)) : "memory");
        }
        if (TLPRO > 0) TSL(33);
        cluster_wait();
        pass_on(1);
        if (elect()) mbar_arrive(written + 8 * rslot(0));
        __syncwarp();
        if (TLPRO > 0) TSL(34);
        mbar_wait(rawh + 8, 0);
        const uint4 a0 = lds128(rsrc + roff(rslot(1))), a1 = lds128(rsrc2 + roff(rslot(1))), s0 = get_sc(sslot(0));
        mbar_wait(rawfull + 8 * rslot(1), 0);
        if (TLPRO == 2) TSL(29);
        const uint4 a2 = lds128(rsrc + roff(rslot(1)) + 7168), a3 = lds128(rsrc2 + roff(rslot(1)) + 7168);
        sts128(wdst + UNIT, dequant8(pack4(a0), pack4(a1), s0, lut));
        sts128(wdst + UNIT + 3584, dequant8(pack4(a2), pack4(a3), s0, lut));
        ok0 = mbar_try(xbar + 8 * wg, 0) & mbar_try(ebar, 0);
        pass_on(3);
        if (elect()) mbar_arrive(written + 8 * rslot(1));
        __syncwarp();
        if (PB == 4) { mbar_wait(rawh + 16, 0); fetch(rslot(2), 0); sc = get_sc(sslot(1)); }
        static_assert(fconv(0, 0) == 4 && fconv(1, 0) == 4 && PB >= 4 && DEF >= 4, "");
    }
    if (TLPRO > 0) TSL(31);
    wait_slice(0, ok0);

    float acc0[112], acc1[112];
    const uint32_t descA = ((0x400 + wg * 16384) >> 4) | (1u << 16);
    constexpr uint32_t descB = ((0x400 + W_OFF) >> 4) | ((7168u >> 4) << 16);
    auto mma = [&](int slot, int ks, int tl = -1) {
        const uint32_t da = opq(descA) + slot * (32768 >> 4) + ks * 2, db = descB + (2 * slot + (ks >> 1)) * (UNIT >> 4) + (ks & 1) * 224;
        if (tl >= 0 && TLPRO == 0) TSL(3 * tl);
        wgmma_fence();
        wgmma224<1, 8>(acc0, da, db); wgmma224<1, 8>(acc1, da + 512, db);
        wgmma_commit();
        wgmma_wait<2>();
        if (tl >= 0 && TLPRO == 0) TSL(3 * tl + 1);
    };
    static_for<0, 4 * C0>([&](auto S) {
        constexpr int s = S.value;
        constexpr int c = s >> 2;
        if (s == 0) {
            wgmma_fence();
            wgmma224<0, 8>(acc0, descA, descB); wgmma224<0, 8>(acc1, descA + 512, descB);
            wgmma_commit();
        } else mma(c % 3, s & 3);
        if (TLPRO > 0) TSL(s);
        constexpr int a0 = fconv(0, s), b0 = fconv(0, s + 1), a1 = fconv(1, s), b1 = fconv(1, s + 1);
        if (warp == 7) { duties(S); wait_slice(s + 1, false); }
        else if ((a0 == a1 && b0 == b1) || wg == 0) blocks(IC<a0>{}, IC<b0>{}, s + 1);
        else blocks(IC<a1>{}, IC<b1>{}, s + 1);
    });
    auto load_w = [&](int v, uint32_t dst, uint32_t bar) {
        mbar_expect_tx(bar, UNIT);
        bulk_load(dst, wpan + (2 * (chunk(v >> 1) - 12) + (v & 1)) * UNIT, UNIT, bar);
    };
    auto load_l = [&](int i, int slot, int g, uint32_t bar) {
        tma_load_2d(sbase + slot * 32768 + g * 16384, &tmx64, chunk(i) * 64, mt * BM + g * 128, bar);
        tma_load_2d(sbase + slot * 32768 + g * 16384 + 8192, &tmx64, chunk(i + 1) * 64, mt * BM + g * 128, bar);
    };
    static_assert(fconv(0, 4 * C0) == 4 * C0 + 6 && fconv(1, 4 * C0) == 4 * C0 + 6 && PB <= 4 * C0 + 6, "ramp must be over");
    {
        uint32_t ph = (C0 / 3) & 1;
#pragma unroll 1
        for (int cb = C0; cb < C1; cb += 3)
          static_for<0, 3>([&](auto I) {
            constexpr int cc = C0 + I.value;
            constexpr int j0 = cc % 3, j1 = (cc + 1) % 3, j2 = (cc + 2) % 3;
            const int c = cb + I.value;
            if (TLPRO > 0 && I.value == 0) TSL(c < 8 ? 36 : 37);
            mma(j0, 0, 4 * I.value + 0);
            if (TLPRO > 0) TSL(cb == TLIT ? 8 + 4 * I.value + 0 : 30);
            if (warp < 7) convert0(j0, 2 * j1 + 1, true, written + 8 * j2, ((2 * cc + 1) / 3) & 1, 4 * I.value);
            else hand_over(2 * c + 2, j1, ((2 * cc + 2) / 3) & 1, 2 * j1, TXE, true);
            mma(j0, 1, 4 * I.value + 1);
            if (TLPRO > 0) TSL(cb == TLIT ? 8 + 4 * I.value + 1 : 30);
            if (warp < 7) convert1(j0, 2 * j1 + 1, true, j2, rpar(2 * cc + 4), true, j2, STFIRST, true, fullW + 16 * j0 + 8, ph, 4 * I.value + 1);
            else {
                if (elect()) {
                    load_sc(c + 3, j0, fullW + 16 * j1 + 8);
                    prefetch(c);
                    share(2 * c + 2, 2 * j1);
                    if (c == GUEST + PUBD) {
                        asm volatile("cp.async.bulk.wait_group 0;" ::: "memory");
                        asm volatile("red.relaxed.gpu.global.add.u32 [%0], 1;" ::"l"(flag) : "memory");
                    }
                }
                __syncwarp();
                mbar_wait(fullW + 16 * j0 + 8, ph);
            }
            if (j1 == 0) asm volatile("xor.b32 %0, %0, 1;" : "+r"(ph));
            mma(j0, 2, 4 * I.value + 2);
            if (TLPRO > 0) TSL(cb == TLIT ? 8 + 4 * I.value + 2 : 30);
            if (warp < 7) convert0(j2, 2 * j2, true, written + 8 * j1, ((2 * cc + 2) / 3) & 1, 4 * I.value + 2);
            else {
                hand_over(2 * c + 3, j0, ((2 * cc + 3) / 3) & 1, 2 * j1 + 1, TXO, j0 != 1 || c < 10);
                if (j0 == 1 && c == 10) {
                    unsigned f0, f1;
                    asm volatile("ld.shared.u32 %0, [%1];" : "=r"(f0) : "r"(sbase + SC_OFF + sslot(1) * SC_STRIDE + 448) : "memory");
                    asm volatile("ld.shared.u32 %0, [%1];" : "=r"(f1) : "r"(sbase + SC_OFF + sslot(12) * SC_STRIDE + 448) : "memory");
                    asm volatile("{\n.reg .pred p;\n.reg .u32 n, d;\nmov.u32 n, 0;\nLAB_POLL:\nsub.u32 d, %0, %1;\nsetp.ge.u32 p, d, 8;\n@p bra.uni LAB_DONE;\n"
                                 "ld.relaxed.gpu.global.u32 %0, [%2];\nadd.u32 n, n, 1;\nsetp.lt.u32 p, n, 0x10000;\n@p bra.uni LAB_POLL;\nLAB_DONE:\n}\n"
                                 : "+r"(f1) : "r"(f0 & ~7u), "l"(flag) : "memory");
                    if (elect()) load_w(26, sbase + RAW_OFF + roff(rslot(23)), rawfull + 8 * rslot(23));
                    __syncwarp();
                }
            }
            mma(j0, 3, 4 * I.value + 3);
            if (TLPRO > 0) TSL(cb == TLIT ? 8 + 4 * I.value + 3 : 30);
            if (warp < 7) convert1(j2, 2 * j2, true, j1, rpar(2 * cc + 5), false, 0, STFIRST, true, fullW + 16 * j1, ph, 4 * I.value + 3);
            else {
                if (elect()) {
                    if (j0 == 1 && c == 10) { load_l(12, 0, 0, fullW); load_l(12, 0, 1, fullW); }
                    else load_x(c + 2, j2);
                    share(2 * c + 3, 2 * j1 + 1);
                }
                __syncwarp();
                mbar_wait(fullW + 16 * j1, ph);
            }
          });
    }
    static_assert(C1 == 11 && GUEST + PUBD < 9, "");
    mma(2, 0);
    if (warp < 7) block(50, -1);
    else {
        mbar_wait(written + 8 * rslot(24), 0);
        if (elect()) {
            load_w(27, sbase + RAW_OFF + roff(rslot(24)), rawfull + 8 * rslot(24));
            load_w(28, wbase + 2 * UNIT, fullW + 16);
        }
        __syncwarp();
        hand_over_c(24);
        TSX(7, 6);
    }
    mma(2, 1);
    if (warp < 7) block(51, 46);
    else {
        if (elect()) {
            asm volatile("prefetch.tensormap [%0];" ::"l"(&tmo64) : "memory");
            asm volatile("prefetch.tensormap [%0];" ::"l"(&tmo32) : "memory");
        }
        __syncwarp();
        mbar_wait(fullW + 8 * 5, 1);
        hand_over_c(25);
        if (elect()) {
            mbar_expect_tx(xbar, 16384); load_l(14, 1, 0, xbar);
            load_w(29, sbase + RAW_OFF + roff(rslot(25)), rawfull + 8 * rslot(25));
            load_w(30, wbase + 3 * UNIT, fullW + 24);
        }
        __syncwarp();
        TSX(7, 7);
    }
    if (wg == 1) bar_sync(8);
    mma(2, 2);
    if (warp == 7) {
        wgmma_wait<1>();
        mbar_wait(fullW, 0);
        if (elect()) { load_w(31, wbase + 4 * UNIT, fullW + 32); mbar_expect_tx(xbar + 8, 16384); load_l(14, 1, 1, xbar + 8); }
        __syncwarp();
    }
    mma(2, 3);
    if (wg == 0) bar_arrive(8);
    const uint32_t slice0 = sbase + wg * 16384 + (warp & 3) * 2048;
    auto slc = [&](int p) { return slice0 + (p >> 1) * 32768 + (p & 1) * 8192; };
    const int row0 = mt * BM + wg * 128 + (warp & 3) * 16, odd = ALIGNO ? nt & 1 : 0;
    const int colL = nt * BN + odd * 96, colA = nt * BN + (odd ? 32 : 128), colB = nt * BN + (odd ? 0 : 192);
    auto load_s = [&](int i, int p, uint32_t bar) { tma_load_2d(slc(p), &tmx16, chunk(i) * 64, row0 + 64, bar); };
    const uint32_t tA = opq(descA);
    auto stagger = [&](unsigned d) { if (d) { const unsigned t = clk() + (warp & 3) * d; while ((int)(clk() - t) < 0) { } } };
    unsigned rt[16];
    mbar_wait(fullW, 0);
    wgmma_wait<0>();
    RT(0);
    TSX(wg * 4, 8 + wg);
    float lo0[64], hi0[48], lo1[64], hi1[48];
#pragma unroll
    for (int i = 0; i < 64; i++) { asm volatile("mov.b32 %0, %1;" : "=f"(lo0[i]) : "f"(acc0[i])); asm volatile("mov.b32 %0, %1;" : "=f"(lo1[i]) : "f"(acc1[i])); }
#pragma unroll
    for (int i = 0; i < 48; i++) { asm volatile("mov.b32 %0, %1;" : "=f"(hi0[i]) : "f"(acc0[64 + i])); asm volatile("mov.b32 %0, %1;" : "=f"(hi1[i]) : "f"(acc1[64 + i])); }
    auto udesc = [](int s) {
        const int v = 24 + (s >> 1);
        const int off = v == 26 ? RAW_OFF + roff(rslot(23)) : v == 27 ? RAW_OFF + roff(rslot(24)) : v == 29 ? RAW_OFF + roff(rslot(25))
                      : W_OFF + (v < 26 ? v - 24 : v == 28 ? 2 : v - 27) * UNIT;
        return (uint32_t)(((0x400 + off) >> 4) | ((7168u >> 4) << 16)) + (s & 1) * 224;
    };
    auto tdesc = [&](int p, int s) { return tA + (p >> 1) * (32768 >> 4) + (p & 1) * 512 + (s & 3) * 2; };
    auto ldesc = [&](int s) { return tdesc(s >> 2, s); };
    auto gdesc = [&](int s) { return tdesc(((s >> 2) + 4) % 6, s); };
    if (wg == 1) { mbar_wait(xbar + 8, 1); bar_sync(1); }
    static_for<0, 8>([&](auto V) {
        constexpr int v = 24 + (V.value == 0 || V.value > 3 ? V.value : V.value == 3 ? 1 : V.value + 1), s = 2 * (v - 24);
        if (v == 26) mbar_wait2(rawfull + 8 * rslot(23), rpar(26), rawfull + 8 * rslot(24), rpar(27), wg);
        else if (v == 29) mbar_wait1(rawfull + 8 * rslot(25), rpar(28), wg);
        else if (v == 28) mbar_wait2(fullW + 16, 0, xbar, 1, wg);
        else if (v != 24 && v != 27) mbar_wait1(fullW + 8 * (v == 25 ? 1 : v - 27), 0, wg);
        if (v == 28) TSX(wg * 4, 12 + wg);
        if (v == 31) TSX(wg * 4, 10 + wg);
        wgmma_fence();
        wgmma96<1, 8>(hi0, ldesc(s), udesc(s) + 128);
        wgmma96<1, 8>(hi0, ldesc(s + 1), udesc(s + 1) + 128);
    });
    wgmma_commit();
    bar_arrive(1 + wg);
    cluster_arrive();
    wgmma_wait<0>();
    RT(1);
    stagger(SG0);
    stage_cols<64, 0>(hi0, slc(4)); send(slc(4), &tmo64, colA, row0);
    stage_cols<32, 32>(hi0, slc(5));
    RT(2);
    bar_sync(2 + wg);
    RT(3);
    wgmma_fence();
#pragma unroll
    for (int s = 0; s < G1; s++) wgmma128<1, 8>(lo0, ldesc(s), udesc(s));
    wgmma_commit();
    if (GS) {
        if (elect()) { bulk_wait_read<0>(); mbar_expect_tx(gbar, 2048); load_s(12, 4, gbar); }
        __syncwarp();
    }
    send(slc(5), &tmo32, colB, row0);
    wgmma_fence();
#pragma unroll
    for (int s = G1; s < 16; s++) wgmma128<1, 8>(lo0, ldesc(s), udesc(s));
    wgmma_commit();
    bar_arrive(3 + wg);
    RT(4);
    if (elect()) {
        if (GS) { mbar_expect_tx(gbar + 16, 2048); bulk_wait_read<0>(); load_s(13, 5, gbar + 16); }
        else { mbar_expect_tx(gbar, 4096); bulk_wait_read<0>(); load_s(12, 4, gbar); load_s(13, 5, gbar); }
    }
    __syncwarp();
    TSX(wg * 4, 58 + wg);
    wgmma_wait<0>();
    RT(5);
    stagger(SG1);
    if (GL == -1) {
        if (elect()) { mbar_expect_tx(gbar + 8, 4096); load_s(14, 0, gbar + 8); load_s(15, 1, gbar + 8); }
        __syncwarp();
    }
    stage_cols<64, 0>(lo0, slc(2));
    if (E1 == 5) stage_cols<64, 32>(lo0, slc(3));
    if (GL == 0) {
        if (elect()) { mbar_expect_tx(gbar + 8, 4096); load_s(14, 0, gbar + 8); load_s(15, 1, gbar + 8); }
        __syncwarp();
    }
    const bool okg = mbar_try(gbar, 0), okg2 = !GS || mbar_try(gbar + 16, 0);
    send(slc(2), &tmo64, colL, row0);
    TSX(wg * 4, 48 + wg);
    if (GR == 0) mbar_wait1(gbar, 0, okg);
    if (E1 == 5) { if (elect()) { tma_store_2d(&tmo64, slc(3), colL + 64, row0); bulk_commit(); } __syncwarp(); }
    if (E1 < 4) stage_cols<64, 32>(lo0, slc(3));
    if (GL == 1) {
        if (elect()) { mbar_expect_tx(gbar + 8, 4096); load_s(14, 0, gbar + 8); load_s(15, 1, gbar + 8); }
        __syncwarp();
    }
    if (GR == 1) mbar_wait1(gbar, 0, okg);
    if (E1 == 0) send(slc(3), &tmo64, colL + 64, row0);
    RT(6);
    bar_sync(4 + wg);
    RT(7);
    wgmma_fence();
#pragma unroll
    for (int s = 0; s < 4; s++) wgmma128<1, 8>(lo1, gdesc(s), udesc(s));
    if (GS) { mbar_wait1(gbar + 16, 0, okg2); wgmma_fence(); }
#pragma unroll
    for (int s = 4; s < 8; s++) wgmma128<1, 8>(lo1, gdesc(s), udesc(s));
    wgmma_commit();
    const bool okg3 = mbar_try(gbar + 8, 0);
    if (E1 == 1) send(slc(3), &tmo64, colL + 64, row0);
    mbar_wait1(gbar + 8, 0, okg3);
    if (E1 == 4) stage_cols<64, 32>(lo0, slc(3));
    TSX(wg * 4, 52 + wg);
    wgmma_fence();
#pragma unroll
    for (int s = 8; s < 12; s++) wgmma128<1, 8>(lo1, gdesc(s), udesc(s));
    if (E1 == 3) { wgmma_commit(); send(slc(3), &tmo64, colL + 64, row0); wgmma_fence(); }
#pragma unroll
    for (int s = 12; s < 16; s++) wgmma128<1, 8>(lo1, gdesc(s), udesc(s));
    wgmma_commit();
    bar_arrive(5 + wg);
    RT(8);
    if (elect()) bulk_wait_read<0>();
    __syncwarp();
    if (E1 == 2 || E1 == 4) send(slc(3), &tmo64, colL + 64, row0);
    wgmma_wait<0>();
    RT(9);
    stagger(SG2);
    stage_cols<64, 0>(lo1, slc(2));
    if (E2 == 2) stage_cols<64, 32>(lo1, slc(3));
    send(slc(2), &tmo64, colL, row0 + 64);
    if (E2 == 2) { if (elect()) { tma_store_2d(&tmo64, slc(3), colL + 64, row0 + 64); bulk_commit(); } __syncwarp(); }
    if (E1 == 2 || E1 == 4) { if (elect()) bulk_wait_read<1>(); __syncwarp(); }
    if (E2 != 2) stage_cols<64, 32>(lo1, slc(3));
    if (HO && wg == 1) { __syncwarp(); if (elect()) mbar_arrive(ebar + 8 * (2 * (warp & 3) + 1)); __syncwarp(); }
    if (E2 == 0 && wg == 0) send(slc(3), &tmo64, colL + 64, row0 + 64);
    RT(10);
    bar_sync(6 + wg);
    RT(11);
    wgmma_fence();
#pragma unroll
    for (int s = 0; s < G3; s++) wgmma96<1, 8>(hi1, gdesc(s), udesc(s) + 128);
    wgmma_commit();
    if (E2 != 2 && (HO ? wg == 0 : (E2 == 1 || wg == 1))) send(slc(3), &tmo64, colL + 64, row0 + 64);
    wgmma_fence();
#pragma unroll
    for (int s = G3; s < 16; s++) wgmma96<1, 8>(hi1, gdesc(s), udesc(s) + 128);
    wgmma_commit();
    if (wg == 0) bar_arrive(7);
    RT(12);
    wgmma_wait<0>();
    RT(13);
    stagger(wg ? SG4 : SG3);
    if (HO == 1 && wg == 0) { mbar_wait(ebar + 8 * (2 * warp + 1), 0); send(slc(3) + 16384, &tmo64, colL + 64, row0 + 64 + 128); }
    stage_cols<64, 0>(hi1, slc(1));
    if (HO == 2 && wg == 0) { mbar_wait(ebar + 8 * (2 * warp + 1), 0); send(slc(3) + 16384, &tmo64, colL + 64, row0 + 64 + 128); }
    if (E3 == 0) send(slc(1), &tmo64, colA, row0 + 64);
    stage_cols<32, 32>(hi1, slc(5));
    if (E3 == 0) send(slc(5), &tmo32, colB, row0 + 64);
    else {
        fence_async_smem();
        __syncwarp();
        if (elect()) { tma_store_2d(&tmo64, slc(1), colA, row0 + 64); tma_store_2d(&tmo32, slc(5), colB, row0 + 64); bulk_commit(); }
        __syncwarp();
    }
    RT(14);
    if (elect()) bulk_wait_read<0>();
    __syncwarp();
    RT(15);
    TSW(wg * 4, 38 + wg);
    TS_DUMP();
    TL_DUMP();
    cluster_wait();
}

typedef CUresult (*EncodeFn)(CUtensorMap*, CUtensorMapDataType, cuuint32_t, void*, const cuuint64_t*, const cuuint64_t*,
                             const cuuint32_t*, const cuuint32_t*, CUtensorMapInterleave, CUtensorMapSwizzle,
                             CUtensorMapL2promotion, CUtensorMapFloatOOBfill);

extern "C" void kernel_launch(void* const* d_in, const int* in_sizes, int n_in, void* d_out, int out_size) {
    const __nv_bfloat16* x = (const __nv_bfloat16*)d_in[0];
    const int* qw = (const int*)d_in[1];
    const __nv_bfloat16* cb = (const __nv_bfloat16*)d_in[2];
    const __nv_bfloat16* absmax = (const __nv_bfloat16*)d_in[3];
    static EncodeFn encode = nullptr;
    static void *wimg = nullptr, *gflag = nullptr;
    if (!encode) {
        cudaGetSymbolAddress(&wimg, g_wimg);
        cudaGetSymbolAddress(&gflag, g_flag);
        void* fn = nullptr;
        cudaDriverEntryPointQueryResult qr;
        cudaGetDriverEntryPoint("cuTensorMapEncodeTiled", &fn, cudaEnableDefault, &qr);
        encode = (EncodeFn)fn;
        cudaFuncSetAttribute(nf4_gemm_kernel, cudaFuncAttributeMaxDynamicSharedMemorySize, SMEM_BYTES);
    }
    CUtensorMap tmx, tmq, tmo64, tmo32, tmqp, tmx16, tmx64, tmq1;
    {
        cuuint64_t dims[2] = {(cuuint64_t)K_, (cuuint64_t)M_};
        cuuint64_t strides[1] = {(cuuint64_t)K_ * 2};
        cuuint32_t box[2] = {64, 128};
        cuuint32_t es[2] = {1, 1};
        encode(&tmx, CU_TENSOR_MAP_DATA_TYPE_BFLOAT16, 2, (void*)x, dims, strides, box, es, CU_TENSOR_MAP_INTERLEAVE_NONE,
               CU_TENSOR_MAP_SWIZZLE_128B, CU_TENSOR_MAP_L2_PROMOTION_L2_128B, CU_TENSOR_MAP_FLOAT_OOB_FILL_NONE);
        box[1] = 64;
        encode(&tmx64, CU_TENSOR_MAP_DATA_TYPE_BFLOAT16, 2, (void*)x, dims, strides, box, es, CU_TENSOR_MAP_INTERLEAVE_NONE,
               CU_TENSOR_MAP_SWIZZLE_128B, CU_TENSOR_MAP_L2_PROMOTION_L2_128B, CU_TENSOR_MAP_FLOAT_OOB_FILL_NONE);
        box[1] = 16;
        encode(&tmx16, CU_TENSOR_MAP_DATA_TYPE_BFLOAT16, 2, (void*)x, dims, strides, box, es, CU_TENSOR_MAP_INTERLEAVE_NONE,
               CU_TENSOR_MAP_SWIZZLE_128B, CU_TENSOR_MAP_L2_PROMOTION_L2_128B, CU_TENSOR_MAP_FLOAT_OOB_FILL_NONE);
    }
    {
        cuuint64_t dims[5] = {32, 8, (cuuint64_t)(N_ / 32), 2, (cuuint64_t)(K_ / 16)};
        cuuint64_t strides[4] = {(cuuint64_t)N_ * 4, 128, (cuuint64_t)N_ * 4 * 8, (cuuint64_t)N_ * 4 * 16};
        cuuint32_t box[5] = {32, 8, 7, 1, 2};
        cuuint32_t es[5] = {1, 1, 1, 1, 1};
        encode(&tmq, CU_TENSOR_MAP_DATA_TYPE_INT32, 5, (void*)qw, dims, strides, box, es, CU_TENSOR_MAP_INTERLEAVE_NONE,
               CU_TENSOR_MAP_SWIZZLE_128B, CU_TENSOR_MAP_L2_PROMOTION_L2_128B, CU_TENSOR_MAP_FLOAT_OOB_FILL_NONE);
        box[4] = 1;
        encode(&tmq1, CU_TENSOR_MAP_DATA_TYPE_INT32, 5, (void*)qw, dims, strides, box, es, CU_TENSOR_MAP_INTERLEAVE_NONE,
               CU_TENSOR_MAP_SWIZZLE_128B, CU_TENSOR_MAP_L2_PROMOTION_L2_128B, CU_TENSOR_MAP_FLOAT_OOB_FILL_NONE);
        cuuint64_t dims2[2] = {(cuuint64_t)N_, (cuuint64_t)K_};
        cuuint32_t box2[2] = {224, 8};
        encode(&tmqp, CU_TENSOR_MAP_DATA_TYPE_INT32, 2, (void*)qw, dims2, strides, box2, es, CU_TENSOR_MAP_INTERLEAVE_NONE,
               CU_TENSOR_MAP_SWIZZLE_NONE, CU_TENSOR_MAP_L2_PROMOTION_L2_128B, CU_TENSOR_MAP_FLOAT_OOB_FILL_NONE);
    }
    {
        cuuint64_t dims[2] = {(cuuint64_t)N_, (cuuint64_t)M_};
        cuuint64_t strides[1] = {(cuuint64_t)N_ * 2};
        cuuint32_t box[2] = {64, 16};
        cuuint32_t es[2] = {1, 1};
        encode(&tmo64, CU_TENSOR_MAP_DATA_TYPE_BFLOAT16, 2, d_out, dims, strides, box, es, CU_TENSOR_MAP_INTERLEAVE_NONE,
               CU_TENSOR_MAP_SWIZZLE_128B, CU_TENSOR_MAP_L2_PROMOTION_NONE, CU_TENSOR_MAP_FLOAT_OOB_FILL_NONE);
        box[0] = 32;
        encode(&tmo32, CU_TENSOR_MAP_DATA_TYPE_BFLOAT16, 2, d_out, dims, strides, box, es, CU_TENSOR_MAP_INTERLEAVE_NONE,
               CU_TENSOR_MAP_SWIZZLE_64B, CU_TENSOR_MAP_L2_PROMOTION_NONE, CU_TENSOR_MAP_FLOAT_OOB_FILL_NONE);
    }
    nf4_gemm_kernel<<<dim3(2, 16, 4), 256, SMEM_BYTES>>>(qw, cb, absmax, (uint8_t*)wimg, (unsigned*)gflag, tmx, tmq, tmo64, tmo32, tmqp, tmx16, tmx64, tmq1);
}
```

```cpp
#include <cuda_runtime.h>
#include <cuda_bf16.h>
#include <cuda.h>
#include <stdint.h>

#define NG 2
#define G1 (NG == 1 ? 7 : 5)
#define G2 8
#define PFG (NG == 1 ? 1 : 0)
#define PUB 1
#define T2 900
#define T2B 1300
#define T3 1700
#define TLPRO -2
#define TLIT 2
constexpr int M_ = 2048, K_ = 1024, N_ = 3584;
constexpr int BM = 256, BN = 224;
constexpr int UNIT = 14336;
constexpr int NW = 6, NR = 3;
constexpr int NU = 32 - 6 * NG;
constexpr int NC = 16 - 4 * NG;
constexpr int CE = NU / 2 - 2;
constexpr int PFQ = 4, PFX = 3;
constexpr int RAW_OFF = 3 * 32768;
constexpr int SC_OFF = RAW_OFF + 2 * UNIT;
constexpr int SC_STRIDE = 464;
constexpr int W_OFF = 127 * 1024;
constexpr int RAW2_OFF = W_OFF + NW * UNIT;
constexpr int BAR_OFF = RAW2_OFF + UNIT;
constexpr int SMEM_BYTES = BAR_OFF + 320;
__device__ __align__(1024) uint8_t g_wimg[16 * 8 * NG * UNIT];
__device__ __align__(128) unsigned g_flag[16 * 32];

#define TSL(i)
#define TL_DUMP()
#define TSW(w, i)
#define TS_INIT()
#define TS_DUMP()
#define RT(i)

__device__ __forceinline__ uint32_t smem_u32(const void* p) { return (uint32_t)__cvta_generic_to_shared(p); }
__device__ __forceinline__ bool elect() {
    uint32_t ok;
    asm volatile("{\n.reg .pred p;\nelect.sync _|p, 0xffffffff;\nselp.u32 %0, 1, 0, p;\n}\n" : "=r"(ok));
    return ok != 0;
}
__device__ __forceinline__ void mbar_init(uint32_t bar, uint32_t cnt) { asm volatile("mbarrier.init.shared::cta.b64 [%0], %1;" ::"r"(bar), "r"(cnt) : "memory"); }
__device__ __forceinline__ void mbar_expect_tx(uint32_t bar, uint32_t bytes) { asm volatile("mbarrier.arrive.expect_tx.shared::cta.b64 _, [%0], %1;" ::"r"(bar), "r"(bytes) : "memory"); }
__device__ __forceinline__ void mbar_arrive(uint32_t bar) { asm volatile("mbarrier.arrive.shared::cta.b64 _, [%0];" ::"r"(bar) : "memory"); }
#define BOUNDED
#define WAIT_INIT "mov.u32 n, 0;\n"
#define WAIT_NEXT "@p bra.uni LAB_DONE;\nadd.u32 n, n, 1;\nsetp.lt.u32 p, n, 0x4000;\n@p bra.uni LAB_WAIT;\n"
__device__ __forceinline__ void mbar_wait(uint32_t bar, uint32_t parity) {
    asm volatile(
        "{\n.reg .pred p;\n.reg .u32 n;\n"
        WAIT_INIT
        "LAB_WAIT:\n"
        "mbarrier.try_wait.parity.shared::cta.b64 p, [%0], %1;\n"
        WAIT_NEXT
        "LAB_DONE:\n}\n" ::"r"(bar), "r"(parity) : "memory");
}
__device__ __forceinline__ bool mbar_try(uint32_t bar, uint32_t parity) {
    uint32_t ok;
    asm volatile("{\n.reg .pred p;\nmbarrier.test_wait.parity.shared::cta.b64 p, [%1], %2;\nselp.u32 %0, 1, 0, p;\n}\n" : "=r"(ok) : "r"(bar), "r"(parity) : "memory");
    return ok != 0;
}
__device__ __forceinline__ void mbar_wait1(uint32_t b0, uint32_t p0, bool skip) {
    asm volatile(
        "{\n.reg .pred p;\n.reg .u32 n;\n"
        "setp.ne.u32 p, %2, 0;\n@p bra.uni LAB_DONE;\n"
        WAIT_INIT
        "LAB_WAIT:\n"
        "mbarrier.try_wait.parity.shared::cta.b64 p, [%0], %1;\n"
        WAIT_NEXT
        "LAB_DONE:\n}\n" ::"r"(b0), "r"(p0), "r"((uint32_t)skip) : "memory");
}
__device__ __forceinline__ void mbar_wait2(uint32_t b0, uint32_t p0, uint32_t b1, uint32_t p1, bool skip = false) {
    asm volatile(
        "{\n.reg .pred p, q;\n.reg .u32 n;\n"
        "setp.ne.u32 p, %4, 0;\n@p bra.uni LAB_DONE;\n"
        WAIT_INIT
        "LAB_WAIT:\n"
        "mbarrier.try_wait.parity.shared::cta.b64 p, [%0], %1;\n"
        "mbarrier.try_wait.parity.shared::cta.b64 q, [%2], %3;\n"
        "and.pred p, p, q;\n"
        WAIT_NEXT
        "LAB_DONE:\n}\n" ::"r"(b0), "r"(p0), "r"(b1), "r"(p1), "r"((uint32_t)skip) : "memory");
}
__device__ __forceinline__ void tma_load_2d(uint32_t dst, const CUtensorMap* tm, int c0, int c1, uint32_t bar) {
    asm volatile("cp.async.bulk.tensor.2d.shared::cluster.global.mbarrier::complete_tx::bytes [%0], [%1, {%2, %3}], [%4];"
                 ::"r"(dst), "l"(tm), "r"(c0), "r"(c1), "r"(bar) : "memory");
}
__device__ __forceinline__ void tma_load_5d(uint32_t dst, const CUtensorMap* tm, int c0, int c1, int c2, int c3, int c4, uint32_t bar) {
    asm volatile("cp.async.bulk.tensor.5d.shared::cluster.global.mbarrier::complete_tx::bytes [%0], [%1, {%2, %3, %4, %5, %6}], [%7];"
                 ::"r"(dst), "l"(tm), "r"(c0), "r"(c1), "r"(c2), "r"(c3), "r"(c4), "r"(bar) : "memory");
}
__device__ __forceinline__ void tma_prefetch_2d(const CUtensorMap* tm, int c0, int c1) {
    asm volatile("cp.async.bulk.prefetch.tensor.2d.L2.global [%0, {%1, %2}];" ::"l"(tm), "r"(c0), "r"(c1) : "memory");
}
__device__ __forceinline__ void bulk_load(uint32_t dst, const void* src, uint32_t bytes, uint32_t bar) {
    asm volatile("cp.async.bulk.shared::cluster.global.mbarrier::complete_tx::bytes [%0], [%1], %2, [%3];"
                 ::"r"(dst), "l"(src), "r"(bytes), "r"(bar) : "memory");
}
__device__ __forceinline__ void cluster_arrive() { asm volatile("barrier.cluster.arrive.relaxed.aligned;" ::: "memory"); }
__device__ __forceinline__ void cluster_wait() { asm volatile("barrier.cluster.wait.acquire.aligned;" ::: "memory"); }
__device__ __forceinline__ uint32_t mapa(uint32_t addr, uint32_t cta) {
    uint32_t r; asm("mapa.shared::cluster.u32 %0, %1, %2;" : "=r"(r) : "r"(addr), "r"(cta)); return r;
}
__device__ __forceinline__ void copy_to_peer(uint32_t cdst, uint32_t src, uint32_t bytes, uint32_t cbar) {
    asm volatile("cp.async.bulk.shared::cluster.shared::cta.mbarrier::complete_tx::bytes [%0], [%1], %2, [%3];"
                 ::"r"(cdst), "r"(src), "r"(bytes), "r"(cbar) : "memory");
}
__device__ __forceinline__ void wgmma_fence() { asm volatile("wgmma.fence.sync.aligned;" ::: "memory"); }
__device__ __forceinline__ void wgmma_commit() { asm volatile("wgmma.commit_group.sync.aligned;" ::: "memory"); }
template <int N> __device__ __forceinline__ void wgmma_wait() { asm volatile("wgmma.wait_group.sync.aligned %0;" ::"n"(N) : "memory"); }
__device__ __forceinline__ uint32_t pack_bf16(float lo, float hi) {
    uint32_t r; asm("cvt.rn.bf16x2.f32 %0, %1, %2;" : "=r"(r) : "f"(hi), "f"(lo)); return r;
}
__device__ __forceinline__ void stmatrix_x4(uint32_t addr, uint32_t a, uint32_t b, uint32_t c, uint32_t d) {
    asm volatile("stmatrix.sync.aligned.m8n8.x4.shared.b16 [%0], {%1, %2, %3, %4};" ::"r"(addr), "r"(a), "r"(b), "r"(c), "r"(d) : "memory");
}
__device__ __forceinline__ uint4 lds128(uint32_t a) {
    uint4 v; asm volatile("ld.shared.v4.b32 {%0, %1, %2, %3}, [%4];" : "=r"(v.x), "=r"(v.y), "=r"(v.z), "=r"(v.w) : "r"(a) : "memory"); return v;
}
__device__ __forceinline__ void sts128(uint32_t a, uint4 v) {
    asm volatile("st.shared.v4.b32 [%0], {%1, %2, %3, %4};" ::"r"(a), "r"(v.x), "r"(v.y), "r"(v.z), "r"(v.w) : "memory");
}
__device__ __forceinline__ uint4 ldg128(const void* p) {
    uint4 v; asm volatile("ld.global.nc.v4.b32 {%0, %1, %2, %3}, [%4];" : "=r"(v.x), "=r"(v.y), "=r"(v.z), "=r"(v.w) : "l"(p) : "memory"); return v;
}
__device__ __forceinline__ unsigned clk() { unsigned c; asm volatile("mov.u32 %0, %%clock;" : "=r"(c) :: "memory"); return c; }
__device__ __forceinline__ uint32_t mul_bf16x2(uint32_t a, uint32_t b) { uint32_t r; asm("mul.rn.bf16x2 %0, %1, %2;" : "=r"(r) : "r"(a), "r"(b)); return r; }
struct Lut { uint32_t lo[4], hi[4]; };
__device__ __forceinline__ uint32_t prmt(uint32_t a, uint32_t b, uint32_t s) { uint32_t r; asm("prmt.b32 %0, %1, %2, %3;" : "=r"(r) : "r"(a), "r"(b), "r"(s)); return r; }
__device__ __forceinline__ uint32_t pack4(const uint4& q) {
    uint32_t ab, cd, p;
    asm volatile("mad.lo.u32 %0, %1, 16, %2;" : "=r"(ab) : "r"(q.y), "r"(q.x));
    asm volatile("mad.lo.u32 %0, %1, 16, %2;" : "=r"(cd) : "r"(q.w), "r"(q.z));
    asm volatile("mad.lo.u32 %0, %1, 256, %2;" : "=r"(p) : "r"(cd), "r"(ab));
    return p;
}
__device__ __forceinline__ void lookup4(uint32_t p, const Lut& t, uint32_t& w01, uint32_t& w23) {
    const uint32_t t8 = p & 0x8888u, s7 = p & 0x7777u;
    const uint32_t sel = (t8 >> 1) + 0x3210u;
    const uint32_t lo = prmt(prmt(t.lo[0], t.lo[1], p), prmt(t.lo[2], t.lo[3], s7), sel);
    const uint32_t hi = prmt(prmt(t.hi[0], t.hi[1], p), prmt(t.hi[2], t.hi[3], s7), sel);
    w01 = prmt(lo, hi, 0x5140);
    w23 = prmt(lo, hi, 0x7362);
}
__device__ __forceinline__ uint4 dequant8(uint32_t p0, uint32_t p1, const uint4& sc, const Lut& t) {
    uint4 r;
    lookup4(p0, t, r.x, r.y);
    lookup4(p1, t, r.z, r.w);
    r.x = mul_bf16x2(r.x, sc.x); r.y = mul_bf16x2(r.y, sc.y); r.z = mul_bf16x2(r.z, sc.z); r.w = mul_bf16x2(r.w, sc.w);
    return r;
}
__device__ __forceinline__ void fence_async_smem() { asm volatile("fence.proxy.async.shared::cta;" ::: "memory"); }

template <int SCALE_D, int BHI, uint32_t AHI = 0x40000040u>
__device__ __forceinline__ void wgmma224(float (&d)[112], uint32_t descA, uint32_t descB) {
    asm volatile(
        "{\n.reg .pred p;\n.reg .b64 da, db;\nsetp.ne.b32 p, %114, 0;\n"
        "mov.b64 da, {%112, %116};\nmov.b64 db, {%113, %115};\n"
        "wgmma.mma_async.sync.aligned.m64n224k16.f32.bf16.bf16 "
        "{%0, %1, %2, %3, %4, %5, %6, %7, %8, %9, %10, %11, %12, %13, %14, %15, "
        "%16, %17, %18, %19, %20, %21, %22, %23, %24, %25, %26, %27, %28, %29, %30, %31, "
        "%32, %33, %34, %35, %36, %37, %38, %39, %40, %41, %42, %43, %44, %45, %46, %47, "
        "%48, %49, %50, %51, %52, %53, %54, %55, %56, %57, %58, %59, %60, %61, %62, %63, "
        "%64, %65, %66, %67, %68, %69, %70, %71, %72, %73, %74, %75, %76, %77, %78, %79, "
        "%80, %81, %82, %83, %84, %85, %86, %87, %88, %89, %90, %91, %92, %93, %94, %95, "
        "%96, %97, %98, %99, %100, %101, %102, %103, %104, %105, %106, %107, %108, %109, %110, %111}, "
        "da, db, p, 1, 1, 0, 1;\n}\n"
        : "+f"(d[0]), "+f"(d[1]), "+f"(d[2]), "+f"(d[3]), "+f"(d[4]), "+f"(d[5]), "+f"(d[6]), "+f"(d[7]),
          "+f"(d[8]), "+f"(d[9]), "+f"(d[10]), "+f"(d[11]), "+f"(d[12]), "+f"(d[13]), "+f"(d[14]), "+f"(d[15]),
          "+f"(d[16]), "+f"(d[17]), "+f"(d[18]), "+f"(d[19]), "+f"(d[20]), "+f"(d[21]), "+f"(d[22]), "+f"(d[23]),
          "+f"(d[24]), "+f"(d[25]), "+f"(d[26]), "+f"(d[27]), "+f"(d[28]), "+f"(d[29]), "+f"(d[30]), "+f"(d[31]),
          "+f"(d[32]), "+f"(d[33]), "+f"(d[34]), "+f"(d[35]), "+f"(d[36]), "+f"(d[37]), "+f"(d[38]), "+f"(d[39]),
          "+f"(d[40]), "+f"(d[41]), "+f"(d[42]), "+f"(d[43]), "+f"(d[44]), "+f"(d[45]), "+f"(d[46]), "+f"(d[47]),
          "+f"(d[48]), "+f"(d[49]), "+f"(d[50]), "+f"(d[51]), "+f"(d[52]), "+f"(d[53]), "+f"(d[54]), "+f"(d[55]),
          "+f"(d[56]), "+f"(d[57]), "+f"(d[58]), "+f"(d[59]), "+f"(d[60]), "+f"(d[61]), "+f"(d[62]), "+f"(d[63]),
          "+f"(d[64]), "+f"(d[65]), "+f"(d[66]), "+f"(d[67]), "+f"(d[68]), "+f"(d[69]), "+f"(d[70]), "+f"(d[71]),
          "+f"(d[72]), "+f"(d[73]), "+f"(d[74]), "+f"(d[75]), "+f"(d[76]), "+f"(d[77]), "+f"(d[78]), "+f"(d[79]),
          "+f"(d[80]), "+f"(d[81]), "+f"(d[82]), "+f"(d[83]), "+f"(d[84]), "+f"(d[85]), "+f"(d[86]), "+f"(d[87]),
          "+f"(d[88]), "+f"(d[89]), "+f"(d[90]), "+f"(d[91]), "+f"(d[92]), "+f"(d[93]), "+f"(d[94]), "+f"(d[95]),
          "+f"(d[96]), "+f"(d[97]), "+f"(d[98]), "+f"(d[99]), "+f"(d[100]), "+f"(d[101]), "+f"(d[102]), "+f"(d[103]),
          "+f"(d[104]), "+f"(d[105]), "+f"(d[106]), "+f"(d[107]), "+f"(d[108]), "+f"(d[109]), "+f"(d[110]), "+f"(d[111])
        : "r"(descA), "r"(descB), "n"(SCALE_D), "n"(BHI), "n"(AHI));
}

template <int SCALE_D, int BHI, uint32_t AHI = 0x40000040u>
__device__ __forceinline__ void wgmma128(float (&d)[64], uint32_t descA, uint32_t descB) {
    asm volatile(
        "{\n.reg .pred p;\n.reg .b64 da, db;\nsetp.ne.b32 p, %66, 0;\n"
        "mov.b64 da, {%64, %68};\nmov.b64 db, {%65, %67};\n"
        "wgmma.mma_async.sync.aligned.m64n128k16.f32.bf16.bf16 "
        "{%0, %1, %2, %3, %4, %5, %6, %7, %8, %9, %10, %11, %12, %13, %14, %15, "
        "%16, %17, %18, %19, %20, %21, %22, %23, %24, %25, %26, %27, %28, %29, %30, %31, "
        "%32, %33, %34, %35, %36, %37, %38, %39, %40, %41, %42, %43, %44, %45, %46, %47, "
        "%48, %49, %50, %51, %52, %53, %54, %55, %56, %57, %58, %59, %60, %61, %62, %63}, "
        "da, db, p, 1, 1, 0, 1;\n}\n"
        : "+f"(d[0]), "+f"(d[1]), "+f"(d[2]), "+f"(d[3]), "+f"(d[4]), "+f"(d[5]), "+f"(d[6]), "+f"(d[7]),
          "+f"(d[8]), "+f"(d[9]), "+f"(d[10]), "+f"(d[11]), "+f"(d[12]), "+f"(d[13]), "+f"(d[14]), "+f"(d[15]),
          "+f"(d[16]), "+f"(d[17]), "+f"(d[18]), "+f"(d[19]), "+f"(d[20]), "+f"(d[21]), "+f"(d[22]), "+f"(d[23]),
          "+f"(d[24]), "+f"(d[25]), "+f"(d[26]), "+f"(d[27]), "+f"(d[28]), "+f"(d[29]), "+f"(d[30]), "+f"(d[31]),
          "+f"(d[32]), "+f"(d[33]), "+f"(d[34]), "+f"(d[35]), "+f"(d[36]), "+f"(d[37]), "+f"(d[38]), "+f"(d[39]),
          "+f"(d[40]), "+f"(d[41]), "+f"(d[42]), "+f"(d[43]), "+f"(d[44]), "+f"(d[45]), "+f"(d[46]), "+f"(d[47]),
          "+f"(d[48]), "+f"(d[49]), "+f"(d[50]), "+f"(d[51]), "+f"(d[52]), "+f"(d[53]), "+f"(d[54]), "+f"(d[55]),
          "+f"(d[56]), "+f"(d[57]), "+f"(d[58]), "+f"(d[59]), "+f"(d[60]), "+f"(d[61]), "+f"(d[62]), "+f"(d[63])
        : "r"(descA), "r"(descB), "n"(SCALE_D), "n"(BHI), "n"(AHI));
}

template <int SCALE_D, int BHI, uint32_t AHI = 0x40000040u>
__device__ __forceinline__ void wgmma96(float (&d)[48], uint32_t descA, uint32_t descB) {
    asm volatile(
        "{\n.reg .pred p;\n.reg .b64 da, db;\nsetp.ne.b32 p, %50, 0;\n"
        "mov.b64 da, {%48, %52};\nmov.b64 db, {%49, %51};\n"
        "wgmma.mma_async.sync.aligned.m64n96k16.f32.bf16.bf16 "
        "{%0, %1, %2, %3, %4, %5, %6, %7, %8, %9, %10, %11, %12, %13, %14, %15, "
        "%16, %17, %18, %19, %20, %21, %22, %23, %24, %25, %26, %27, %28, %29, %30, %31, "
        "%32, %33, %34, %35, %36, %37, %38, %39, %40, %41, %42, %43, %44, %45, %46, %47}, "
        "da, db, p, 1, 1, 0, 1;\n}\n"
        : "+f"(d[0]), "+f"(d[1]), "+f"(d[2]), "+f"(d[3]), "+f"(d[4]), "+f"(d[5]), "+f"(d[6]), "+f"(d[7]),
          "+f"(d[8]), "+f"(d[9]), "+f"(d[10]), "+f"(d[11]), "+f"(d[12]), "+f"(d[13]), "+f"(d[14]), "+f"(d[15]),
          "+f"(d[16]), "+f"(d[17]), "+f"(d[18]), "+f"(d[19]), "+f"(d[20]), "+f"(d[21]), "+f"(d[22]), "+f"(d[23]),
          "+f"(d[24]), "+f"(d[25]), "+f"(d[26]), "+f"(d[27]), "+f"(d[28]), "+f"(d[29]), "+f"(d[30]), "+f"(d[31]),
          "+f"(d[32]), "+f"(d[33]), "+f"(d[34]), "+f"(d[35]), "+f"(d[36]), "+f"(d[37]), "+f"(d[38]), "+f"(d[39]),
          "+f"(d[40]), "+f"(d[41]), "+f"(d[42]), "+f"(d[43]), "+f"(d[44]), "+f"(d[45]), "+f"(d[46]), "+f"(d[47])
        : "r"(descA), "r"(descB), "n"(SCALE_D), "n"(BHI), "n"(AHI));
}

__device__ __forceinline__ uint32_t opq(uint32_t v) { asm volatile("" : "+r"(v)); return v; }
template <int I> struct IC { static constexpr int value = I; };
template <int B, int E, class F> __device__ __forceinline__ void static_for(F&& f) {
    if constexpr (B < E) { f(IC<B>{}); static_for<B + 1, E>(f); }
}

__device__ __forceinline__ void tma_store_2d(const CUtensorMap* tm, uint32_t src, int c0, int c1) {
    asm volatile("cp.async.bulk.tensor.2d.global.shared::cta.bulk_group [%0, {%2, %3}], [%1];" ::"l"(tm), "r"(src), "r"(c0), "r"(c1) : "memory");
}
__device__ __forceinline__ void bulk_store(void* dst, uint32_t src, uint32_t bytes) {
    asm volatile("cp.async.bulk.global.shared::cta.bulk_group [%0], [%1], %2;" ::"l"(dst), "r"(src), "r"(bytes) : "memory");
}
__device__ __forceinline__ void bulk_commit() { asm volatile("cp.async.bulk.commit_group;" ::: "memory"); }
template <int N> __device__ __forceinline__ void bulk_wait_read() { asm volatile("cp.async.bulk.wait_group.read %0;" ::"n"(N) : "memory"); }
__device__ __forceinline__ void bar_arrive(int id) { asm volatile("bar.arrive %0, 256;" ::"r"(id) : "memory"); }
__device__ __forceinline__ void bar_sync(int id) { asm volatile("bar.sync %0, 256;" ::"r"(id) : "memory"); }
template <int NC, int OFF, int N>
__device__ __forceinline__ void stage_cols(const float (&acc)[N], uint32_t stg) {
    int lane; asm volatile("mov.u32 %0, %%laneid;" : "=r"(lane));
    const int r = lane & 15;
    const uint32_t a0 = NC == 64 ? stg + r * 128 + (((lane >> 4) ^ (r & 7)) << 4) : stg + r * 64 + (((lane >> 4) ^ ((r >> 1) & 3)) << 4);
#pragma unroll
    for (int j = 0; j < NC / 16; j++) {
        const int i = OFF + 8 * j;
        stmatrix_x4(a0 ^ (j * 32), pack_bf16(acc[i], acc[i + 1]), pack_bf16(acc[i + 2], acc[i + 3]), pack_bf16(acc[i + 4], acc[i + 5]), pack_bf16(acc[i + 6], acc[i + 7]));
    }
}
__device__ __forceinline__ void send(uint32_t stg, const CUtensorMap* tmo, int col, int row) {
    fence_async_smem();
    __syncwarp();
    if (elect()) { tma_store_2d(tmo, stg, col, row); bulk_commit(); }
    __syncwarp();
}

__host__ __device__ constexpr int rslot(int u) { return (2 * u) % 3; }
__host__ __device__ constexpr int roff(int slot) { return slot < 2 ? slot * UNIT : RAW2_OFF - RAW_OFF; }
__host__ __device__ constexpr int rpar(int u) { return (u / 3 - (u % 3 == 0)) & 1; }
__host__ __device__ constexpr int sslot(int c) { return c < 3 ? c + 3 : c % 3; }
__host__ __device__ constexpr int vturn(int v) {
    return v < NU ? v : v < NU + 2 ? -v : v == NU + 2 ? NU : v == NU + 3 ? -(NU + 2) : v < NU + 9 ? v - 3 : v < NU + 11 ? 6 - v : NU + 6;
}
__host__ __device__ constexpr int uoff(int v) { return vturn(v) < 0 ? RAW_OFF + roff(rslot(-vturn(v))) : W_OFF + (vturn(v) % NW) * UNIT; }
__host__ __device__ constexpr int ubar(int v) { return vturn(v) < 0 ? 96 + 8 * rslot(-vturn(v)) : 16 * (vturn(v) % NW); }
__host__ __device__ constexpr int upar(int v) { return vturn(v) < 0 ? rpar(-vturn(v)) : (vturn(v) / NW) & 1; }
__host__ __device__ constexpr int utime(int v) {
    const int t = v < NU + 4 ? 2 * NU - 10 + 2 * ((v - NU + 1) / 2) : 2 * v - 14;
    return NG == 2 && t < 14 + (v & ~1) ? 14 + (v & ~1) : t;
}
__host__ __device__ constexpr uint32_t bdesc(int s) { return (uint32_t)(((0x400 + uoff(s >> 1)) >> 4) | ((7168u >> 4) << 16)) + (s & 1) * 224; }

__global__ void __cluster_dims__(2, 1, 1) __launch_bounds__(256, 1)
nf4_gemm_kernel(const int* __restrict__ qw, const __nv_bfloat16* __restrict__ cb, const __nv_bfloat16* __restrict__ absmax,
                uint8_t* __restrict__ wimg, unsigned* __restrict__ gflag,
                const __grid_constant__ CUtensorMap tmx, const __grid_constant__ CUtensorMap tmq, const __grid_constant__ CUtensorMap tmo64,
                const __grid_constant__ CUtensorMap tmo32, const __grid_constant__ CUtensorMap tmqp, const __grid_constant__ CUtensorMap tmx16,
                const __grid_constant__ CUtensorMap tmx64, const __grid_constant__ CUtensorMap tmq1) {
    extern __shared__ __align__(1024) uint8_t smem[];
    const uint32_t sbase = smem_u32(smem);
    const int rank = blockIdx.x, nt = blockIdx.y, pair = blockIdx.z;
    uint4 q[4], c0, c1;
    uint2 sf;
    if (threadIdx.x < 224) {
        const uint32_t t = threadIdx.x;
        const int* p = qw + (uint32_t)((t & 3) * (N_ - 1) + t + blockIdx.x * (8 * N_) + blockIdx.y * BN);
        q[0] = ldg128(p); q[1] = ldg128(p + 4 * N_);
        q[2] = ldg128(p + 16 * N_); q[3] = ldg128(p + 20 * N_);
        const void* ps = absmax + (uint32_t)(opq(t & ~3u) + blockIdx.y * BN);
        asm volatile("ld.global.nc.v2.b32 {%0, %1}, [%2];" : "=r"(sf.x), "=r"(sf.y) : "l"(ps) : "memory");
        c0 = ldg128(cb); c1 = ldg128(cb + 8);
    }
    const unsigned tstart = clk();
    const int mt = pair * 2 + rank;
    const int lane = threadIdx.x & 31;
    const int warp = __reduce_max_sync(~0u, threadIdx.x >> 5);
    const int wg = warp >> 2;
    const uint32_t bars = sbase + BAR_OFF;
    const uint32_t full = bars, rawfull = bars + 96, written = bars + 120, xbar = bars + 144, gbar = bars + 160 + wg * 16;
    const uint32_t rawh = bars + 192 - 8, ebar = bars + 216, wre = bars + 232 - 16, ones = bars + 256;
    const uint32_t wbase = sbase + W_OFF;
    TS_INIT();
    __syncwarp();
    TSW(0, 0);

    auto insert = [](uint64_t m, int pos, int v) { const uint64_t low = (1ull << (4 * pos)) - 1; return (m & low) | ((m & ~low) << 4) | ((uint64_t)v << (4 * pos)); };
    const uint64_t others = (0xedcfedu >> (4 * pair)) & 0xfff;
    const uint64_t cmap = NG == 1 ? insert(0xba9876543210ull, G1, 12 + pair) | (others << 52)
                                  : insert(insert(0x76543210ull, G1, 8 + pair), G2, 12 + pair) | ((others - 0x444) << 40) | (others << 52);
    auto chunk = [&](int i) { return (int)(cmap >> (4 * i)) & 15; };
    unsigned* flag = gflag + nt * 32;
    uint8_t* wpan = wimg + nt * (8 * NG * UNIT);
    auto load_x = [&](int i, int slot, uint32_t bar) {
        tma_load_2d(sbase + slot * 32768, &tmx, chunk(i) * 64, mt * BM, bar);
        tma_load_2d(sbase + slot * 32768 + 16384, &tmx, chunk(i) * 64, mt * BM + 128, bar);
    };
    auto load_l = [&](int i, int slot, int g, uint32_t bar) {
        tma_load_2d(sbase + slot * 32768 + g * 16384, &tmx64, chunk(i) * 64, mt * BM + g * 128, bar);
        tma_load_2d(sbase + slot * 32768 + g * 16384 + 8192, &tmx64, chunk(i + 1) * 64, mt * BM + g * 128, bar);
    };
    auto snap = [&](int ss, uint32_t bar) { bulk_load(sbase + SC_OFF + ss * SC_STRIDE + 448, flag, 16, bar); };
    auto load_sc = [&](int i, int ss, uint32_t bar) {
        bulk_load(sbase + SC_OFF + ss * SC_STRIDE, absmax + chunk(i) * N_ + nt * BN, 448, bar);
        snap(ss, bar);
    };
    auto load_raw = [&](int u, int slot) {
        mbar_expect_tx(rawfull + 8 * slot, UNIT);
        tma_load_5d(sbase + RAW_OFF + roff(slot), &tmq, 0, 0, nt * 7, rank, 4 * chunk(u >> 1) + 2 * (u & 1), rawfull + 8 * slot);
    };
    auto load_half = [&](int b, uint32_t more) {
        const uint32_t bar = (b & 1) ? rawfull + 8 * rslot(b >> 1) : rawh + 8 * (b >> 1);
        mbar_expect_tx(bar, 7168 + more);
        tma_load_5d(sbase + RAW_OFF + roff(rslot(b >> 1)) + (b & 1) * 7168, &tmq1, 0, 0, nt * 7, rank, b, bar);
    };
    auto load_w = [&](int v) {
        mbar_expect_tx(bars + ubar(v), UNIT + (!(v & 1) && v <= 24 ? 32768 : 0) + (v == 20 ? 16 : 0));
        bulk_load(sbase + uoff(v), wpan + (2 * (chunk(v >> 1) - NC) + (v & 1)) * UNIT, UNIT, bars + ubar(v));
    };
    auto prefetch = [&](int c) {
        if (c + PFQ < NC) tma_prefetch_2d(&tmqp, nt * BN, (c + PFQ) * 64 + pair * 16 + rank * 8);
        if (NG == 1) { if ((unsigned)(c - PFG) < 4) tma_prefetch_2d(&tmqp, nt * BN, (12 + pair) * 64 + (c - PFG) * 16 + rank * 8); }
        else if ((unsigned)(c - PFG) < 6) {
            const int k = c - PFG, k0 = k + (k >= 3);
            tma_prefetch_2d(&tmqp, nt * BN, (8 + (k0 & 4) + pair) * 64 + (k0 & 3) * 16 + rank * 8);
            if (k == 1 || k == 4) tma_prefetch_2d(&tmqp, nt * BN, (8 + (k0 & 4) + pair) * 64 + 48 + rank * 8);
        }
        if (c + PFX > 2) tma_prefetch_2d(&tmx16, chunk(c + PFX) * 64, mt * BM + nt * 16);
        if (c >= 9) tma_prefetch_2d(&tmx16, chunk(c + 5) * 64, mt * BM + nt * 16);
    };
    if (warp == 7) {
        if (elect()) {
            mbar_init(xbar, 1); mbar_init(rawh + 8, 1); mbar_init(rawfull + 8 * rslot(1), 1); mbar_init(xbar + 8, 1);
            fence_async_smem();
            load_half(2, 448);
            bulk_load(sbase + SC_OFF + sslot(0) * SC_STRIDE, absmax + nt * BN, 448, rawh + 8);
            load_half(3, 0);
            mbar_expect_tx(xbar, 16384);
            tma_load_2d(sbase, &tmx, 0, mt * BM, xbar);
            mbar_expect_tx(xbar + 8, 16384);
            tma_load_2d(sbase + 16384, &tmx, 0, mt * BM + 128, xbar + 8);
            mbar_init(rawfull + 8 * rslot(2), 1); mbar_init(rawfull + 8 * rslot(3), 1); mbar_init(rawh + 16, 1); mbar_init(rawh + 24, 1);
            mbar_init(ebar, 7); mbar_init(ebar + 8, 7); mbar_init(wre + 16, 7); mbar_init(wre + 24, 7);
            sts128(ones, make_uint4(1, 0, 0, 0)); sts128(ones + 16, make_uint4(0, 1, 0, 0));
#pragma unroll
            for (int s = 0; s < 12; s++) if (!(s & 1) || s == 5 || s == 7) mbar_init(full + 8 * s, 1);
            mbar_arrive(full); mbar_arrive(full + 16);
#pragma unroll
            for (int s = 0; s < 3; s++) mbar_init(written + 8 * s, 7);
#pragma unroll
            for (int s = 0; s < 4; s++) mbar_init(bars + 160 + 8 * s, 4);
            asm volatile("fence.mbarrier_init.release.cluster;" ::: "memory");
            fence_async_smem();
            if ((sbase & 0xffffff) != 0x400) __trap();
        }
        __syncwarp();
        cluster_arrive();
        if (elect()) {
            asm volatile("prefetch.tensormap [%0];" ::"l"(&tmq) : "memory");
            asm volatile("prefetch.tensormap [%0];" ::"l"(&tmqp) : "memory");
            asm volatile("prefetch.tensormap [%0];" ::"l"(&tmx16) : "memory");
            asm volatile("prefetch.tensormap [%0];" ::"l"(&tmx64) : "memory");
            while (clk() - tstart < T2) { }
            load_half(4, 2 * SC_STRIDE);
            load_sc(1, sslot(1), rawh + 16); load_sc(2, sslot(2), rawh + 16);
            load_half(5, 0);
            while (clk() - tstart < T2B) { }
            tma_load_2d(sbase + 32768, &tmx, 64, mt * BM, full + 32);
            load_half(6, 0); load_half(7, 0);
            tma_load_2d(sbase + 32768 + 16384, &tmx, 64, mt * BM + 128, full + 32);
            load_sc(3, sslot(3), full + 48);
            while (clk() - tstart < T3) { }
            prefetch(-2); prefetch(-1);
        }
        __syncwarp();
        TSL(33);
        cluster_wait();
    } else {
        cluster_arrive();
    }
    const uint32_t rsrc = __shfl_sync(~0u, sbase + RAW_OFF + warp * 1024 + (lane & 7) * 128 + ((((lane >> 3) * 2) ^ (lane & 7)) << 4), lane);
    const uint32_t ssrc = sbase + SC_OFF + warp * 64;
    const int wpos = (nt & 1) ? (0x73210546 >> (4 * warp)) & 7 : warp;
    const uint32_t wown = wbase + rank * 7168 + wpos * 512;
    const uint32_t wdst = __shfl_sync(~0u, wown + lane * 16, lane);
    auto get_sc = [&](int ss) { return lds128(((opq(wdst) >> 3) & 0x30) + ssrc + ss * SC_STRIDE); };
    const uint32_t whalf = wbase + rank * 7168;
    const uint32_t pwhalf = mapa(whalf, rank ^ 1), pbars = mapa(bars, rank ^ 1);
    Lut lut;
    uint4 sc;
    uint4 q0, q1;
    auto fetch = [&](int slot, int h) {
        q0 = lds128(rsrc + roff(slot) + h * 7168);
        q1 = lds128((opq(rsrc) ^ 16) + roff(slot) + h * 7168);
    };
    auto signal = [&](uint32_t bar) { __syncwarp(); if (elect()) mbar_arrive(bar); __syncwarp(); };
    auto convert = [&](int ws, int h, bool w1, uint32_t bar1, uint32_t par1, bool w2, uint32_t bar2, uint32_t par2, bool next, int rsn,
                       bool sig, uint32_t sbar, bool scales, int cs) {
        bool ok1 = true, ok2 = true;
        if (w2) ok2 = mbar_try(bar2, par2);
        if (w1) ok1 = mbar_try(bar1, par1);
        uint4 w = dequant8(pack4(q0), pack4(q1), sc, lut);
        asm volatile("" : "+r"(w.x), "+r"(w.y), "+r"(w.z), "+r"(w.w));
        if (w1 && w2) mbar_wait2(bar2, par2, bar1, par1, ok1 && ok2);
        else if (w2) mbar_wait1(bar2, par2, ok2);
        else if (w1) mbar_wait1(bar1, par1, ok1);
        if (next) fetch(rsn, h ^ 1);
        sts128(wdst + ws * UNIT + h * 3584, w);
        if (sig) signal(sbar);
        if (scales) sc = get_sc(cs);
    };
    auto hand_over = [&](uint32_t sbar, uint32_t par, int ws, int h, int n, uint32_t more, bool raw, int un, int rs) {
        mbar_wait(sbar, par);
        fence_async_smem();
        if (elect()) {
            if (raw && n == 2) load_raw(un, rs);
            copy_to_peer(pwhalf + ws * UNIT + h * 3584, whalf + ws * UNIT + h * 3584, n * 3584, pbars + 8 * (2 * ws + h));
            mbar_expect_tx(full + 8 * (2 * ws + h), n * 3584 + more);
            if (raw && n == 1) load_raw(un, rs);
        }
        __syncwarp();
    };
    auto share = [&](int v, int ws) {
        if ((v >> 1) == G1 || (NG == 2 && (v >> 1) == G2)) {
            bulk_store(wpan + (2 * (chunk(v >> 1) - NC) + (v & 1)) * UNIT + rank * 7168, whalf + ws * UNIT, 7168);
            bulk_commit();
        }
    };
    auto publish = [&](int k) {
        asm volatile("cp.async.bulk.wait_group 0;" ::: "memory");
        asm volatile("cp.reduce.async.bulk.global.shared::cta.bulk_group.add.u32 [%0], [%1], 16;" ::"l"(flag), "r"(ones + 16 * k) : "memory");
    };
    auto check = [&](int k, int ss) {
        unsigned f0, f1;
        asm volatile("ld.shared.u32 %0, [%1];" : "=r"(f0) : "r"(sbase + SC_OFF + sslot(1) * SC_STRIDE + 448 + 4 * k) : "memory");
        asm volatile("ld.shared.u32 %0, [%1];" : "=r"(f1) : "r"(sbase + SC_OFF + ss * SC_STRIDE + 448 + 4 * k) : "memory");
        asm volatile("{\n.reg .pred p;\n.reg .u32 n, d;\nmov.u32 n, 0;\nLAB_POLL:\nsub.u32 d, %0, %1;\nsetp.ge.u32 p, d, 8;\n@p bra.uni LAB_DONE;\n"
                     "ld.relaxed.gpu.global.u32 %0, [%2];\nadd.u32 n, n, 1;\nsetp.lt.u32 p, n, 0x10000;\n@p bra.uni LAB_POLL;\nLAB_DONE:\n}\n"
                     : "+r"(f1) : "r"(f0 & ~7u), "l"(flag + k) : "memory");
    };
    auto sig_bar = [&](int b) { return (b & 1) ? written + 8 * rslot(b >> 1) : wre + 8 * (b >> 1); };
    auto sig_par = [](int b) { return (b & 1) ? ((b >> 1) / 3) & 1 : 0; };
    auto see = [&](int s) { if (s < 8) mbar_wait(full + 8 * s, 0); else mbar_wait(bars + ubar(s >> 1), upar(s >> 1)); };
    auto block = [&](int b, int sn) {
        const int u = b >> 1, h = b & 1;
        const bool next = b + 1 < 2 * NU, look = sn == 2 || (sn >= 4 && (sn < 8 || !(sn & 1)));
        const uint32_t lbar = sn == 2 ? ebar + 8 : full + 8 * (sn % 12), lpar = (sn / 12) & 1;
        if (!h && u >= NW) convert(u % NW, h, look, lbar, lpar, true, sig_bar(b - 3), sig_par(b - 3), next, rslot(u), false, 0, false, 0);
        else convert(u % NW, h, look, lbar, lpar, next && (h || b < 8), b == 5 ? rawh + 24 : rawfull + 8 * rslot((b + 1) >> 1), b == 5 ? 0 : rpar((b + 1) >> 1),
                     next, rslot((b + 1) >> 1), u < 4 || h, sig_bar(b), (b & 3) == 3 && next, sslot((b + 1) >> 2));
    };
    auto hand = [&](int b) {
        const int u = b >> 1;
        const uint32_t more = (u & 1) ? (u < NU - 1 ? SC_STRIDE : 0) : 32768;
        if (u < 4) hand_over(sig_bar(b), sig_par(b), u % NW, b & 1, 1, (b & 1) ? 0 : more, (b & 1), u + NR, rslot(u));
        else hand_over(sig_bar(b), sig_par(b), u % NW, 0, 2, more, u + NR < NU, u + NR, rslot(u));
    };
    auto pass_on = [&](int u) {
        fence_async_smem();
        __syncwarp();
        if (elect()) {
            const uint32_t o = wpos * 512 + u * UNIT;
            copy_to_peer(pwhalf + o, whalf + o, 512, pbars + 216 + 8 * u);
            copy_to_peer(pwhalf + o + 3584, whalf + o + 3584, 512, pbars + 216 + 8 * u);
            mbar_arrive(written + 8 * rslot(u));
            mbar_expect_tx(ebar + 8 * u, 1024);
        }
        __syncwarp();
    };
    bool ok0 = false;
    if (warp < 7) {
        lut.lo[0] = __byte_perm(c0.x, c0.y, 0x6420); lut.hi[0] = __byte_perm(c0.x, c0.y, 0x7531);
        lut.lo[1] = __byte_perm(c0.z, c0.w, 0x6420); lut.hi[1] = __byte_perm(c0.z, c0.w, 0x7531);
        lut.lo[2] = __byte_perm(c1.x, c1.y, 0x6420); lut.hi[2] = __byte_perm(c1.x, c1.y, 0x7531);
        lut.lo[3] = __byte_perm(c1.z, c1.w, 0x6420); lut.hi[3] = __byte_perm(c1.z, c1.w, 0x7531);
        const uint32_t d = wown + (lane >> 3) * 128 + (lane & 3) * 16 + (lane & 4) * 2;
#pragma unroll
        for (int j = 0; j < 4; j++) {
            uint32_t a, b;
            lookup4(pack4(q[j]), lut, a, b);
            asm volatile("st.shared.v2.b32 [%0], {%1, %2};" ::"r"(d + (j >> 1) * 3584 + (j & 1) * 64), "r"(mul_bf16x2(a, sf.x)), "r"(mul_bf16x2(b, sf.y)) : "memory");
        }
        TSL(33);
        cluster_wait();
        pass_on(0);
        TSL(34);
        mbar_wait(rawh + 8, 0);
        const uint4 a0 = lds128(rsrc + roff(rslot(1))), a1 = lds128((rsrc ^ 16) + roff(rslot(1))), s0 = get_sc(sslot(0));
        mbar_wait(rawfull + 8 * rslot(1), 0);
        const uint4 a2 = lds128(rsrc + roff(rslot(1)) + 7168), a3 = lds128((rsrc ^ 16) + roff(rslot(1)) + 7168);
        sts128(wdst + UNIT, dequant8(pack4(a0), pack4(a1), s0, lut));
        sts128(wdst + UNIT + 3584, dequant8(pack4(a2), pack4(a3), s0, lut));
        ok0 = mbar_try(xbar + 8 * wg, 0) & mbar_try(ebar, 0);
        pass_on(1);
    }
    TSL(31);
    mbar_wait2(xbar + 8 * wg, 0, ebar, 0, ok0);
    TSL(32);

    float acc0[112], acc1[112];
    const uint32_t descA = ((0x400 + wg * 16384) >> 4) | (1u << 16);
    auto mma = [&](int s) {
        const uint32_t da = opq(descA) + ((s >> 2) % 3) * (32768 >> 4) + (s & 3) * 2;
        wgmma_fence();
        wgmma224<1, 8>(acc0, da, bdesc(s)); wgmma224<1, 8>(acc1, da + 512, bdesc(s));
        wgmma_commit();
        wgmma_wait<2>();
    };
    wgmma_fence();
    wgmma224<0, 8>(acc0, descA, bdesc(0)); wgmma224<0, 8>(acc1, descA + 512, bdesc(0));
    wgmma_commit();
    TSL(0);
    mma(1); TSL(1);
    if (warp < 7) {
        mbar_wait(rawh + 16, 0); fetch(rslot(2), 0); sc = get_sc(sslot(1));
        block(4, -1); block(5, 2);
    } else {
        mbar_wait(sig_bar(3), 0);
        if (elect()) { load_raw(4, rslot(4)); load_x(2, 2, full + 64); prefetch(0); }
        __syncwarp();
        hand(4);
        mbar_wait(ebar + 8, 0);
    }
    mma(2); TSL(2);
    if (warp < 7) { block(6, -1); block(7, 3); } else { hand(5); hand(6); }
    mma(3); TSL(3);
    if (warp < 7) block(8, 4); else { hand(7); see(4); }
    mma(4); TSL(4);
    if (warp < 7) block(9, 5); else see(5);
    mma(5); TSL(5);
    if (warp < 7) { block(10, -1); block(11, 6); }
    else { hand(9); if (elect()) { load_sc(4, sslot(4), full + 80); prefetch(1); } __syncwarp(); see(6); }
    mma(6); TSL(6);
    if (warp < 7) block(12, 7); else { hand(11); see(7); }
    mma(7); TSL(7);
    if (warp < 7) block(13, 8); else { if (elect()) load_x(3, 0, full); __syncwarp(); see(8); }
    {
        uint32_t ph = 0;
#pragma unroll 1
        for (int cb = 2; cb < CE; cb += 3)
          static_for<2, 5>([&](auto I) {
            constexpr int cc = I.value;
            constexpr int j0 = cc % 3, j1 = (cc + 1) % 3, j2 = (cc + 2) % 3;
            const int c = cb + cc - 2;
            const bool last = cc == 4 && c == CE - 1;
            if (cc == 2) TSL(c < 8 ? 36 : 37);
            mma(4 * j0); TSL(cb == TLIT ? 4 * cc : 30);
            if (warp < 7) convert(2 * j1 + 1, 0, true, written + 8 * j2, ((2 * cc + 1) / 3) & 1, false, 0, 0, true, j0, false, 0, false, 0);
            else hand_over(written + 8 * j1, ((2 * cc + 2) / 3) & 1, 2 * j1, 0, 2, 32768, true, 2 * c + 5, j1);
            mma(4 * j0 + 1); TSL(cb == TLIT ? 4 * cc + 1 : 30);
            if (warp < 7) convert(2 * j1 + 1, 1, true, full + 32 * j0 + 16, ph, true, rawfull + 8 * j2, rpar(2 * cc + 4), true, j2, true, written + 8 * j0, true, j2);
            else {
                if (elect()) {
                    if ((cc - G1 - PUB) % 3 == 0 && c == G1 + PUB) publish(0);
                    load_sc(c + 3, j0, full + 32 * j1 + 16);
                    prefetch(c);
                    share(2 * c + 2, 2 * j1);
                }
                __syncwarp();
                mbar_wait(full + 32 * j0 + 16, ph);
            }
            if (j1 == 0) asm volatile("xor.b32 %0, %0, 1;" : "+r"(ph));
            mma(4 * j0 + 2); TSL(cb == TLIT ? 4 * cc + 2 : 30);
            if (warp < 7) convert(2 * j2, 0, true, written + 8 * j1, ((2 * cc + 2) / 3) & 1, false, 0, 0, true, j2, false, 0, false, 0);
            else {
                hand_over(written + 8 * j0, ((2 * cc + 3) / 3) & 1, 2 * j1 + 1, 0, 2, SC_STRIDE, !last, 2 * c + 6, j0);
                if (NG == 1 && last) {
                    check(0, sslot(CE + 1));
                    if (elect()) load_w(NU);
                    __syncwarp();
                }
            }
            mma(4 * j0 + 3); TSL(cb == TLIT ? 4 * cc + 3 : 30);
            if (warp < 7) convert(2 * j2, 1, true, full + 32 * j1, ph, true, rawfull + 8 * j1, rpar(2 * cc + 5), true, j1, true, written + 8 * j2, false, 0);
            else {
                if (elect()) {
                    if (NG == 1 && last) { load_l(12, 0, 0, full); load_l(12, 0, 1, full); }
                    else load_x(c + 2, j2, full + 32 * j2);
                    share(2 * c + 3, 2 * j1 + 1);
                }
                __syncwarp();
                mbar_wait(full + 32 * j1, ph);
            }
          });
    }
    static_for<4 * CE, 46>([&](auto S) {
        constexpr int s = S.value, b = s + 6;
        mma(s);
        if (NG == 2 && s == 2 * NU - 2) cluster_arrive();
        if (NG == 2 && s == 2 * NU) cluster_wait();
        if (warp < 7) {
            if (b < 2 * NU) block(b, s + 1);
            else if (s & 1) { signal(sig_bar(b)); see(s + 1); }
        } else {
            if (s == 45) see(46);
            if (!(s & 1) || s == 45) {
                constexpr int t = s == 45 ? 46 : s, bw = t + 5;
                if (bw == 2 * NU - 1) hand(bw);
                else mbar_wait(sig_bar(bw), sig_par(bw));
                if (NG == 2 && s == 4 * CE + 2) check(0, sslot(CE + 2));
                if (NG == 2 && s == 40) check(1, 1);
                if (elect()) {
                    if (s == 45) { mbar_expect_tx(xbar, 16384); load_l(14, 1, 0, xbar); }
                    static_for<NU, 31>([&](auto V) { if constexpr (utime(V.value) == t) load_w(V.value); });
                }
                __syncwarp();
                if (bw == 2 * NU - 3) hand(bw);
            } else {
                if (elect()) {
                    if (NG == 2 && s == 4 * G2 + 1) publish(1);
                    if ((s & 3) == 1) prefetch(s >> 2);
                    if (s == 37) snap(1, bars + ubar(20));
                    if (s == 43) { load_l(12, 0, 0, bars + ubar(24)); load_l(12, 0, 1, bars + ubar(24)); }
                    else if ((s & 3) == 3) load_x((s >> 2) + 2, ((s >> 2) + 2) % 3, bars + ubar(2 * (s >> 2) + 4));
                }
                __syncwarp();
                see(s + 1);
            }
            if (s == 44 && elect()) {
                asm volatile("prefetch.tensormap [%0];" ::"l"(&tmo64) : "memory");
                asm volatile("prefetch.tensormap [%0];" ::"l"(&tmo32) : "memory");
            }
            __syncwarp();
        }
    });
    if (wg == 1) bar_sync(8);
    mma(46);
    if (warp == 7) {
        wgmma_wait<1>();
        see(48);
        if (elect()) { load_w(31); mbar_expect_tx(xbar + 8, 16384); load_l(14, 1, 1, xbar + 8); }
        __syncwarp();
    }
    mma(47);
    if (wg == 0) bar_arrive(8);
    const uint32_t slice0 = sbase + wg * 16384 + (warp & 3) * 2048;
    auto slc = [&](int p) { return slice0 + (p >> 1) * 32768 + (p & 1) * 8192; };
    const int row0 = mt * BM + wg * 128 + (warp & 3) * 16, odd = nt & 1;
    const int colL = nt * BN + odd * 96, colA = nt * BN + (odd ? 32 : 128), colB = nt * BN + (odd ? 0 : 192);
    auto load_s = [&](int i, int p, uint32_t bar) { tma_load_2d(slc(p), &tmx16, chunk(i) * 64, row0 + 64, bar); };
    const uint32_t tA = opq(descA);
    see(48);
    wgmma_wait<0>();
    RT(0);
    float lo0[64], hi0[48], lo1[64], hi1[48];
#pragma unroll
    for (int i = 0; i < 64; i++) { asm volatile("mov.b32 %0, %1;" : "=f"(lo0[i]) : "f"(acc0[i])); asm volatile("mov.b32 %0, %1;" : "=f"(lo1[i]) : "f"(acc1[i])); }
#pragma unroll
    for (int i = 0; i < 48; i++) { asm volatile("mov.b32 %0, %1;" : "=f"(hi0[i]) : "f"(acc0[64 + i])); asm volatile("mov.b32 %0, %1;" : "=f"(hi1[i]) : "f"(acc1[64 + i])); }
    auto tdesc = [&](int p, int s) { return tA + (p >> 1) * (32768 >> 4) + (p & 1) * 512 + (s & 3) * 2; };
    auto ldesc = [&](int s) { return tdesc(s >> 2, s); };
    auto gdesc = [&](int s) { return tdesc(((s >> 2) + 4) % 6, s); };
    if (wg == 1) { mbar_wait(xbar + 8, 1); bar_sync(1); }
    static_for<0, 8>([&](auto V) {
        constexpr int v = 24 + (V.value == 0 || V.value > 3 ? V.value : V.value == 3 ? 1 : V.value + 1), s = 2 * (v - 24);
        if (v == 26) mbar_wait2(bars + ubar(26), upar(26), bars + ubar(27), upar(27), wg);
        else if (v == 28) mbar_wait2(bars + ubar(28), upar(28), xbar, 1, wg);
        else if (v != 24 && v != 27) mbar_wait1(bars + ubar(v), upar(v), wg);
        wgmma_fence();
        wgmma96<1, 8>(hi0, ldesc(s), bdesc(48 + s) + 128);
        wgmma96<1, 8>(hi0, ldesc(s + 1), bdesc(49 + s) + 128);
    });
    wgmma_commit();
    bar_arrive(1 + wg);
    if (NG == 1) cluster_arrive();
    wgmma_wait<0>();
    RT(1);
    stage_cols<64, 0>(hi0, slc(4)); send(slc(4), &tmo64, colA, row0);
    stage_cols<32, 32>(hi0, slc(5));
    RT(2);
    bar_sync(2 + wg);
    RT(3);
    wgmma_fence();
    static_for<0, 7>([&](auto S) { wgmma128<1, 8>(lo0, ldesc(S.value), bdesc(48 + S.value)); });
    wgmma_commit();
    send(slc(5), &tmo32, colB, row0);
    wgmma_fence();
    static_for<7, 16>([&](auto S) { wgmma128<1, 8>(lo0, ldesc(S.value), bdesc(48 + S.value)); });
    wgmma_commit();
    bar_arrive(3 + wg);
    RT(4);
    if (elect()) { mbar_expect_tx(gbar, 4096); bulk_wait_read<0>(); load_s(12, 4, gbar); load_s(13, 5, gbar); }
    __syncwarp();
    wgmma_wait<0>();
    RT(5);
    stage_cols<64, 0>(lo0, slc(2));
    if (elect()) { mbar_expect_tx(gbar + 8, 4096); load_s(14, 0, gbar + 8); load_s(15, 1, gbar + 8); }
    __syncwarp();
    const bool okg = mbar_try(gbar, 0);
    send(slc(2), &tmo64, colL, row0);
    stage_cols<64, 32>(lo0, slc(3));
    mbar_wait1(gbar, 0, okg);
    RT(6);
    bar_sync(4 + wg);
    RT(7);
    wgmma_fence();
    static_for<0, 8>([&](auto S) { wgmma128<1, 8>(lo1, gdesc(S.value), bdesc(48 + S.value)); });
    wgmma_commit();
    const bool okg2 = mbar_try(gbar + 8, 0);
    send(slc(3), &tmo64, colL + 64, row0);
    mbar_wait1(gbar + 8, 0, okg2);
    wgmma_fence();
    static_for<8, 16>([&](auto S) { wgmma128<1, 8>(lo1, gdesc(S.value), bdesc(48 + S.value)); });
    wgmma_commit();
    bar_arrive(5 + wg);
    RT(8);
    if (elect()) bulk_wait_read<0>();
    __syncwarp();
    wgmma_wait<0>();
    RT(9);
    stage_cols<64, 0>(lo1, slc(2)); send(slc(2), &tmo64, colL, row0 + 64);
    stage_cols<64, 32>(lo1, slc(3));
    RT(10);
    bar_sync(6 + wg);
    RT(11);
    wgmma_fence();
    static_for<0, 9>([&](auto S) { wgmma96<1, 8>(hi1, gdesc(S.value), bdesc(48 + S.value) + 128); });
    wgmma_commit();
    send(slc(3), &tmo64, colL + 64, row0 + 64);
    wgmma_fence();
    static_for<9, 16>([&](auto S) { wgmma96<1, 8>(hi1, gdesc(S.value), bdesc(48 + S.value) + 128); });
    wgmma_commit();
    if (wg == 0) bar_arrive(7);
    RT(12);
    wgmma_wait<0>();
    RT(13);
    stage_cols<64, 0>(hi1, slc(1)); send(slc(1), &tmo64, colA, row0 + 64);
    stage_cols<32, 32>(hi1, slc(5)); send(slc(5), &tmo32, colB, row0 + 64);
    RT(14);
    if (elect()) bulk_wait_read<0>();
    __syncwarp();
    RT(15);
    TSW(wg * 4, 38 + wg);
    TS_DUMP();
    TL_DUMP();
    if (NG == 1) cluster_wait();
}

typedef CUresult (*EncodeFn)(CUtensorMap*, CUtensorMapDataType, cuuint32_t, void*, const cuuint64_t*, const cuuint64_t*,
                             const cuuint32_t*, const cuuint32_t*, CUtensorMapInterleave, CUtensorMapSwizzle,
                             CUtensorMapL2promotion, CUtensorMapFloatOOBfill);

extern "C" void kernel_launch(void* const* d_in, const int* in_sizes, int n_in, void* d_out, int out_size) {
    const __nv_bfloat16* x = (const __nv_bfloat16*)d_in[0];
    const int* qw = (const int*)d_in[1];
    const __nv_bfloat16* cb = (const __nv_bfloat16*)d_in[2];
    const __nv_bfloat16* absmax = (const __nv_bfloat16*)d_in[3];
    static EncodeFn encode = nullptr;
    static void *wimg = nullptr, *gflag = nullptr;
    if (!encode) {
        cudaGetSymbolAddress(&wimg, g_wimg);
        cudaGetSymbolAddress(&gflag, g_flag);
        void* fn = nullptr;
        cudaDriverEntryPointQueryResult qr;
        cudaGetDriverEntryPoint("cuTensorMapEncodeTiled", &fn, cudaEnableDefault, &qr);
        encode = (EncodeFn)fn;
        cudaFuncSetAttribute(nf4_gemm_kernel, cudaFuncAttributeMaxDynamicSharedMemorySize, SMEM_BYTES);
    }
    CUtensorMap tmx, tmq, tmo64, tmo32, tmqp, tmx16, tmx64, tmq1;
    {
        cuuint64_t dims[2] = {(cuuint64_t)K_, (cuuint64_t)M_};
        cuuint64_t strides[1] = {(cuuint64_t)K_ * 2};
        cuuint32_t box[2] = {64, 128};
        cuuint32_t es[2] = {1, 1};
        encode(&tmx, CU_TENSOR_MAP_DATA_TYPE_BFLOAT16, 2, (void*)x, dims, strides, box, es, CU_TENSOR_MAP_INTERLEAVE_NONE,
               CU_TENSOR_MAP_SWIZZLE_128B, CU_TENSOR_MAP_L2_PROMOTION_L2_128B, CU_TENSOR_MAP_FLOAT_OOB_FILL_NONE);
        box[1] = 64;
        encode(&tmx64, CU_TENSOR_MAP_DATA_TYPE_BFLOAT16, 2, (void*)x, dims, strides, box, es, CU_TENSOR_MAP_INTERLEAVE_NONE,
               CU_TENSOR_MAP_SWIZZLE_128B, CU_TENSOR_MAP_L2_PROMOTION_L2_128B, CU_TENSOR_MAP_FLOAT_OOB_FILL_NONE);
        box[1] = 16;
        encode(&tmx16, CU_TENSOR_MAP_DATA_TYPE_BFLOAT16, 2, (void*)x, dims, strides, box, es, CU_TENSOR_MAP_INTERLEAVE_NONE,
               CU_TENSOR_MAP_SWIZZLE_128B, CU_TENSOR_MAP_L2_PROMOTION_L2_128B, CU_TENSOR_MAP_FLOAT_OOB_FILL_NONE);
    }
    {
        cuuint64_t dims[5] = {32, 8, (cuuint64_t)(N_ / 32), 2, (cuuint64_t)(K_ / 16)};
        cuuint64_t strides[4] = {(cuuint64_t)N_ * 4, 128, (cuuint64_t)N_ * 4 * 8, (cuuint64_t)N_ * 4 * 16};
        cuuint32_t box[5] = {32, 8, 7, 1, 2};
        cuuint32_t es[5] = {1, 1, 1, 1, 1};
        encode(&tmq, CU_TENSOR_MAP_DATA_TYPE_INT32, 5, (void*)qw, dims, strides, box, es, CU_TENSOR_MAP_INTERLEAVE_NONE,
               CU_TENSOR_MAP_SWIZZLE_128B, CU_TENSOR_MAP_L2_PROMOTION_L2_128B, CU_TENSOR_MAP_FLOAT_OOB_FILL_NONE);
        box[4] = 1;
        encode(&tmq1, CU_TENSOR_MAP_DATA_TYPE_INT32, 5, (void*)qw, dims, strides, box, es, CU_TENSOR_MAP_INTERLEAVE_NONE,
               CU_TENSOR_MAP_SWIZZLE_128B, CU_TENSOR_MAP_L2_PROMOTION_L2_128B, CU_TENSOR_MAP_FLOAT_OOB_FILL_NONE);
        cuuint64_t dims2[2] = {(cuuint64_t)N_, (cuuint64_t)K_};
        cuuint32_t box2[2] = {224, 8};
        encode(&tmqp, CU_TENSOR_MAP_DATA_TYPE_INT32, 2, (void*)qw, dims2, strides, box2, es, CU_TENSOR_MAP_INTERLEAVE_NONE,
               CU_TENSOR_MAP_SWIZZLE_NONE, CU_TENSOR_MAP_L2_PROMOTION_L2_128B, CU_TENSOR_MAP_FLOAT_OOB_FILL_NONE);
    }
    {
        cuuint64_t dims[2] = {(cuuint64_t)N_, (cuuint64_t)M_};
        cuuint64_t strides[1] = {(cuuint64_t)N_ * 2};
        cuuint32_t box[2] = {64, 16};
        cuuint32_t es[2] = {1, 1};
        encode(&tmo64, CU_TENSOR_MAP_DATA_TYPE_BFLOAT16, 2, d_out, dims, strides, box, es, CU_TENSOR_MAP_INTERLEAVE_NONE,
               CU_TENSOR_MAP_SWIZZLE_128B, CU_TENSOR_MAP_L2_PROMOTION_NONE, CU_TENSOR_MAP_FLOAT_OOB_FILL_NONE);
        box[0] = 32;
        encode(&tmo32, CU_TENSOR_MAP_DATA_TYPE_BFLOAT16, 2, d_out, dims, strides, box, es, CU_TENSOR_MAP_INTERLEAVE_NONE,
               CU_TENSOR_MAP_SWIZZLE_64B, CU_TENSOR_MAP_L2_PROMOTION_NONE, CU_TENSOR_MAP_FLOAT_OOB_FILL_NONE);
    }
    nf4_gemm_kernel<<<dim3(2, 16, 4), 256, SMEM_BYTES>>>(qw, cb, absmax, (uint8_t*)wimg, (unsigned*)gflag, tmx, tmq, tmo64, tmo32, tmqp, tmx16, tmx64, tmq1);
}
```

```cpp
#include <cuda_runtime.h>
#include <cuda_bf16.h>
#include <cuda.h>
#include <stdint.h>

#define NG 2
#define G1 (NG == 1 ? 7 : 5)
#define G2 8
#define PFG (NG == 1 ? 1 : 0)
#define NF 2
#define FAT 1
#define MIX 0
#define GG3 6
#define LASTO 0
#define E2 0
#define PF12 0
#define FS 38
#define SPLIT 1
#define PUB 1
#define T2 900
#define T2B 1300
#define T3 1700
#define TLPRO -2
#define TLIT 2
constexpr int M_ = 2048, K_ = 1024, N_ = 3584;
constexpr int BM = 256, BN = 224;
constexpr int UNIT = 14336;
constexpr int NW = 6, NR = 3;
constexpr int NU = 32 - 6 * NG;
constexpr int NC = 16 - 4 * NG;
constexpr int CE = NU / 2 - 2;
constexpr int PFQ = 4, PFX = 3;
constexpr int RAW_OFF = 3 * 32768;
constexpr int SC_OFF = RAW_OFF + 2 * UNIT;
constexpr int SC_STRIDE = 464;
constexpr int W_OFF = 127 * 1024;
constexpr int RAW2_OFF = W_OFF + NW * UNIT;
constexpr int BAR_OFF = RAW2_OFF + UNIT;
constexpr int SMEM_BYTES = BAR_OFF + 320;
__device__ __align__(1024) uint8_t g_wimg[16 * 8 * NG * UNIT];
__device__ __align__(128) unsigned g_flag[16 * 32];

#define TSL(i)
#define TL_DUMP()
#define TSW(w, i)
#define TS_INIT()
#define TS_DUMP()
#define RT(i)

__device__ __forceinline__ uint32_t smem_u32(const void* p) { return (uint32_t)__cvta_generic_to_shared(p); }
__device__ __forceinline__ bool elect() {
    uint32_t ok;
    asm volatile("{\n.reg .pred p;\nelect.sync _|p, 0xffffffff;\nselp.u32 %0, 1, 0, p;\n}\n" : "=r"(ok));
    return ok != 0;
}
__device__ __forceinline__ void mbar_init(uint32_t bar, uint32_t cnt) { asm volatile("mbarrier.init.shared::cta.b64 [%0], %1;" ::"r"(bar), "r"(cnt) : "memory"); }
__device__ __forceinline__ void mbar_expect_tx(uint32_t bar, uint32_t bytes) { asm volatile("mbarrier.arrive.expect_tx.shared::cta.b64 _, [%0], %1;" ::"r"(bar), "r"(bytes) : "memory"); }
__device__ __forceinline__ void mbar_arrive(uint32_t bar) { asm volatile("mbarrier.arrive.shared::cta.b64 _, [%0];" ::"r"(bar) : "memory"); }
#define BOUNDED
#define WAIT_INIT "mov.u32 n, 0;\n"
#define WAIT_NEXT "@p bra.uni LAB_DONE;\nadd.u32 n, n, 1;\nsetp.lt.u32 p, n, 0x4000;\n@p bra.uni LAB_WAIT;\n"
__device__ __forceinline__ void mbar_wait(uint32_t bar, uint32_t parity) {
    asm volatile(
        "{\n.reg .pred p;\n.reg .u32 n;\n"
        WAIT_INIT
        "LAB_WAIT:\n"
        "mbarrier.try_wait.parity.shared::cta.b64 p, [%0], %1;\n"
        WAIT_NEXT
        "LAB_DONE:\n}\n" ::"r"(bar), "r"(parity) : "memory");
}
__device__ __forceinline__ bool mbar_try(uint32_t bar, uint32_t parity) {
    uint32_t ok;
    asm volatile("{\n.reg .pred p;\nmbarrier.test_wait.parity.shared::cta.b64 p, [%1], %2;\nselp.u32 %0, 1, 0, p;\n}\n" : "=r"(ok) : "r"(bar), "r"(parity) : "memory");
    return ok != 0;
}
__device__ __forceinline__ void mbar_wait1(uint32_t b0, uint32_t p0, bool skip) {
    asm volatile(
        "{\n.reg .pred p;\n.reg .u32 n;\n"
        "setp.ne.u32 p, %2, 0;\n@p bra.uni LAB_DONE;\n"
        WAIT_INIT
        "LAB_WAIT:\n"
        "mbarrier.try_wait.parity.shared::cta.b64 p, [%0], %1;\n"
        WAIT_NEXT
        "LAB_DONE:\n}\n" ::"r"(b0), "r"(p0), "r"((uint32_t)skip) : "memory");
}
__device__ __forceinline__ void mbar_wait2(uint32_t b0, uint32_t p0, uint32_t b1, uint32_t p1, bool skip = false) {
    asm volatile(
        "{\n.reg .pred p, q;\n.reg .u32 n;\n"
        "setp.ne.u32 p, %4, 0;\n@p bra.uni LAB_DONE;\n"
        WAIT_INIT
        "LAB_WAIT:\n"
        "mbarrier.try_wait.parity.shared::cta.b64 p, [%0], %1;\n"
        "mbarrier.try_wait.parity.shared::cta.b64 q, [%2], %3;\n"
        "and.pred p, p, q;\n"
        WAIT_NEXT
        "LAB_DONE:\n}\n" ::"r"(b0), "r"(p0), "r"(b1), "r"(p1), "r"((uint32_t)skip) : "memory");
}
__device__ __forceinline__ void tma_load_2d(uint32_t dst, const CUtensorMap* tm, int c0, int c1, uint32_t bar) {
    asm volatile("cp.async.bulk.tensor.2d.shared::cluster.global.mbarrier::complete_tx::bytes [%0], [%1, {%2, %3}], [%4];"
                 ::"r"(dst), "l"(tm), "r"(c0), "r"(c1), "r"(bar) : "memory");
}
__device__ __forceinline__ void tma_load_5d(uint32_t dst, const CUtensorMap* tm, int c0, int c1, int c2, int c3, int c4, uint32_t bar) {
    asm volatile("cp.async.bulk.tensor.5d.shared::cluster.global.mbarrier::complete_tx::bytes [%0], [%1, {%2, %3, %4, %5, %6}], [%7];"
                 ::"r"(dst), "l"(tm), "r"(c0), "r"(c1), "r"(c2), "r"(c3), "r"(c4), "r"(bar) : "memory");
}
__device__ __forceinline__ void tma_prefetch_2d(const CUtensorMap* tm, int c0, int c1) {
    asm volatile("cp.async.bulk.prefetch.tensor.2d.L2.global [%0, {%1, %2}];" ::"l"(tm), "r"(c0), "r"(c1) : "memory");
}
__device__ __forceinline__ void bulk_load(uint32_t dst, const void* src, uint32_t bytes, uint32_t bar) {
    asm volatile("cp.async.bulk.shared::cluster.global.mbarrier::complete_tx::bytes [%0], [%1], %2, [%3];"
                 ::"r"(dst), "l"(src), "r"(bytes), "r"(bar) : "memory");
}
__device__ __forceinline__ void cluster_arrive() { asm volatile("barrier.cluster.arrive.relaxed.aligned;" ::: "memory"); }
__device__ __forceinline__ void cluster_wait() { asm volatile("barrier.cluster.wait.acquire.aligned;" ::: "memory"); }
__device__ __forceinline__ uint32_t mapa(uint32_t addr, uint32_t cta) {
    uint32_t r; asm("mapa.shared::cluster.u32 %0, %1, %2;" : "=r"(r) : "r"(addr), "r"(cta)); return r;
}
__device__ __forceinline__ void copy_to_peer(uint32_t cdst, uint32_t src, uint32_t bytes, uint32_t cbar) {
    asm volatile("cp.async.bulk.shared::cluster.shared::cta.mbarrier::complete_tx::bytes [%0], [%1], %2, [%3];"
                 ::"r"(cdst), "r"(src), "r"(bytes), "r"(cbar) : "memory");
}
__device__ __forceinline__ void wgmma_fence() { asm volatile("wgmma.fence.sync.aligned;" ::: "memory"); }
__device__ __forceinline__ void wgmma_commit() { asm volatile("wgmma.commit_group.sync.aligned;" ::: "memory"); }
template <int N> __device__ __forceinline__ void wgmma_wait() { asm volatile("wgmma.wait_group.sync.aligned %0;" ::"n"(N) : "memory"); }
__device__ __forceinline__ uint32_t pack_bf16(float lo, float hi) {
    uint32_t r; asm("cvt.rn.bf16x2.f32 %0, %1, %2;" : "=r"(r) : "f"(hi), "f"(lo)); return r;
}
__device__ __forceinline__ void stmatrix_x4(uint32_t addr, uint32_t a, uint32_t b, uint32_t c, uint32_t d) {
    asm volatile("stmatrix.sync.aligned.m8n8.x4.shared.b16 [%0], {%1, %2, %3, %4};" ::"r"(addr), "r"(a), "r"(b), "r"(c), "r"(d) : "memory");
}
__device__ __forceinline__ uint4 ldmatrix_x4(uint32_t a) {
    uint4 v; asm volatile("ldmatrix.sync.aligned.m8n8.x4.shared.b16 {%0, %1, %2, %3}, [%4];" : "=r"(v.x), "=r"(v.y), "=r"(v.z), "=r"(v.w) : "r"(a) : "memory"); return v;
}
__device__ __forceinline__ uint4 lds128(uint32_t a) {
    uint4 v; asm volatile("ld.shared.v4.b32 {%0, %1, %2, %3}, [%4];" : "=r"(v.x), "=r"(v.y), "=r"(v.z), "=r"(v.w) : "r"(a) : "memory"); return v;
}
__device__ __forceinline__ void sts128(uint32_t a, uint4 v) {
    asm volatile("st.shared.v4.b32 [%0], {%1, %2, %3, %4};" ::"r"(a), "r"(v.x), "r"(v.y), "r"(v.z), "r"(v.w) : "memory");
}
__device__ __forceinline__ uint4 ldg128(const void* p) {
    uint4 v; asm volatile("ld.global.nc.v4.b32 {%0, %1, %2, %3}, [%4];" : "=r"(v.x), "=r"(v.y), "=r"(v.z), "=r"(v.w) : "l"(p) : "memory"); return v;
}
__device__ __forceinline__ unsigned clk() { unsigned c; asm volatile("mov.u32 %0, %%clock;" : "=r"(c) :: "memory"); return c; }
__device__ __forceinline__ uint32_t mul_bf16x2(uint32_t a, uint32_t b) { uint32_t r; asm("mul.rn.bf16x2 %0, %1, %2;" : "=r"(r) : "r"(a), "r"(b)); return r; }
struct Lut { uint32_t lo[4], hi[4]; };
__device__ __forceinline__ uint32_t prmt(uint32_t a, uint32_t b, uint32_t s) { uint32_t r; asm("prmt.b32 %0, %1, %2, %3;" : "=r"(r) : "r"(a), "r"(b), "r"(s)); return r; }
__device__ __forceinline__ uint32_t pack4(const uint4& q) {
    uint32_t ab, cd, p;
    asm volatile("mad.lo.u32 %0, %1, 16, %2;" : "=r"(ab) : "r"(q.y), "r"(q.x));
    asm volatile("mad.lo.u32 %0, %1, 16, %2;" : "=r"(cd) : "r"(q.w), "r"(q.z));
    asm volatile("mad.lo.u32 %0, %1, 256, %2;" : "=r"(p) : "r"(cd), "r"(ab));
    return p;
}
__device__ __forceinline__ void lookup4(uint32_t p, const Lut& t, uint32_t& w01, uint32_t& w23) {
    const uint32_t t8 = p & 0x8888u, s7 = p & 0x7777u;
    const uint32_t sel = (t8 >> 1) + 0x3210u;
    const uint32_t lo = prmt(prmt(t.lo[0], t.lo[1], p), prmt(t.lo[2], t.lo[3], s7), sel);
    const uint32_t hi = prmt(prmt(t.hi[0], t.hi[1], p), prmt(t.hi[2], t.hi[3], s7), sel);
    w01 = prmt(lo, hi, 0x5140);
    w23 = prmt(lo, hi, 0x7362);
}
__device__ __forceinline__ uint4 dequant8(uint32_t p0, uint32_t p1, const uint4& sc, const Lut& t) {
    uint4 r;
    lookup4(p0, t, r.x, r.y);
    lookup4(p1, t, r.z, r.w);
    r.x = mul_bf16x2(r.x, sc.x); r.y = mul_bf16x2(r.y, sc.y); r.z = mul_bf16x2(r.z, sc.z); r.w = mul_bf16x2(r.w, sc.w);
    return r;
}
__device__ __forceinline__ void fence_async_smem() { asm volatile("fence.proxy.async.shared::cta;" ::: "memory"); }

template <int SCALE_D, int BHI, uint32_t AHI = 0x40000040u>
__device__ __forceinline__ void wgmma224(float (&d)[112], uint32_t descA, uint32_t descB) {
    asm volatile(
        "{\n.reg .pred p;\n.reg .b64 da, db;\nsetp.ne.b32 p, %114, 0;\n"
        "mov.b64 da, {%112, %116};\nmov.b64 db, {%113, %115};\n"
        "wgmma.mma_async.sync.aligned.m64n224k16.f32.bf16.bf16 "
        "{%0, %1, %2, %3, %4, %5, %6, %7, %8, %9, %10, %11, %12, %13, %14, %15, "
        "%16, %17, %18, %19, %20, %21, %22, %23, %24, %25, %26, %27, %28, %29, %30, %31, "
        "%32, %33, %34, %35, %36, %37, %38, %39, %40, %41, %42, %43, %44, %45, %46, %47, "
        "%48, %49, %50, %51, %52, %53, %54, %55, %56, %57, %58, %59, %60, %61, %62, %63, "
        "%64, %65, %66, %67, %68, %69, %70, %71, %72, %73, %74, %75, %76, %77, %78, %79, "
        "%80, %81, %82, %83, %84, %85, %86, %87, %88, %89, %90, %91, %92, %93, %94, %95, "
        "%96, %97, %98, %99, %100, %101, %102, %103, %104, %105, %106, %107, %108, %109, %110, %111}, "
        "da, db, p, 1, 1, 0, 1;\n}\n"
        : "+f"(d[0]), "+f"(d[1]), "+f"(d[2]), "+f"(d[3]), "+f"(d[4]), "+f"(d[5]), "+f"(d[6]), "+f"(d[7]),
          "+f"(d[8]), "+f"(d[9]), "+f"(d[10]), "+f"(d[11]), "+f"(d[12]), "+f"(d[13]), "+f"(d[14]), "+f"(d[15]),
          "+f"(d[16]), "+f"(d[17]), "+f"(d[18]), "+f"(d[19]), "+f"(d[20]), "+f"(d[21]), "+f"(d[22]), "+f"(d[23]),
          "+f"(d[24]), "+f"(d[25]), "+f"(d[26]), "+f"(d[27]), "+f"(d[28]), "+f"(d[29]), "+f"(d[30]), "+f"(d[31]),
          "+f"(d[32]), "+f"(d[33]), "+f"(d[34]), "+f"(d[35]), "+f"(d[36]), "+f"(d[37]), "+f"(d[38]), "+f"(d[39]),
          "+f"(d[40]), "+f"(d[41]), "+f"(d[42]), "+f"(d[43]), "+f"(d[44]), "+f"(d[45]), "+f"(d[46]), "+f"(d[47]),
          "+f"(d[48]), "+f"(d[49]), "+f"(d[50]), "+f"(d[51]), "+f"(d[52]), "+f"(d[53]), "+f"(d[54]), "+f"(d[55]),
          "+f"(d[56]), "+f"(d[57]), "+f"(d[58]), "+f"(d[59]), "+f"(d[60]), "+f"(d[61]), "+f"(d[62]), "+f"(d[63]),
          "+f"(d[64]), "+f"(d[65]), "+f"(d[66]), "+f"(d[67]), "+f"(d[68]), "+f"(d[69]), "+f"(d[70]), "+f"(d[71]),
          "+f"(d[72]), "+f"(d[73]), "+f"(d[74]), "+f"(d[75]), "+f"(d[76]), "+f"(d[77]), "+f"(d[78]), "+f"(d[79]),
          "+f"(d[80]), "+f"(d[81]), "+f"(d[82]), "+f"(d[83]), "+f"(d[84]), "+f"(d[85]), "+f"(d[86]), "+f"(d[87]),
          "+f"(d[88]), "+f"(d[89]), "+f"(d[90]), "+f"(d[91]), "+f"(d[92]), "+f"(d[93]), "+f"(d[94]), "+f"(d[95]),
          "+f"(d[96]), "+f"(d[97]), "+f"(d[98]), "+f"(d[99]), "+f"(d[100]), "+f"(d[101]), "+f"(d[102]), "+f"(d[103]),
          "+f"(d[104]), "+f"(d[105]), "+f"(d[106]), "+f"(d[107]), "+f"(d[108]), "+f"(d[109]), "+f"(d[110]), "+f"(d[111])
        : "r"(descA), "r"(descB), "n"(SCALE_D), "n"(BHI), "n"(AHI));
}

template <int SCALE_D, int BHI, uint32_t AHI = 0x40000040u>
__device__ __forceinline__ void wgmma128(float (&d)[64], uint32_t descA, uint32_t descB) {
    asm volatile(
        "{\n.reg .pred p;\n.reg .b64 da, db;\nsetp.ne.b32 p, %66, 0;\n"
        "mov.b64 da, {%64, %68};\nmov.b64 db, {%65, %67};\n"
        "wgmma.mma_async.sync.aligned.m64n128k16.f32.bf16.bf16 "
        "{%0, %1, %2, %3, %4, %5, %6, %7, %8, %9, %10, %11, %12, %13, %14, %15, "
        "%16, %17, %18, %19, %20, %21, %22, %23, %24, %25, %26, %27, %28, %29, %30, %31, "
        "%32, %33, %34, %35, %36, %37, %38, %39, %40, %41, %42, %43, %44, %45, %46, %47, "
        "%48, %49, %50, %51, %52, %53, %54, %55, %56, %57, %58, %59, %60, %61, %62, %63}, "
        "da, db, p, 1, 1, 0, 1;\n}\n"
        : "+f"(d[0]), "+f"(d[1]), "+f"(d[2]), "+f"(d[3]), "+f"(d[4]), "+f"(d[5]), "+f"(d[6]), "+f"(d[7]),
          "+f"(d[8]), "+f"(d[9]), "+f"(d[10]), "+f"(d[11]), "+f"(d[12]), "+f"(d[13]), "+f"(d[14]), "+f"(d[15]),
          "+f"(d[16]), "+f"(d[17]), "+f"(d[18]), "+f"(d[19]), "+f"(d[20]), "+f"(d[21]), "+f"(d[22]), "+f"(d[23]),
          "+f"(d[24]), "+f"(d[25]), "+f"(d[26]), "+f"(d[27]), "+f"(d[28]), "+f"(d[29]), "+f"(d[30]), "+f"(d[31]),
          "+f"(d[32]), "+f"(d[33]), "+f"(d[34]), "+f"(d[35]), "+f"(d[36]), "+f"(d[37]), "+f"(d[38]), "+f"(d[39]),
          "+f"(d[40]), "+f"(d[41]), "+f"(d[42]), "+f"(d[43]), "+f"(d[44]), "+f"(d[45]), "+f"(d[46]), "+f"(d[47]),
          "+f"(d[48]), "+f"(d[49]), "+f"(d[50]), "+f"(d[51]), "+f"(d[52]), "+f"(d[53]), "+f"(d[54]), "+f"(d[55]),
          "+f"(d[56]), "+f"(d[57]), "+f"(d[58]), "+f"(d[59]), "+f"(d[60]), "+f"(d[61]), "+f"(d[62]), "+f"(d[63])
        : "r"(descA), "r"(descB), "n"(SCALE_D), "n"(BHI), "n"(AHI));
}

template <int SCALE_D, int BHI, uint32_t AHI = 0x40000040u>
__device__ __forceinline__ void wgmma96(float (&d)[48], uint32_t descA, uint32_t descB) {
    asm volatile(
        "{\n.reg .pred p;\n.reg .b64 da, db;\nsetp.ne.b32 p, %50, 0;\n"
        "mov.b64 da, {%48, %52};\nmov.b64 db, {%49, %51};\n"
        "wgmma.mma_async.sync.aligned.m64n96k16.f32.bf16.bf16 "
        "{%0, %1, %2, %3, %4, %5, %6, %7, %8, %9, %10, %11, %12, %13, %14, %15, "
        "%16, %17, %18, %19, %20, %21, %22, %23, %24, %25, %26, %27, %28, %29, %30, %31, "
        "%32, %33, %34, %35, %36, %37, %38, %39, %40, %41, %42, %43, %44, %45, %46, %47}, "
        "da, db, p, 1, 1, 0, 1;\n}\n"
        : "+f"(d[0]), "+f"(d[1]), "+f"(d[2]), "+f"(d[3]), "+f"(d[4]), "+f"(d[5]), "+f"(d[6]), "+f"(d[7]),
          "+f"(d[8]), "+f"(d[9]), "+f"(d[10]), "+f"(d[11]), "+f"(d[12]), "+f"(d[13]), "+f"(d[14]), "+f"(d[15]),
          "+f"(d[16]), "+f"(d[17]), "+f"(d[18]), "+f"(d[19]), "+f"(d[20]), "+f"(d[21]), "+f"(d[22]), "+f"(d[23]),
          "+f"(d[24]), "+f"(d[25]), "+f"(d[26]), "+f"(d[27]), "+f"(d[28]), "+f"(d[29]), "+f"(d[30]), "+f"(d[31]),
          "+f"(d[32]), "+f"(d[33]), "+f"(d[34]), "+f"(d[35]), "+f"(d[36]), "+f"(d[37]), "+f"(d[38]), "+f"(d[39]),
          "+f"(d[40]), "+f"(d[41]), "+f"(d[42]), "+f"(d[43]), "+f"(d[44]), "+f"(d[45]), "+f"(d[46]), "+f"(d[47])
        : "r"(descA), "r"(descB), "n"(SCALE_D), "n"(BHI), "n"(AHI));
}

template <int BHI>
__device__ __forceinline__ void wgmma128r(float (&d)[64], const uint4& a, uint32_t descB) {
    asm volatile(
        "{\n.reg .pred p;\n.reg .b64 db;\nsetp.eq.b32 p, 0, 0;\n"
        "mov.b64 db, {%68, %69};\n"
        "wgmma.mma_async.sync.aligned.m64n128k16.f32.bf16.bf16 "
        "{%0, %1, %2, %3, %4, %5, %6, %7, %8, %9, %10, %11, %12, %13, %14, %15, "
        "%16, %17, %18, %19, %20, %21, %22, %23, %24, %25, %26, %27, %28, %29, %30, %31, "
        "%32, %33, %34, %35, %36, %37, %38, %39, %40, %41, %42, %43, %44, %45, %46, %47, "
        "%48, %49, %50, %51, %52, %53, %54, %55, %56, %57, %58, %59, %60, %61, %62, %63}, "
        "{%64, %65, %66, %67}, db, p, 1, 1, 1;\n}\n"
        : "+f"(d[0]), "+f"(d[1]), "+f"(d[2]), "+f"(d[3]), "+f"(d[4]), "+f"(d[5]), "+f"(d[6]), "+f"(d[7]),
          "+f"(d[8]), "+f"(d[9]), "+f"(d[10]), "+f"(d[11]), "+f"(d[12]), "+f"(d[13]), "+f"(d[14]), "+f"(d[15]),
          "+f"(d[16]), "+f"(d[17]), "+f"(d[18]), "+f"(d[19]), "+f"(d[20]), "+f"(d[21]), "+f"(d[22]), "+f"(d[23]),
          "+f"(d[24]), "+f"(d[25]), "+f"(d[26]), "+f"(d[27]), "+f"(d[28]), "+f"(d[29]), "+f"(d[30]), "+f"(d[31]),
          "+f"(d[32]), "+f"(d[33]), "+f"(d[34]), "+f"(d[35]), "+f"(d[36]), "+f"(d[37]), "+f"(d[38]), "+f"(d[39]),
          "+f"(d[40]), "+f"(d[41]), "+f"(d[42]), "+f"(d[43]), "+f"(d[44]), "+f"(d[45]), "+f"(d[46]), "+f"(d[47]),
          "+f"(d[48]), "+f"(d[49]), "+f"(d[50]), "+f"(d[51]), "+f"(d[52]), "+f"(d[53]), "+f"(d[54]), "+f"(d[55]),
          "+f"(d[56]), "+f"(d[57]), "+f"(d[58]), "+f"(d[59]), "+f"(d[60]), "+f"(d[61]), "+f"(d[62]), "+f"(d[63])
        : "r"(a.x), "r"(a.y), "r"(a.z), "r"(a.w), "r"(descB), "n"(BHI));
}

template <int BHI>
__device__ __forceinline__ void wgmma96r(float (&d)[48], const uint4& a, uint32_t descB) {
    asm volatile(
        "{\n.reg .pred p;\n.reg .b64 db;\nsetp.eq.b32 p, 0, 0;\n"
        "mov.b64 db, {%52, %53};\n"
        "wgmma.mma_async.sync.aligned.m64n96k16.f32.bf16.bf16 "
        "{%0, %1, %2, %3, %4, %5, %6, %7, %8, %9, %10, %11, %12, %13, %14, %15, "
        "%16, %17, %18, %19, %20, %21, %22, %23, %24, %25, %26, %27, %28, %29, %30, %31, "
        "%32, %33, %34, %35, %36, %37, %38, %39, %40, %41, %42, %43, %44, %45, %46, %47}, "
        "{%48, %49, %50, %51}, db, p, 1, 1, 1;\n}\n"
        : "+f"(d[0]), "+f"(d[1]), "+f"(d[2]), "+f"(d[3]), "+f"(d[4]), "+f"(d[5]), "+f"(d[6]), "+f"(d[7]),
          "+f"(d[8]), "+f"(d[9]), "+f"(d[10]), "+f"(d[11]), "+f"(d[12]), "+f"(d[13]), "+f"(d[14]), "+f"(d[15]),
          "+f"(d[16]), "+f"(d[17]), "+f"(d[18]), "+f"(d[19]), "+f"(d[20]), "+f"(d[21]), "+f"(d[22]), "+f"(d[23]),
          "+f"(d[24]), "+f"(d[25]), "+f"(d[26]), "+f"(d[27]), "+f"(d[28]), "+f"(d[29]), "+f"(d[30]), "+f"(d[31]),
          "+f"(d[32]), "+f"(d[33]), "+f"(d[34]), "+f"(d[35]), "+f"(d[36]), "+f"(d[37]), "+f"(d[38]), "+f"(d[39]),
          "+f"(d[40]), "+f"(d[41]), "+f"(d[42]), "+f"(d[43]), "+f"(d[44]), "+f"(d[45]), "+f"(d[46]), "+f"(d[47])
        : "r"(a.x), "r"(a.y), "r"(a.z), "r"(a.w), "r"(descB), "n"(BHI));
}

__device__ __forceinline__ uint32_t opq(uint32_t v) { asm volatile("" : "+r"(v)); return v; }
template <int I> struct IC { static constexpr int value = I; };
template <int B, int E, class F> __device__ __forceinline__ void static_for(F&& f) {
    if constexpr (B < E) { f(IC<B>{}); static_for<B + 1, E>(f); }
}

__device__ __forceinline__ void tma_store_2d(const CUtensorMap* tm, uint32_t src, int c0, int c1) {
    asm volatile("cp.async.bulk.tensor.2d.global.shared::cta.bulk_group [%0, {%2, %3}], [%1];" ::"l"(tm), "r"(src), "r"(c0), "r"(c1) : "memory");
}
__device__ __forceinline__ void bulk_store(void* dst, uint32_t src, uint32_t bytes) {
    asm volatile("cp.async.bulk.global.shared::cta.bulk_group [%0], [%1], %2;" ::"l"(dst), "r"(src), "r"(bytes) : "memory");
}
__device__ __forceinline__ void bulk_commit() { asm volatile("cp.async.bulk.commit_group;" ::: "memory"); }
template <int N> __device__ __forceinline__ void bulk_wait_read() { asm volatile("cp.async.bulk.wait_group.read %0;" ::"n"(N) : "memory"); }
__device__ __forceinline__ void bar_arrive(int id) { asm volatile("bar.arrive %0, 256;" ::"r"(id) : "memory"); }
__device__ __forceinline__ void bar_sync(int id) { asm volatile("bar.sync %0, 256;" ::"r"(id) : "memory"); }
template <int NC, int OFF, int N>
__device__ __forceinline__ void stage_cols(const float (&acc)[N], uint32_t stg) {
    int lane; asm volatile("mov.u32 %0, %%laneid;" : "=r"(lane));
    const int r = lane & 15;
    const uint32_t a0 = NC == 64 ? stg + r * 128 + (((lane >> 4) ^ (r & 7)) << 4) : stg + r * 64 + (((lane >> 4) ^ ((r >> 1) & 3)) << 4);
#pragma unroll
    for (int j = 0; j < NC / 16; j++) {
        const int i = OFF + 8 * j;
        stmatrix_x4(a0 ^ (j * 32), pack_bf16(acc[i], acc[i + 1]), pack_bf16(acc[i + 2], acc[i + 3]), pack_bf16(acc[i + 4], acc[i + 5]), pack_bf16(acc[i + 6], acc[i + 7]));
    }
}
__device__ __forceinline__ void send(uint32_t stg, const CUtensorMap* tmo, int col, int row) {
    fence_async_smem();
    __syncwarp();
    if (elect()) { tma_store_2d(tmo, stg, col, row); bulk_commit(); }
    __syncwarp();
}

__host__ __device__ constexpr int rslot(int u) { return (2 * u) % 3; }
__host__ __device__ constexpr int roff(int slot) { return slot < 2 ? slot * UNIT : RAW2_OFF - RAW_OFF; }
__host__ __device__ constexpr int rpar(int u) { return (u / 3 - (u % 3 == 0)) & 1; }
__host__ __device__ constexpr int sslot(int c) { return c < 3 ? c + 3 : c % 3; }
__host__ __device__ constexpr int vturn(int v) {
    return v < 20 ? v : v == 20 ? -20 : v == 21 ? -22 : v == 22 ? 21 : v == 23 ? -21 : v == 24 ? 20 : v < 29 ? v - 3 : v == 29 ? -23 : v == 30 ? -25 : 27;
}
__host__ __device__ constexpr int uoff(int v) { return vturn(v) < 0 ? RAW_OFF + roff(rslot(-vturn(v))) : W_OFF + (vturn(v) % NW) * UNIT; }
__host__ __device__ constexpr int ubar(int v) { return vturn(v) < 0 ? 96 + 8 * rslot(-vturn(v)) : 16 * (vturn(v) % NW); }
__host__ __device__ constexpr int upar(int v) { return vturn(v) < 0 ? rpar(-vturn(v)) : (vturn(v) / NW) & 1; }
__host__ __device__ constexpr int utime(int v) {
    return v < 22 ? 34 : v == 22 ? 36 : v == 25 ? 38 : v < 27 ? 40 : v == 27 ? 42 : 2 * v - 14;
}
__host__ __device__ constexpr uint32_t bdesc(int s) { return (uint32_t)(((0x400 + uoff(s >> 1)) >> 4) | ((7168u >> 4) << 16)) + (s & 1) * 224; }

__global__ void __cluster_dims__(2, 1, 1) __launch_bounds__(256, 1)
nf4_gemm_kernel(const int* __restrict__ qw, const __nv_bfloat16* __restrict__ cb, const __nv_bfloat16* __restrict__ absmax,
                uint8_t* __restrict__ wimg, unsigned* __restrict__ gflag,
                const __grid_constant__ CUtensorMap tmx, const __grid_constant__ CUtensorMap tmq, const __grid_constant__ CUtensorMap tmo64,
                const __grid_constant__ CUtensorMap tmo32, const __grid_constant__ CUtensorMap tmqp, const __grid_constant__ CUtensorMap tmx16,
                const __grid_constant__ CUtensorMap tmx64, const __grid_constant__ CUtensorMap tmq1) {
    extern __shared__ __align__(1024) uint8_t smem[];
    const uint32_t sbase = smem_u32(smem);
    const int rank = blockIdx.x, nt = blockIdx.y, pair = blockIdx.z;
    uint4 q[4], c0, c1;
    uint2 sf;
    if (threadIdx.x < 224) {
        const uint32_t t = threadIdx.x;
        const int* p = qw + (uint32_t)((t & 3) * (N_ - 1) + t + blockIdx.x * (8 * N_) + blockIdx.y * BN);
        q[0] = ldg128(p); q[1] = ldg128(p + 4 * N_);
        q[2] = ldg128(p + 16 * N_); q[3] = ldg128(p + 20 * N_);
        const void* ps = absmax + (uint32_t)(opq(t & ~3u) + blockIdx.y * BN);
        asm volatile("ld.global.nc.v2.b32 {%0, %1}, [%2];" : "=r"(sf.x), "=r"(sf.y) : "l"(ps) : "memory");
        c0 = ldg128(cb); c1 = ldg128(cb + 8);
    }
    const unsigned tstart = clk();
    const int mt = pair * 2 + rank;
    const int lane = threadIdx.x & 31;
    const int warp = __reduce_max_sync(~0u, threadIdx.x >> 5);
    const int wg = warp >> 2;
    const uint32_t bars = sbase + BAR_OFF;
    const uint32_t full = bars, rawfull = bars + 96, written = bars + 120, xbar = bars + 144, gbar = bars + 160 + wg * 16;
    const uint32_t rawh = bars + 192 - 8, ebar = bars + 216, wre = bars + 232 - 16, ones = bars + 256;
    const uint32_t wbase = sbase + W_OFF;
    TS_INIT();
    __syncwarp();
    TSW(0, 0);

    auto insert = [](uint64_t m, int pos, int v) { const uint64_t low = (1ull << (4 * pos)) - 1; return (m & low) | ((m & ~low) << 4) | ((uint64_t)v << (4 * pos)); };
    const uint64_t others = (0xedcfedu >> (4 * pair)) & 0xfff;
    const uint64_t cmap = NG == 1 ? insert(0xba9876543210ull, G1, 12 + pair) | (others << 52)
                                  : insert(insert(0x76543210ull, G1, 8 + pair), G2, 12 + pair) | ((others - 0x444) << 40) | (others << 52);
    auto chunk = [&](int i) { return (int)(cmap >> (4 * i)) & 15; };
    unsigned* flag = gflag + nt * 32;
    uint8_t* wpan = wimg + nt * (8 * NG * UNIT);
    auto load_x = [&](int i, int slot, uint32_t bar) {
        tma_load_2d(sbase + slot * 32768, &tmx, chunk(i) * 64, mt * BM, bar);
        tma_load_2d(sbase + slot * 32768 + 16384, &tmx, chunk(i) * 64, mt * BM + 128, bar);
    };
    auto load_l = [&](int i, int slot, int g, uint32_t bar) {
        tma_load_2d(sbase + slot * 32768 + g * 16384, &tmx64, chunk(i) * 64, mt * BM + g * 128, bar);
        tma_load_2d(sbase + slot * 32768 + g * 16384 + 8192, &tmx64, chunk(i + 1) * 64, mt * BM + g * 128, bar);
    };
    auto snap = [&](int ss, uint32_t bar) { bulk_load(sbase + SC_OFF + ss * SC_STRIDE + 448, flag, 16, bar); };
    auto load_sc = [&](int i, int ss, uint32_t bar) {
        bulk_load(sbase + SC_OFF + ss * SC_STRIDE, absmax + chunk(i) * N_ + nt * BN, 448, bar);
        snap(ss, bar);
    };
    auto load_raw = [&](int u, int slot) {
        mbar_expect_tx(rawfull + 8 * slot, UNIT);
        tma_load_5d(sbase + RAW_OFF + roff(slot), &tmq, 0, 0, nt * 7, rank, 4 * chunk(u >> 1) + 2 * (u & 1), rawfull + 8 * slot);
    };
    auto load_half = [&](int b, uint32_t more) {
        const uint32_t bar = (b & 1) ? rawfull + 8 * rslot(b >> 1) : rawh + 8 * (b >> 1);
        mbar_expect_tx(bar, 7168 + more);
        tma_load_5d(sbase + RAW_OFF + roff(rslot(b >> 1)) + (b & 1) * 7168, &tmq1, 0, 0, nt * 7, rank, b, bar);
    };
    auto load_w = [&](int v) {
        mbar_expect_tx(bars + ubar(v), UNIT + (!(v & 1) && v <= 24 ? 32768 : 0) + (v == 20 ? 16 : 0));
        bulk_load(sbase + uoff(v), wpan + (2 * (chunk(v >> 1) - NC) + (v & 1)) * UNIT, UNIT, bars + ubar(v));
    };
    auto prefetch = [&](int c) {
        if (c + PFQ < NC) tma_prefetch_2d(&tmqp, nt * BN, (c + PFQ) * 64 + pair * 16 + rank * 8);
        if (NG == 1) { if ((unsigned)(c - PFG) < 4) tma_prefetch_2d(&tmqp, nt * BN, (12 + pair) * 64 + (c - PFG) * 16 + rank * 8); }
        else if ((unsigned)(c - PFG) < 6) {
            const int k = c - PFG, k0 = k + (k >= 3);
            tma_prefetch_2d(&tmqp, nt * BN, (8 + (k0 & 4) + pair) * 64 + (k0 & 3) * 16 + rank * 8);
            if (k == 1 || k == 4) tma_prefetch_2d(&tmqp, nt * BN, (8 + (k0 & 4) + pair) * 64 + 48 + rank * 8);
        }
        if (c + PFX > 2) tma_prefetch_2d(&tmx16, chunk(c + PFX) * 64, mt * BM + nt * 16);
        if (c >= 9 || (PF12 && c == 7)) tma_prefetch_2d(&tmx16, chunk(c + 5) * 64, mt * BM + nt * 16);
    };
    if (warp == 7) {
        if (elect()) {
            mbar_init(xbar, 1); mbar_init(rawh + 8, 1); mbar_init(rawfull + 8 * rslot(1), 1); mbar_init(xbar + 8, 1);
            fence_async_smem();
            load_half(2, 448);
            bulk_load(sbase + SC_OFF + sslot(0) * SC_STRIDE, absmax + nt * BN, 448, rawh + 8);
            load_half(3, 0);
            mbar_expect_tx(xbar, 16384);
            tma_load_2d(sbase, &tmx, 0, mt * BM, xbar);
            mbar_expect_tx(xbar + 8, 16384);
            tma_load_2d(sbase + 16384, &tmx, 0, mt * BM + 128, xbar + 8);
            mbar_init(rawfull + 8 * rslot(2), 1); mbar_init(rawfull + 8 * rslot(3), 1); mbar_init(rawh + 16, 1); mbar_init(rawh + 24, 1);
            mbar_init(ebar, 7); mbar_init(ebar + 8, 7); mbar_init(wre + 16, 7); mbar_init(wre + 24, 7);
            sts128(ones, make_uint4(1, 0, 0, 0)); sts128(ones + 16, make_uint4(0, 1, 0, 0));
#pragma unroll
            for (int s = 0; s < 12; s++) if (!(s & 1) || s == 5 || s == 7) mbar_init(full + 8 * s, 1);
            mbar_arrive(full); mbar_arrive(full + 16);
#pragma unroll
            for (int s = 0; s < 3; s++) mbar_init(written + 8 * s, 7);
#pragma unroll
            for (int s = 0; s < 4; s++) mbar_init(bars + 160 + 8 * s, 4);
            asm volatile("fence.mbarrier_init.release.cluster;" ::: "memory");
            fence_async_smem();
            if ((sbase & 0xffffff) != 0x400) __trap();
        }
        __syncwarp();
        cluster_arrive();
        if (elect()) {
            asm volatile("prefetch.tensormap [%0];" ::"l"(&tmq) : "memory");
            asm volatile("prefetch.tensormap [%0];" ::"l"(&tmqp) : "memory");
            asm volatile("prefetch.tensormap [%0];" ::"l"(&tmx16) : "memory");
            asm volatile("prefetch.tensormap [%0];" ::"l"(&tmx64) : "memory");
            while (clk() - tstart < T2) { }
            load_half(4, 2 * SC_STRIDE);
            load_sc(1, sslot(1), rawh + 16); load_sc(2, sslot(2), rawh + 16);
            load_half(5, 0);
            while (clk() - tstart < T2B) { }
            tma_load_2d(sbase + 32768, &tmx, 64, mt * BM, full + 32);
            load_half(6, 0); load_half(7, 0);
            tma_load_2d(sbase + 32768 + 16384, &tmx, 64, mt * BM + 128, full + 32);
            load_sc(3, sslot(3), full + 48);
            while (clk() - tstart < T3) { }
            prefetch(-2); prefetch(-1);
        }
        __syncwarp();
        TSL(33);
        cluster_wait();
    } else {
        cluster_arrive();
    }
    const uint32_t rsrc = __shfl_sync(~0u, sbase + RAW_OFF + warp * 1024 + (lane & 7) * 128 + ((((lane >> 3) * 2) ^ (lane & 7)) << 4), lane);
    const uint32_t ssrc = sbase + SC_OFF + warp * 64;
    const int wpos = (nt & 1) ? (0x73210546 >> (4 * warp)) & 7 : warp;
    const uint32_t wown = wbase + rank * 7168 + wpos * 512;
    const uint32_t wdst = __shfl_sync(~0u, wown + lane * 16, lane);
    auto get_sc = [&](int ss) { return lds128(((opq(wdst) >> 3) & 0x30) + ssrc + ss * SC_STRIDE); };
    const uint32_t whalf = wbase + rank * 7168;
    const uint32_t pwhalf = mapa(whalf, rank ^ 1), pbars = mapa(bars, rank ^ 1);
    Lut lut;
    uint4 sc;
    uint4 q0, q1;
    auto fetch = [&](int slot, int h) {
        q0 = lds128(rsrc + roff(slot) + h * 7168);
        q1 = lds128((opq(rsrc) ^ 16) + roff(slot) + h * 7168);
    };
    auto signal = [&](uint32_t bar) { __syncwarp(); if (elect()) mbar_arrive(bar); __syncwarp(); };
    auto convert = [&](int ws, int h, bool w1, uint32_t bar1, uint32_t par1, bool w2, uint32_t bar2, uint32_t par2, bool next, int rsn,
                       bool sig, uint32_t sbar, bool scales, int cs) {
        bool ok1 = true, ok2 = true;
        if (w2) ok2 = mbar_try(bar2, par2);
        if (w1) ok1 = mbar_try(bar1, par1);
        uint4 w = dequant8(pack4(q0), pack4(q1), sc, lut);
        asm volatile("" : "+r"(w.x), "+r"(w.y), "+r"(w.z), "+r"(w.w));
        if (w1 && w2) mbar_wait2(bar2, par2, bar1, par1, ok1 && ok2);
        else if (w2) mbar_wait1(bar2, par2, ok2);
        else if (w1) mbar_wait1(bar1, par1, ok1);
        if (next) fetch(rsn, h ^ 1);
        sts128(wdst + ws * UNIT + h * 3584, w);
        if (sig) signal(sbar);
        if (scales) sc = get_sc(cs);
    };
    auto hand_over = [&](uint32_t sbar, uint32_t par, int ws, int h, int n, uint32_t more, bool raw, int un, int rs) {
        mbar_wait(sbar, par);
        fence_async_smem();
        if (elect()) {
            if (raw && n == 2) load_raw(un, rs);
            copy_to_peer(pwhalf + ws * UNIT + h * 3584, whalf + ws * UNIT + h * 3584, n * 3584, pbars + 8 * (2 * ws + h));
            mbar_expect_tx(full + 8 * (2 * ws + h), n * 3584 + more);
            if (raw && n == 1) load_raw(un, rs);
        }
        __syncwarp();
    };
    auto share = [&](int g, uint32_t o, uint32_t n) {
        bulk_store(wpan + 2 * (chunk(g) - NC) * UNIT + rank * 7168 + o, whalf + 2 * (g % 3) * UNIT + o, n);
        bulk_commit();
    };
    auto publish = [&](int k) {
        asm volatile("cp.async.bulk.wait_group 0;" ::: "memory");
        asm volatile("cp.reduce.async.bulk.global.shared::cta.bulk_group.add.u32 [%0], [%1], 16;" ::"l"(flag), "r"(ones + 16 * k) : "memory");
    };
    auto check = [&](int k, int ss) {
        unsigned f0, f1;
        asm volatile("ld.shared.u32 %0, [%1];" : "=r"(f0) : "r"(sbase + SC_OFF + sslot(1) * SC_STRIDE + 448 + 4 * k) : "memory");
        asm volatile("ld.shared.u32 %0, [%1];" : "=r"(f1) : "r"(sbase + SC_OFF + ss * SC_STRIDE + 448 + 4 * k) : "memory");
        asm volatile("{\n.reg .pred p;\n.reg .u32 n, d;\nmov.u32 n, 0;\nLAB_POLL:\nsub.u32 d, %0, %1;\nsetp.ge.u32 p, d, 8;\n@p bra.uni LAB_DONE;\n"
                     "ld.relaxed.gpu.global.u32 %0, [%2];\nadd.u32 n, n, 1;\nsetp.lt.u32 p, n, 0x10000;\n@p bra.uni LAB_POLL;\nLAB_DONE:\n}\n"
                     : "+r"(f1) : "r"(f0 & ~7u), "l"(flag + k) : "memory");
    };
    auto sig_bar = [&](int b) { return (b & 1) ? written + 8 * rslot(b >> 1) : wre + 8 * (b >> 1); };
    auto sig_par = [](int b) { return (b & 1) ? ((b >> 1) / 3) & 1 : 0; };
    auto see = [&](int s) { if (s < 8) mbar_wait(full + 8 * s, 0); else mbar_wait(bars + ubar(s >> 1), upar(s >> 1)); };
    auto block = [&](int b, int sn) {
        const int u = b >> 1, h = b & 1;
        const bool next = b + 1 < 2 * NU, look = sn == 2 || (sn >= 4 && (sn < 8 || !(sn & 1)));
        const uint32_t lbar = sn == 2 ? ebar + 8 : full + 8 * (sn % 12), lpar = (sn / 12) & 1;
        if (!h && u >= NW) convert(u % NW, h, look, lbar, lpar, true, sig_bar(b - 3), sig_par(b - 3), next, rslot(u), false, 0, false, 0);
        else convert(u % NW, h, look, lbar, lpar, next && (h || b < 8), b == 5 ? rawh + 24 : rawfull + 8 * rslot((b + 1) >> 1), b == 5 ? 0 : rpar((b + 1) >> 1),
                     next, rslot((b + 1) >> 1), u < 4 || h, sig_bar(b), (b & 3) == 3 && next, sslot((b + 1) >> 2));
    };
    auto hand = [&](int b) {
        const int u = b >> 1;
        const uint32_t more = (u & 1) ? (u < NU - 1 ? SC_STRIDE : 0) : 32768;
        if (u < 4) hand_over(sig_bar(b), sig_par(b), u % NW, b & 1, 1, (b & 1) ? 0 : more, (b & 1), u + NR, rslot(u));
        else hand_over(sig_bar(b), sig_par(b), u % NW, 0, 2, more, u + NR < NU, u + NR, rslot(u));
    };
    auto pass_on = [&](int u) {
        fence_async_smem();
        __syncwarp();
        if (elect()) {
            const uint32_t o = wpos * 512 + u * UNIT;
            copy_to_peer(pwhalf + o, whalf + o, 512, pbars + 216 + 8 * u);
            copy_to_peer(pwhalf + o + 3584, whalf + o + 3584, 512, pbars + 216 + 8 * u);
            mbar_arrive(written + 8 * rslot(u));
            mbar_expect_tx(ebar + 8 * u, 1024);
        }
        __syncwarp();
    };
    bool ok0 = false;
    if (warp < 7) {
        lut.lo[0] = __byte_perm(c0.x, c0.y, 0x6420); lut.hi[0] = __byte_perm(c0.x, c0.y, 0x7531);
        lut.lo[1] = __byte_perm(c0.z, c0.w, 0x6420); lut.hi[1] = __byte_perm(c0.z, c0.w, 0x7531);
        lut.lo[2] = __byte_perm(c1.x, c1.y, 0x6420); lut.hi[2] = __byte_perm(c1.x, c1.y, 0x7531);
        lut.lo[3] = __byte_perm(c1.z, c1.w, 0x6420); lut.hi[3] = __byte_perm(c1.z, c1.w, 0x7531);
        const uint32_t d = wown + (lane >> 3) * 128 + (lane & 3) * 16 + (lane & 4) * 2;
#pragma unroll
        for (int j = 0; j < 4; j++) {
            uint32_t a, b;
            lookup4(pack4(q[j]), lut, a, b);
            asm volatile("st.shared.v2.b32 [%0], {%1, %2};" ::"r"(d + (j >> 1) * 3584 + (j & 1) * 64), "r"(mul_bf16x2(a, sf.x)), "r"(mul_bf16x2(b, sf.y)) : "memory");
        }
        TSL(33);
        cluster_wait();
        pass_on(0);
        TSL(34);
        mbar_wait(rawh + 8, 0);
        const uint4 a0 = lds128(rsrc + roff(rslot(1))), a1 = lds128((rsrc ^ 16) + roff(rslot(1))), s0 = get_sc(sslot(0));
        mbar_wait(rawfull + 8 * rslot(1), 0);
        const uint4 a2 = lds128(rsrc + roff(rslot(1)) + 7168), a3 = lds128((rsrc ^ 16) + roff(rslot(1)) + 7168);
        sts128(wdst + UNIT, dequant8(pack4(a0), pack4(a1), s0, lut));
        sts128(wdst + UNIT + 3584, dequant8(pack4(a2), pack4(a3), s0, lut));
        ok0 = mbar_try(xbar + 8 * wg, 0) & mbar_try(ebar, 0);
        pass_on(1);
    }
    TSL(31);
    mbar_wait2(xbar + 8 * wg, 0, ebar, 0, ok0);
    TSL(32);

    float acc0[112], acc1[112];
    const uint32_t descA = ((0x400 + wg * 16384) >> 4) | (1u << 16);
    auto mma = [&](int s) {
        const uint32_t da = opq(descA) + ((s >> 2) % 3) * (32768 >> 4) + (s & 3) * 2;
        wgmma_fence();
        wgmma224<1, 8>(acc0, da, bdesc(s)); wgmma224<1, 8>(acc1, da + 512, bdesc(s));
        wgmma_commit();
        wgmma_wait<2>();
    };
    wgmma_fence();
    wgmma224<0, 8>(acc0, descA, bdesc(0)); wgmma224<0, 8>(acc1, descA + 512, bdesc(0));
    wgmma_commit();
    TSL(0);
    mma(1); TSL(1);
    if (warp < 7) {
        mbar_wait(rawh + 16, 0); fetch(rslot(2), 0); sc = get_sc(sslot(1));
        block(4, -1); block(5, 2);
    } else {
        mbar_wait(sig_bar(3), 0);
        if (elect()) { load_raw(4, rslot(4)); load_x(2, 2, full + 64); prefetch(0); }
        __syncwarp();
        hand(4);
        mbar_wait(ebar + 8, 0);
    }
    mma(2); TSL(2);
    if (warp < 7) { block(6, -1); block(7, 3); } else { hand(5); hand(6); }
    mma(3); TSL(3);
    if (warp < 7) block(8, 4); else { hand(7); see(4); }
    mma(4); TSL(4);
    if (warp < 7) block(9, 5); else see(5);
    mma(5); TSL(5);
    if (warp < 7) { block(10, -1); block(11, 6); }
    else { hand(9); if (elect()) { load_sc(4, sslot(4), full + 80); prefetch(1); } __syncwarp(); see(6); }
    mma(6); TSL(6);
    if (warp < 7) block(12, 7); else { hand(11); see(7); }
    mma(7); TSL(7);
    if (warp < 7) block(13, 8); else { if (elect()) load_x(3, 0, full); __syncwarp(); see(8); }
    {
        uint32_t ph = 0;
#pragma unroll 1
        for (int cb = 2; cb < CE; cb += 3)
          static_for<2, 5>([&](auto I) {
            constexpr int cc = I.value;
            constexpr int j0 = cc % 3, j1 = (cc + 1) % 3, j2 = (cc + 2) % 3;
            const int c = cb + cc - 2;
            const bool last = cc == 4 && c == CE - 1;
            auto sh = [&](int h) {
                if (SPLIT) {
                    if ((cc - G1 + 1) % 3 == 0 && c == G1 - 1) share(G1, h * 3584, 3584);
                    if ((cc - G1) % 3 == 0 && c == G1) share(G1, UNIT + h * 3584, 3584);
                } else if ((cc - G1 + 1) % 3 == 0 && c == G1 - 1) share(G1, h * UNIT, 7168);
                if ((cc - G2 + 1) % 3 == 0 && c == G2 - 1) share(G2, h * UNIT, 7168);
            };
            if (cc == 2) TSL(c < 8 ? 36 : 37);
            mma(4 * j0); TSL(cb == TLIT ? 4 * cc : 30);
            if (warp < 7) convert(2 * j1 + 1, 0, true, written + 8 * j2, ((2 * cc + 1) / 3) & 1, false, 0, 0, true, j0, false, 0, false, 0);
            else hand_over(written + 8 * j1, ((2 * cc + 2) / 3) & 1, 2 * j1, 0, 2, 32768, true, 2 * c + 5, j1);
            mma(4 * j0 + 1); TSL(cb == TLIT ? 4 * cc + 1 : 30);
            if (warp < 7) convert(2 * j1 + 1, 1, true, full + 32 * j0 + 16, ph, true, rawfull + 8 * j2, rpar(2 * cc + 4), true, j2, true, written + 8 * j0, true, j2);
            else {
                if (elect()) {
                    if ((cc - G1 - PUB) % 3 == 0 && c == G1 + PUB) publish(0);
                    load_sc(c + 3, j0, full + 32 * j1 + 16);
                    prefetch(c);
                    sh(0);
                }
                __syncwarp();
                mbar_wait(full + 32 * j0 + 16, ph);
            }
            if (j1 == 0) asm volatile("xor.b32 %0, %0, 1;" : "+r"(ph));
            mma(4 * j0 + 2); TSL(cb == TLIT ? 4 * cc + 2 : 30);
            if (warp < 7) convert(2 * j2, 0, true, written + 8 * j1, ((2 * cc + 2) / 3) & 1, false, 0, 0, true, j2, false, 0, false, 0);
            else {
                hand_over(written + 8 * j0, ((2 * cc + 3) / 3) & 1, 2 * j1 + 1, 0, 2, SC_STRIDE, !last, 2 * c + 6, j0);
                if (NG == 1 && last) {
                    check(0, sslot(CE + 1));
                    if (elect()) load_w(NU);
                    __syncwarp();
                }
            }
            mma(4 * j0 + 3); TSL(cb == TLIT ? 4 * cc + 3 : 30);
            if (warp < 7) convert(2 * j2, 1, true, full + 32 * j1, ph, true, rawfull + 8 * j1, rpar(2 * cc + 5), true, j1, true, written + 8 * j2, false, 0);
            else {
                if (elect()) {
                    if (NG == 1 && last) { load_l(12, 0, 0, full); load_l(12, 0, 1, full); }
                    else load_x(c + 2, j2, full + 32 * j2);
                    sh(1);
                }
                __syncwarp();
                mbar_wait(full + 32 * j1, ph);
            }
          });
    }
    uint4 fa[4 * NF];
    auto get_frag = [&](int f, uint32_t rows, int j0 = 0, int j1 = 4) {
        int ln; asm volatile("mov.u32 %0, %%laneid;" : "=r"(ln));
        const uint32_t a = rows + (ln & 15) * 128 + (((ln >> 4) ^ (ln & 7)) << 4);
#pragma unroll
        for (int j = j0; j < j1; j++) fa[4 * f + j] = ldmatrix_x4(a ^ (j * 32));
    };
    static_for<4 * CE, 46>([&](auto S) {
        constexpr int s = S.value, b = s + 6;
        mma(s);
        if (TLIT == 99) TSL(s - 26);
        if (NG == 2 && s == 2 * NU - 2) cluster_arrive();
        if (NG == 2 && s == 2 * NU) cluster_wait();
        if (s == 36) mbar_wait(rawh + 8, 1);
        if (s >= 36 && s < 40) get_frag(0, sbase + uoff(24) + wg * (uoff(23) - uoff(24)) + (warp & 3) * 2048, s - 36, s - 35);
        if (warp < 7) {
            if (b < 2 * NU) block(b, s + 1);
            else if (s & 1) { signal(sig_bar(b)); see(s + 1); }
        } else {
            if (s == 45) see(46);
            if (!(s & 1) || s == 45) {
                constexpr int t = s == 45 ? 46 : s, bw = t + 5;
                if (bw == 2 * NU - 1) hand(bw);
                else mbar_wait(sig_bar(bw), sig_par(bw));
                if (NG == 2 && s == 4 * CE + 2) check(0, sslot(CE + 2));
                if (NG == 2 && s == 40) check(1, 1);
                if (elect()) {
                    if (s == 45) { mbar_expect_tx(xbar, 16384); load_l(14, 1, 0, xbar); }
                    static_for<NU, 31>([&](auto V) { if constexpr (utime(V.value) == t) load_w(V.value); });
                }
                __syncwarp();
                if (bw == 2 * NU - 3) hand(bw);
            } else {
                if (elect()) {
                    if (NG == 2 && s == 4 * CE + 1) publish(1);
                    if ((s & 3) == 1) prefetch(s >> 2);
                    if (s == 37) snap(1, bars + ubar(20));
                    if (s == 33) {
                        mbar_expect_tx(rawh + 8, 16384);
                        tma_load_2d(sbase + uoff(24), &tmx64, chunk(12) * 64, mt * BM + 64, rawh + 8);
                        tma_load_2d(sbase + uoff(23), &tmx64, chunk(12) * 64, mt * BM + 192, rawh + 8);
                    }
                    if (s == 43) { load_l(12, 0, 0, bars + ubar(24)); load_l(12, 0, 1, bars + ubar(24)); }
                    else if ((s & 3) == 3) load_x((s >> 2) + 2, ((s >> 2) + 2) % 3, bars + ubar(2 * (s >> 2) + 4));
                }
                __syncwarp();
                see(s + 1);
            }
            if (s == 44 && elect()) {
                asm volatile("prefetch.tensormap [%0];" ::"l"(&tmo64) : "memory");
                asm volatile("prefetch.tensormap [%0];" ::"l"(&tmo32) : "memory");
            }
            __syncwarp();
        }
    });
    if (wg == 1) bar_sync(8);
    mma(46);
    if (warp == 7) {
        wgmma_wait<1>();
        see(48);
        if (elect()) { load_w(31); mbar_expect_tx(xbar + 8, 16384); load_l(14, 1, 1, xbar + 8); }
        __syncwarp();
    }
    mma(47);
    if (wg == 0) bar_arrive(8);
    const uint32_t slice0 = sbase + wg * 16384 + (warp & 3) * 2048;
    auto slc = [&](int p) { return slice0 + (p >> 1) * 32768 + (p & 1) * 8192; };
    const int row0 = mt * BM + wg * 128 + (warp & 3) * 16, odd = nt & 1;
    const int colL = nt * BN + odd * 96, colA = nt * BN + (odd ? 32 : 128), colB = nt * BN + (odd ? 0 : 192);
    auto load_s = [&](int i, int p, uint32_t bar) { tma_load_2d(slc(p), &tmx16, chunk(i) * 64, row0 + 64, bar); };
    const uint32_t tA = opq(descA);
    see(48);
    wgmma_wait<0>();
    RT(0);
    float lo0[64], hi0[48], lo1[64], hi1[48];
#pragma unroll
    for (int i = 0; i < 64; i++) { asm volatile("mov.b32 %0, %1;" : "=f"(lo0[i]) : "f"(acc0[i])); asm volatile("mov.b32 %0, %1;" : "=f"(lo1[i]) : "f"(acc1[i])); }
#pragma unroll
    for (int i = 0; i < 48; i++) { asm volatile("mov.b32 %0, %1;" : "=f"(hi0[i]) : "f"(acc0[64 + i])); asm volatile("mov.b32 %0, %1;" : "=f"(hi1[i]) : "f"(acc1[64 + i])); }
    auto tdesc = [&](int p, int s) { return tA + (p >> 1) * (32768 >> 4) + (p & 1) * 512 + (s & 3) * 2; };
    auto ldesc = [&](int s) { return tdesc(s >> 2, s); };
    auto gdesc = [&](int s) { return tdesc(((s >> 2) + 3) % 6, s); };
    if (wg == 1) { mbar_wait(xbar + 8, 1); bar_sync(1); }
    static_for<0, 8>([&](auto V) {
        constexpr int v = 24 + (V.value == 0 || V.value > 3 ? V.value : V.value == 3 ? 1 : V.value + 1), s = 2 * (v - 24);
        if (v == 26) mbar_wait2(bars + ubar(26), upar(26), bars + ubar(27), upar(27), wg);
        else if (v == 28) mbar_wait2(bars + ubar(28), upar(28), xbar, 1, wg);
        else if (v != 24 && v != 27) mbar_wait1(bars + ubar(v), upar(v), wg);
        wgmma_fence();
        wgmma96<1, 8>(hi0, ldesc(s), bdesc(48 + s) + 128);
        wgmma96<1, 8>(hi0, ldesc(s + 1), bdesc(49 + s) + 128);
    });
    wgmma_commit();
    bar_arrive(1 + wg);
    if (NG == 1) cluster_arrive();
    wgmma_wait<0>();
    RT(1);
    stage_cols<64, 0>(hi0, slc(4)); send(slc(4), &tmo64, colA, row0);
    stage_cols<32, 32>(hi0, slc(5));
    RT(2);
    bar_sync(2 + wg);
    RT(3);
    wgmma_fence();
    static_for<0, 7>([&](auto S) { wgmma128<1, 8>(lo0, ldesc(S.value), bdesc(48 + S.value)); });
    wgmma_commit();
    send(slc(5), &tmo32, colB, row0);
    wgmma_fence();
    static_for<7, 16>([&](auto S) { wgmma128<1, 8>(lo0, ldesc(S.value), bdesc(48 + S.value)); });
    wgmma_commit();
    bar_arrive(3 + wg);
    RT(4);
    {
        const uint32_t zero = opq(gridDim.x - 2);
#pragma unroll
        for (int j = 0; j < 4; j++) { fa[j].x ^= zero; fa[j].y ^= zero; fa[j].z ^= zero; fa[j].w ^= zero; asm volatile("" : "+r"(fa[j].x), "+r"(fa[j].y), "+r"(fa[j].z), "+r"(fa[j].w)); }
    }
    if (elect()) { mbar_expect_tx(gbar, 4096); bulk_wait_read<0>(); load_s(13, 4, gbar); load_s(14, 5, gbar); }
    __syncwarp();
    wgmma_wait<0>();
    RT(5);
    stage_cols<64, 0>(lo0, slc(2));
    if (elect()) { mbar_expect_tx(gbar + 8, 2048); load_s(15, 0, gbar + 8); }
    __syncwarp();
    const bool okg = mbar_try(gbar, 0);
    send(slc(2), &tmo64, colL, row0);
    stage_cols<64, 32>(lo0, slc(3));
    mbar_wait1(gbar, 0, okg);
    if (NF > 1 && FAT == 0) get_frag(1, slc(4));
    RT(6);
    constexpr int NF2 = FAT == 0 ? NF : 1;
    auto ord2 = [](int i) { return MIX && i < 8 * NF2 ? ((i & 1) ? 4 * NF2 + (i >> 1) : i >> 1) : i; };
    auto ord3 = [](int i) { return MIX == 2 ? ((i % (4 / NF)) == 0 ? i / (4 / NF) : 4 * NF + i - i / (4 / NF) - 1) : MIX && i < 8 * NF ? ((i & 1) ? 4 * NF + (i >> 1) : i >> 1) : i; };
    auto mma2 = [&](auto I) { constexpr int s = ord2(I.value); if constexpr (s < 4 * NF2) wgmma128r<8>(lo1, fa[s], bdesc(48 + s)); else wgmma128<1, 8>(lo1, gdesc(s), bdesc(48 + s)); };
    auto mma3 = [&](auto I) { constexpr int s = ord3(I.value); if constexpr (s < 4 * NF) wgmma96r<8>(hi1, fa[s], bdesc(48 + s) + 128); else wgmma96<1, 8>(hi1, gdesc(s), bdesc(48 + s) + 128); };
    bar_sync(4 + wg);
    RT(7);
    wgmma_fence();
    static_for<0, 8>(mma2);
    wgmma_commit();
    const bool okg2 = mbar_try(gbar + 8, 0);
    send(slc(3), &tmo64, colL + 64, row0);
    mbar_wait1(gbar + 8, 0, okg2);
    wgmma_fence();
    static_for<8, 16>(mma2);
    wgmma_commit();
    bar_arrive(5 + wg);
    RT(8);
    if (NF > 1 && FAT == 1) get_frag(1, slc(4));
    if (NF > 2) get_frag(2, slc(5));
    if (NF > 3) get_frag(3, slc(0));
    if (elect()) bulk_wait_read<1>();
    __syncwarp();
    wgmma_wait<0>();
    RT(9);
    stage_cols<64, 0>(lo1, slc(1)); send(slc(1), &tmo64, colL, row0 + 64);
    stage_cols<64, 32>(lo1, slc(2));
    if (E2) send(slc(2), &tmo64, colL + 64, row0 + 64);
    RT(10);
    bar_sync(6 + wg);
    RT(11);
    wgmma_fence();
    static_for<0, GG3>(mma3);
    wgmma_commit();
    if (!E2) send(slc(2), &tmo64, colL + 64, row0 + 64);
    wgmma_fence();
    static_for<GG3, 16>(mma3);
    wgmma_commit();
    if (wg == 0) bar_arrive(7);
    RT(12);
    wgmma_wait<0>();
    RT(13);
    if (LASTO) { stage_cols<32, 32>(hi1, slc(5)); send(slc(5), &tmo32, colB, row0 + 64); }
    stage_cols<64, 0>(hi1, slc(4)); send(slc(4), &tmo64, colA, row0 + 64);
    if (!LASTO) { stage_cols<32, 32>(hi1, slc(5)); send(slc(5), &tmo32, colB, row0 + 64); }
    RT(14);
    if (elect()) bulk_wait_read<0>();
    __syncwarp();
    RT(15);
    TSW(wg * 4, 38 + wg);
    TS_DUMP();
    TL_DUMP();
    if (NG == 1) cluster_wait();
}

typedef CUresult (*EncodeFn)(CUtensorMap*, CUtensorMapDataType, cuuint32_t, void*, const cuuint64_t*, const cuuint64_t*,
                             const cuuint32_t*, const cuuint32_t*, CUtensorMapInterleave, CUtensorMapSwizzle,
                             CUtensorMapL2promotion, CUtensorMapFloatOOBfill);

extern "C" void kernel_launch(void* const* d_in, const int* in_sizes, int n_in, void* d_out, int out_size) {
    const __nv_bfloat16* x = (const __nv_bfloat16*)d_in[0];
    const int* qw = (const int*)d_in[1];
    const __nv_bfloat16* cb = (const __nv_bfloat16*)d_in[2];
    const __nv_bfloat16* absmax = (const __nv_bfloat16*)d_in[3];
    static EncodeFn encode = nullptr;
    static void *wimg = nullptr, *gflag = nullptr;
    if (!encode) {
        cudaGetSymbolAddress(&wimg, g_wimg);
        cudaGetSymbolAddress(&gflag, g_flag);
        void* fn = nullptr;
        cudaDriverEntryPointQueryResult qr;
        cudaGetDriverEntryPoint("cuTensorMapEncodeTiled", &fn, cudaEnableDefault, &qr);
        encode = (EncodeFn)fn;
        cudaFuncSetAttribute(nf4_gemm_kernel, cudaFuncAttributeMaxDynamicSharedMemorySize, SMEM_BYTES);
    }
    CUtensorMap tmx, tmq, tmo64, tmo32, tmqp, tmx16, tmx64, tmq1;
    {
        cuuint64_t dims[2] = {(cuuint64_t)K_, (cuuint64_t)M_};
        cuuint64_t strides[1] = {(cuuint64_t)K_ * 2};
        cuuint32_t box[2] = {64, 128};
        cuuint32_t es[2] = {1, 1};
        encode(&tmx, CU_TENSOR_MAP_DATA_TYPE_BFLOAT16, 2, (void*)x, dims, strides, box, es, CU_TENSOR_MAP_INTERLEAVE_NONE,
               CU_TENSOR_MAP_SWIZZLE_128B, CU_TENSOR_MAP_L2_PROMOTION_L2_128B, CU_TENSOR_MAP_FLOAT_OOB_FILL_NONE);
        box[1] = 64;
        encode(&tmx64, CU_TENSOR_MAP_DATA_TYPE_BFLOAT16, 2, (void*)x, dims, strides, box, es, CU_TENSOR_MAP_INTERLEAVE_NONE,
               CU_TENSOR_MAP_SWIZZLE_128B, CU_TENSOR_MAP_L2_PROMOTION_L2_128B, CU_TENSOR_MAP_FLOAT_OOB_FILL_NONE);
        box[1] = 16;
        encode(&tmx16, CU_TENSOR_MAP_DATA_TYPE_BFLOAT16, 2, (void*)x, dims, strides, box, es, CU_TENSOR_MAP_INTERLEAVE_NONE,
               CU_TENSOR_MAP_SWIZZLE_128B, CU_TENSOR_MAP_L2_PROMOTION_L2_128B, CU_TENSOR_MAP_FLOAT_OOB_FILL_NONE);
    }
    {
        cuuint64_t dims[5] = {32, 8, (cuuint64_t)(N_ / 32), 2, (cuuint64_t)(K_ / 16)};
        cuuint64_t strides[4] = {(cuuint64_t)N_ * 4, 128, (cuuint64_t)N_ * 4 * 8, (cuuint64_t)N_ * 4 * 16};
        cuuint32_t box[5] = {32, 8, 7, 1, 2};
        cuuint32_t es[5] = {1, 1, 1, 1, 1};
        encode(&tmq, CU_TENSOR_MAP_DATA_TYPE_INT32, 5, (void*)qw, dims, strides, box, es, CU_TENSOR_MAP_INTERLEAVE_NONE,
               CU_TENSOR_MAP_SWIZZLE_128B, CU_TENSOR_MAP_L2_PROMOTION_L2_128B, CU_TENSOR_MAP_FLOAT_OOB_FILL_NONE);
        box[4] = 1;
        encode(&tmq1, CU_TENSOR_MAP_DATA_TYPE_INT32, 5, (void*)qw, dims, strides, box, es, CU_TENSOR_MAP_INTERLEAVE_NONE,
               CU_TENSOR_MAP_SWIZZLE_128B, CU_TENSOR_MAP_L2_PROMOTION_L2_128B, CU_TENSOR_MAP_FLOAT_OOB_FILL_NONE);
        cuuint64_t dims2[2] = {(cuuint64_t)N_, (cuuint64_t)K_};
        cuuint32_t box2[2] = {224, 8};
        encode(&tmqp, CU_TENSOR_MAP_DATA_TYPE_INT32, 2, (void*)qw, dims2, strides, box2, es, CU_TENSOR_MAP_INTERLEAVE_NONE,
               CU_TENSOR_MAP_SWIZZLE_NONE, CU_TENSOR_MAP_L2_PROMOTION_L2_128B, CU_TENSOR_MAP_FLOAT_OOB_FILL_NONE);
    }
    {
        cuuint64_t dims[2] = {(cuuint64_t)N_, (cuuint64_t)M_};
        cuuint64_t strides[1] = {(cuuint64_t)N_ * 2};
        cuuint32_t box[2] = {64, 16};
        cuuint32_t es[2] = {1, 1};
        encode(&tmo64, CU_TENSOR_MAP_DATA_TYPE_BFLOAT16, 2, d_out, dims, strides, box, es, CU_TENSOR_MAP_INTERLEAVE_NONE,
               CU_TENSOR_MAP_SWIZZLE_128B, CU_TENSOR_MAP_L2_PROMOTION_NONE, CU_TENSOR_MAP_FLOAT_OOB_FILL_NONE);
        box[0] = 32;
        encode(&tmo32, CU_TENSOR_MAP_DATA_TYPE_BFLOAT16, 2, d_out, dims, strides, box, es, CU_TENSOR_MAP_INTERLEAVE_NONE,
               CU_TENSOR_MAP_SWIZZLE_64B, CU_TENSOR_MAP_L2_PROMOTION_NONE, CU_TENSOR_MAP_FLOAT_OOB_FILL_NONE);
    }
    nf4_gemm_kernel<<<dim3(2, 16, 4), 256, SMEM_BYTES>>>(qw, cb, absmax, (uint8_t*)wimg, (unsigned*)gflag, tmx, tmq, tmo64, tmo32, tmqp, tmx16, tmx64, tmq1);
}
```

```cpp
#include <cuda_runtime.h>
#include <cuda_bf16.h>
#include <cuda.h>
#include <stdint.h>

#define NG 2
#define G1 6
#define G2 8
#define PFG 1
#define NF 2
#define FAT 1
#define MIX 0
#define GG3 6
#define LASTO 0
#define E2 0
#define PF12 0
#define FS 38
#define SPLIT 1
#define RAWFIRST 1
#define SHE 0
#define SN0 32
#define CK0 36
#define PUB 1
#define T2 900
#define T2B 1300
#define T3 1700
#define TLPRO -2
#define TLIT 2
constexpr int M_ = 2048, K_ = 1024, N_ = 3584;
constexpr int BM = 256, BN = 224;
constexpr int UNIT = 14336;
constexpr int NW = 6, NR = 3;
constexpr int NU = 32 - 6 * NG;
constexpr int NC = 16 - 4 * NG;
constexpr int CE = NU / 2 - 2;
#define PFQ 4
constexpr int PFX = 3;
constexpr int RAW_OFF = 3 * 32768;
constexpr int SC_OFF = RAW_OFF + 2 * UNIT;
constexpr int SC_STRIDE = 464;
constexpr int W_OFF = 127 * 1024;
constexpr int RAW2_OFF = W_OFF + NW * UNIT;
constexpr int BAR_OFF = RAW2_OFF + UNIT;
constexpr int SMEM_BYTES = BAR_OFF + 320;
__device__ __align__(1024) uint8_t g_wimg[16 * 8 * NG * UNIT];
__device__ __align__(128) unsigned g_flag[16 * 32];

#define TSL(i)
#define TL_DUMP()
#define TSW(w, i)
#define TS_INIT()
#define TS_DUMP()
#define RT(i)

__device__ __forceinline__ uint32_t smem_u32(const void* p) { return (uint32_t)__cvta_generic_to_shared(p); }
__device__ __forceinline__ bool elect() {
    uint32_t ok;
    asm volatile("{\n.reg .pred p;\nelect.sync _|p, 0xffffffff;\nselp.u32 %0, 1, 0, p;\n}\n" : "=r"(ok));
    return ok != 0;
}
__device__ __forceinline__ void mbar_init(uint32_t bar, uint32_t cnt) { asm volatile("mbarrier.init.shared::cta.b64 [%0], %1;" ::"r"(bar), "r"(cnt) : "memory"); }
__device__ __forceinline__ void mbar_expect_tx(uint32_t bar, uint32_t bytes) { asm volatile("mbarrier.arrive.expect_tx.shared::cta.b64 _, [%0], %1;" ::"r"(bar), "r"(bytes) : "memory"); }
__device__ __forceinline__ void mbar_arrive(uint32_t bar) { asm volatile("mbarrier.arrive.shared::cta.b64 _, [%0];" ::"r"(bar) : "memory"); }
#define BOUNDED
#define WAIT_INIT "mov.u32 n, 0;\n"
#define WAIT_NEXT "@p bra.uni LAB_DONE;\nadd.u32 n, n, 1;\nsetp.lt.u32 p, n, 0x4000;\n@p bra.uni LAB_WAIT;\n"
__device__ __forceinline__ void mbar_wait(uint32_t bar, uint32_t parity) {
    asm volatile(
        "{\n.reg .pred p;\n.reg .u32 n;\n"
        WAIT_INIT
        "LAB_WAIT:\n"
        "mbarrier.try_wait.parity.shared::cta.b64 p, [%0], %1;\n"
        WAIT_NEXT
        "LAB_DONE:\n}\n" ::"r"(bar), "r"(parity) : "memory");
}
__device__ __forceinline__ bool mbar_try(uint32_t bar, uint32_t parity) {
    uint32_t ok;
    asm volatile("{\n.reg .pred p;\nmbarrier.test_wait.parity.shared::cta.b64 p, [%1], %2;\nselp.u32 %0, 1, 0, p;\n}\n" : "=r"(ok) : "r"(bar), "r"(parity) : "memory");
    return ok != 0;
}
__device__ __forceinline__ void mbar_wait1(uint32_t b0, uint32_t p0, bool skip) {
    asm volatile(
        "{\n.reg .pred p;\n.reg .u32 n;\n"
        "setp.ne.u32 p, %2, 0;\n@p bra.uni LAB_DONE;\n"
        WAIT_INIT
        "LAB_WAIT:\n"
        "mbarrier.try_wait.parity.shared::cta.b64 p, [%0], %1;\n"
        WAIT_NEXT
        "LAB_DONE:\n}\n" ::"r"(b0), "r"(p0), "r"((uint32_t)skip) : "memory");
}
__device__ __forceinline__ void mbar_wait2(uint32_t b0, uint32_t p0, uint32_t b1, uint32_t p1, bool skip = false) {
    asm volatile(
        "{\n.reg .pred p, q;\n.reg .u32 n;\n"
        "setp.ne.u32 p, %4, 0;\n@p bra.uni LAB_DONE;\n"
        WAIT_INIT
        "LAB_WAIT:\n"
        "mbarrier.try_wait.parity.shared::cta.b64 p, [%0], %1;\n"
        "mbarrier.try_wait.parity.shared::cta.b64 q, [%2], %3;\n"
        "and.pred p, p, q;\n"
        WAIT_NEXT
        "LAB_DONE:\n}\n" ::"r"(b0), "r"(p0), "r"(b1), "r"(p1), "r"((uint32_t)skip) : "memory");
}
__device__ __forceinline__ void tma_load_2d(uint32_t dst, const CUtensorMap* tm, int c0, int c1, uint32_t bar) {
    asm volatile("cp.async.bulk.tensor.2d.shared::cluster.global.mbarrier::complete_tx::bytes [%0], [%1, {%2, %3}], [%4];"
                 ::"r"(dst), "l"(tm), "r"(c0), "r"(c1), "r"(bar) : "memory");
}
__device__ __forceinline__ void tma_load_5d(uint32_t dst, const CUtensorMap* tm, int c0, int c1, int c2, int c3, int c4, uint32_t bar) {
    asm volatile("cp.async.bulk.tensor.5d.shared::cluster.global.mbarrier::complete_tx::bytes [%0], [%1, {%2, %3, %4, %5, %6}], [%7];"
                 ::"r"(dst), "l"(tm), "r"(c0), "r"(c1), "r"(c2), "r"(c3), "r"(c4), "r"(bar) : "memory");
}
__device__ __forceinline__ void tma_prefetch_2d(const CUtensorMap* tm, int c0, int c1) {
    asm volatile("cp.async.bulk.prefetch.tensor.2d.L2.global [%0, {%1, %2}];" ::"l"(tm), "r"(c0), "r"(c1) : "memory");
}
__device__ __forceinline__ void bulk_load(uint32_t dst, const void* src, uint32_t bytes, uint32_t bar) {
    asm volatile("cp.async.bulk.shared::cluster.global.mbarrier::complete_tx::bytes [%0], [%1], %2, [%3];"
                 ::"r"(dst), "l"(src), "r"(bytes), "r"(bar) : "memory");
}
__device__ __forceinline__ void cluster_arrive() { asm volatile("barrier.cluster.arrive.relaxed.aligned;" ::: "memory"); }
__device__ __forceinline__ void cluster_wait() { asm volatile("barrier.cluster.wait.acquire.aligned;" ::: "memory"); }
__device__ __forceinline__ uint32_t mapa(uint32_t addr, uint32_t cta) {
    uint32_t r; asm("mapa.shared::cluster.u32 %0, %1, %2;" : "=r"(r) : "r"(addr), "r"(cta)); return r;
}
__device__ __forceinline__ void copy_to_peer(uint32_t cdst, uint32_t src, uint32_t bytes, uint32_t cbar) {
    asm volatile("cp.async.bulk.shared::cluster.shared::cta.mbarrier::complete_tx::bytes [%0], [%1], %2, [%3];"
                 ::"r"(cdst), "r"(src), "r"(bytes), "r"(cbar) : "memory");
}
__device__ __forceinline__ void wgmma_fence() { asm volatile("wgmma.fence.sync.aligned;" ::: "memory"); }
__device__ __forceinline__ void wgmma_commit() { asm volatile("wgmma.commit_group.sync.aligned;" ::: "memory"); }
template <int N> __device__ __forceinline__ void wgmma_wait() { asm volatile("wgmma.wait_group.sync.aligned %0;" ::"n"(N) : "memory"); }
__device__ __forceinline__ uint32_t pack_bf16(float lo, float hi) {
    uint32_t r; asm("cvt.rn.bf16x2.f32 %0, %1, %2;" : "=r"(r) : "f"(hi), "f"(lo)); return r;
}
__device__ __forceinline__ void stmatrix_x4(uint32_t addr, uint32_t a, uint32_t b, uint32_t c, uint32_t d) {
    asm volatile("stmatrix.sync.aligned.m8n8.x4.shared.b16 [%0], {%1, %2, %3, %4};" ::"r"(addr), "r"(a), "r"(b), "r"(c), "r"(d) : "memory");
}
__device__ __forceinline__ uint4 ldmatrix_x4(uint32_t a) {
    uint4 v; asm volatile("ldmatrix.sync.aligned.m8n8.x4.shared.b16 {%0, %1, %2, %3}, [%4];" : "=r"(v.x), "=r"(v.y), "=r"(v.z), "=r"(v.w) : "r"(a) : "memory"); return v;
}
__device__ __forceinline__ uint4 lds128(uint32_t a) {
    uint4 v; asm volatile("ld.shared.v4.b32 {%0, %1, %2, %3}, [%4];" : "=r"(v.x), "=r"(v.y), "=r"(v.z), "=r"(v.w) : "r"(a) : "memory"); return v;
}
__device__ __forceinline__ void sts128(uint32_t a, uint4 v) {
    asm volatile("st.shared.v4.b32 [%0], {%1, %2, %3, %4};" ::"r"(a), "r"(v.x), "r"(v.y), "r"(v.z), "r"(v.w) : "memory");
}
__device__ __forceinline__ uint4 ldg128(const void* p) {
    uint4 v; asm volatile("ld.global.nc.v4.b32 {%0, %1, %2, %3}, [%4];" : "=r"(v.x), "=r"(v.y), "=r"(v.z), "=r"(v.w) : "l"(p) : "memory"); return v;
}
__device__ __forceinline__ unsigned clk() { unsigned c; asm volatile("mov.u32 %0, %%clock;" : "=r"(c) :: "memory"); return c; }
__device__ __forceinline__ uint32_t mul_bf16x2(uint32_t a, uint32_t b) { uint32_t r; asm("mul.rn.bf16x2 %0, %1, %2;" : "=r"(r) : "r"(a), "r"(b)); return r; }
struct Lut { uint32_t lo[4], hi[4]; };
__device__ __forceinline__ uint32_t prmt(uint32_t a, uint32_t b, uint32_t s) { uint32_t r; asm("prmt.b32 %0, %1, %2, %3;" : "=r"(r) : "r"(a), "r"(b), "r"(s)); return r; }
__device__ __forceinline__ uint32_t pack4(const uint4& q) {
    uint32_t ab, cd, p;
    asm volatile("mad.lo.u32 %0, %1, 16, %2;" : "=r"(ab) : "r"(q.y), "r"(q.x));
    asm volatile("mad.lo.u32 %0, %1, 16, %2;" : "=r"(cd) : "r"(q.w), "r"(q.z));
    asm volatile("mad.lo.u32 %0, %1, 256, %2;" : "=r"(p) : "r"(cd), "r"(ab));
    return p;
}
__device__ __forceinline__ void lookup4(uint32_t p, const Lut& t, uint32_t& w01, uint32_t& w23) {
    const uint32_t t8 = p & 0x8888u, s7 = p & 0x7777u;
    const uint32_t sel = (t8 >> 1) + 0x3210u;
    const uint32_t lo = prmt(prmt(t.lo[0], t.lo[1], p), prmt(t.lo[2], t.lo[3], s7), sel);
    const uint32_t hi = prmt(prmt(t.hi[0], t.hi[1], p), prmt(t.hi[2], t.hi[3], s7), sel);
    w01 = prmt(lo, hi, 0x5140);
    w23 = prmt(lo, hi, 0x7362);
}
__device__ __forceinline__ uint4 dequant8(uint32_t p0, uint32_t p1, const uint4& sc, const Lut& t) {
    uint4 r;
    lookup4(p0, t, r.x, r.y);
    lookup4(p1, t, r.z, r.w);
    r.x = mul_bf16x2(r.x, sc.x); r.y = mul_bf16x2(r.y, sc.y); r.z = mul_bf16x2(r.z, sc.z); r.w = mul_bf16x2(r.w, sc.w);
    return r;
}
__device__ __forceinline__ void fence_async_smem() { asm volatile("fence.proxy.async.shared::cta;" ::: "memory"); }

template <int SCALE_D, int BHI, uint32_t AHI = 0x40000040u>
__device__ __forceinline__ void wgmma224(float (&d)[112], uint32_t descA, uint32_t descB) {
    asm volatile(
        "{\n.reg .pred p;\n.reg .b64 da, db;\nsetp.ne.b32 p, %114, 0;\n"
        "mov.b64 da, {%112, %116};\nmov.b64 db, {%113, %115};\n"
        "wgmma.mma_async.sync.aligned.m64n224k16.f32.bf16.bf16 "
        "{%0, %1, %2, %3, %4, %5, %6, %7, %8, %9, %10, %11, %12, %13, %14, %15, "
        "%16, %17, %18, %19, %20, %21, %22, %23, %24, %25, %26, %27, %28, %29, %30, %31, "
        "%32, %33, %34, %35, %36, %37, %38, %39, %40, %41, %42, %43, %44, %45, %46, %47, "
        "%48, %49, %50, %51, %52, %53, %54, %55, %56, %57, %58, %59, %60, %61, %62, %63, "
        "%64, %65, %66, %67, %68, %69, %70, %71, %72, %73, %74, %75, %76, %77, %78, %79, "
        "%80, %81, %82, %83, %84, %85, %86, %87, %88, %89, %90, %91, %92, %93, %94, %95, "
        "%96, %97, %98, %99, %100, %101, %102, %103, %104, %105, %106, %107, %108, %109, %110, %111}, "
        "da, db, p, 1, 1, 0, 1;\n}\n"
        : "+f"(d[0]), "+f"(d[1]), "+f"(d[2]), "+f"(d[3]), "+f"(d[4]), "+f"(d[5]), "+f"(d[6]), "+f"(d[7]),
          "+f"(d[8]), "+f"(d[9]), "+f"(d[10]), "+f"(d[11]), "+f"(d[12]), "+f"(d[13]), "+f"(d[14]), "+f"(d[15]),
          "+f"(d[16]), "+f"(d[17]), "+f"(d[18]), "+f"(d[19]), "+f"(d[20]), "+f"(d[21]), "+f"(d[22]), "+f"(d[23]),
          "+f"(d[24]), "+f"(d[25]), "+f"(d[26]), "+f"(d[27]), "+f"(d[28]), "+f"(d[29]), "+f"(d[30]), "+f"(d[31]),
          "+f"(d[32]), "+f"(d[33]), "+f"(d[34]), "+f"(d[35]), "+f"(d[36]), "+f"(d[37]), "+f"(d[38]), "+f"(d[39]),
          "+f"(d[40]), "+f"(d[41]), "+f"(d[42]), "+f"(d[43]), "+f"(d[44]), "+f"(d[45]), "+f"(d[46]), "+f"(d[47]),
          "+f"(d[48]), "+f"(d[49]), "+f"(d[50]), "+f"(d[51]), "+f"(d[52]), "+f"(d[53]), "+f"(d[54]), "+f"(d[55]),
          "+f"(d[56]), "+f"(d[57]), "+f"(d[58]), "+f"(d[59]), "+f"(d[60]), "+f"(d[61]), "+f"(d[62]), "+f"(d[63]),
          "+f"(d[64]), "+f"(d[65]), "+f"(d[66]), "+f"(d[67]), "+f"(d[68]), "+f"(d[69]), "+f"(d[70]), "+f"(d[71]),
          "+f"(d[72]), "+f"(d[73]), "+f"(d[74]), "+f"(d[75]), "+f"(d[76]), "+f"(d[77]), "+f"(d[78]), "+f"(d[79]),
          "+f"(d[80]), "+f"(d[81]), "+f"(d[82]), "+f"(d[83]), "+f"(d[84]), "+f"(d[85]), "+f"(d[86]), "+f"(d[87]),
          "+f"(d[88]), "+f"(d[89]), "+f"(d[90]), "+f"(d[91]), "+f"(d[92]), "+f"(d[93]), "+f"(d[94]), "+f"(d[95]),
          "+f"(d[96]), "+f"(d[97]), "+f"(d[98]), "+f"(d[99]), "+f"(d[100]), "+f"(d[101]), "+f"(d[102]), "+f"(d[103]),
          "+f"(d[104]), "+f"(d[105]), "+f"(d[106]), "+f"(d[107]), "+f"(d[108]), "+f"(d[109]), "+f"(d[110]), "+f"(d[111])
        : "r"(descA), "r"(descB), "n"(SCALE_D), "n"(BHI), "n"(AHI));
}

template <int SCALE_D, int BHI, uint32_t AHI = 0x40000040u>
__device__ __forceinline__ void wgmma128(float (&d)[64], uint32_t descA, uint32_t descB) {
    asm volatile(
        "{\n.reg .pred p;\n.reg .b64 da, db;\nsetp.ne.b32 p, %66, 0;\n"
        "mov.b64 da, {%64, %68};\nmov.b64 db, {%65, %67};\n"
        "wgmma.mma_async.sync.aligned.m64n128k16.f32.bf16.bf16 "
        "{%0, %1, %2, %3, %4, %5, %6, %7, %8, %9, %10, %11, %12, %13, %14, %15, "
        "%16, %17, %18, %19, %20, %21, %22, %23, %24, %25, %26, %27, %28, %29, %30, %31, "
        "%32, %33, %34, %35, %36, %37, %38, %39, %40, %41, %42, %43, %44, %45, %46, %47, "
        "%48, %49, %50, %51, %52, %53, %54, %55, %56, %57, %58, %59, %60, %61, %62, %63}, "
        "da, db, p, 1, 1, 0, 1;\n}\n"
        : "+f"(d[0]), "+f"(d[1]), "+f"(d[2]), "+f"(d[3]), "+f"(d[4]), "+f"(d[5]), "+f"(d[6]), "+f"(d[7]),
          "+f"(d[8]), "+f"(d[9]), "+f"(d[10]), "+f"(d[11]), "+f"(d[12]), "+f"(d[13]), "+f"(d[14]), "+f"(d[15]),
          "+f"(d[16]), "+f"(d[17]), "+f"(d[18]), "+f"(d[19]), "+f"(d[20]), "+f"(d[21]), "+f"(d[22]), "+f"(d[23]),
          "+f"(d[24]), "+f"(d[25]), "+f"(d[26]), "+f"(d[27]), "+f"(d[28]), "+f"(d[29]), "+f"(d[30]), "+f"(d[31]),
          "+f"(d[32]), "+f"(d[33]), "+f"(d[34]), "+f"(d[35]), "+f"(d[36]), "+f"(d[37]), "+f"(d[38]), "+f"(d[39]),
          "+f"(d[40]), "+f"(d[41]), "+f"(d[42]), "+f"(d[43]), "+f"(d[44]), "+f"(d[45]), "+f"(d[46]), "+f"(d[47]),
          "+f"(d[48]), "+f"(d[49]), "+f"(d[50]), "+f"(d[51]), "+f"(d[52]), "+f"(d[53]), "+f"(d[54]), "+f"(d[55]),
          "+f"(d[56]), "+f"(d[57]), "+f"(d[58]), "+f"(d[59]), "+f"(d[60]), "+f"(d[61]), "+f"(d[62]), "+f"(d[63])
        : "r"(descA), "r"(descB), "n"(SCALE_D), "n"(BHI), "n"(AHI));
}

template <int SCALE_D, int BHI, uint32_t AHI = 0x40000040u>
__device__ __forceinline__ void wgmma96(float (&d)[48], uint32_t descA, uint32_t descB) {
    asm volatile(
        "{\n.reg .pred p;\n.reg .b64 da, db;\nsetp.ne.b32 p, %50, 0;\n"
        "mov.b64 da, {%48, %52};\nmov.b64 db, {%49, %51};\n"
        "wgmma.mma_async.sync.aligned.m64n96k16.f32.bf16.bf16 "
        "{%0, %1, %2, %3, %4, %5, %6, %7, %8, %9, %10, %11, %12, %13, %14, %15, "
        "%16, %17, %18, %19, %20, %21, %22, %23, %24, %25, %26, %27, %28, %29, %30, %31, "
        "%32, %33, %34, %35, %36, %37, %38, %39, %40, %41, %42, %43, %44, %45, %46, %47}, "
        "da, db, p, 1, 1, 0, 1;\n}\n"
        : "+f"(d[0]), "+f"(d[1]), "+f"(d[2]), "+f"(d[3]), "+f"(d[4]), "+f"(d[5]), "+f"(d[6]), "+f"(d[7]),
          "+f"(d[8]), "+f"(d[9]), "+f"(d[10]), "+f"(d[11]), "+f"(d[12]), "+f"(d[13]), "+f"(d[14]), "+f"(d[15]),
          "+f"(d[16]), "+f"(d[17]), "+f"(d[18]), "+f"(d[19]), "+f"(d[20]), "+f"(d[21]), "+f"(d[22]), "+f"(d[23]),
          "+f"(d[24]), "+f"(d[25]), "+f"(d[26]), "+f"(d[27]), "+f"(d[28]), "+f"(d[29]), "+f"(d[30]), "+f"(d[31]),
          "+f"(d[32]), "+f"(d[33]), "+f"(d[34]), "+f"(d[35]), "+f"(d[36]), "+f"(d[37]), "+f"(d[38]), "+f"(d[39]),
          "+f"(d[40]), "+f"(d[41]), "+f"(d[42]), "+f"(d[43]), "+f"(d[44]), "+f"(d[45]), "+f"(d[46]), "+f"(d[47])
        : "r"(descA), "r"(descB), "n"(SCALE_D), "n"(BHI), "n"(AHI));
}

template <int BHI>
__device__ __forceinline__ void wgmma128r(float (&d)[64], const uint4& a, uint32_t descB) {
    asm volatile(
        "{\n.reg .pred p;\n.reg .b64 db;\nsetp.eq.b32 p, 0, 0;\n"
        "mov.b64 db, {%68, %69};\n"
        "wgmma.mma_async.sync.aligned.m64n128k16.f32.bf16.bf16 "
        "{%0, %1, %2, %3, %4, %5, %6, %7, %8, %9, %10, %11, %12, %13, %14, %15, "
        "%16, %17, %18, %19, %20, %21, %22, %23, %24, %25, %26, %27, %28, %29, %30, %31, "
        "%32, %33, %34, %35, %36, %37, %38, %39, %40, %41, %42, %43, %44, %45, %46, %47, "
        "%48, %49, %50, %51, %52, %53, %54, %55, %56, %57, %58, %59, %60, %61, %62, %63}, "
        "{%64, %65, %66, %67}, db, p, 1, 1, 1;\n}\n"
        : "+f"(d[0]), "+f"(d[1]), "+f"(d[2]), "+f"(d[3]), "+f"(d[4]), "+f"(d[5]), "+f"(d[6]), "+f"(d[7]),
          "+f"(d[8]), "+f"(d[9]), "+f"(d[10]), "+f"(d[11]), "+f"(d[12]), "+f"(d[13]), "+f"(d[14]), "+f"(d[15]),
          "+f"(d[16]), "+f"(d[17]), "+f"(d[18]), "+f"(d[19]), "+f"(d[20]), "+f"(d[21]), "+f"(d[22]), "+f"(d[23]),
          "+f"(d[24]), "+f"(d[25]), "+f"(d[26]), "+f"(d[27]), "+f"(d[28]), "+f"(d[29]), "+f"(d[30]), "+f"(d[31]),
          "+f"(d[32]), "+f"(d[33]), "+f"(d[34]), "+f"(d[35]), "+f"(d[36]), "+f"(d[37]), "+f"(d[38]), "+f"(d[39]),
          "+f"(d[40]), "+f"(d[41]), "+f"(d[42]), "+f"(d[43]), "+f"(d[44]), "+f"(d[45]), "+f"(d[46]), "+f"(d[47]),
          "+f"(d[48]), "+f"(d[49]), "+f"(d[50]), "+f"(d[51]), "+f"(d[52]), "+f"(d[53]), "+f"(d[54]), "+f"(d[55]),
          "+f"(d[56]), "+f"(d[57]), "+f"(d[58]), "+f"(d[59]), "+f"(d[60]), "+f"(d[61]), "+f"(d[62]), "+f"(d[63])
        : "r"(a.x), "r"(a.y), "r"(a.z), "r"(a.w), "r"(descB), "n"(BHI));
}

template <int BHI>
__device__ __forceinline__ void wgmma96r(float (&d)[48], const uint4& a, uint32_t descB) {
    asm volatile(
        "{\n.reg .pred p;\n.reg .b64 db;\nsetp.eq.b32 p, 0, 0;\n"
        "mov.b64 db, {%52, %53};\n"
        "wgmma.mma_async.sync.aligned.m64n96k16.f32.bf16.bf16 "
        "{%0, %1, %2, %3, %4, %5, %6, %7, %8, %9, %10, %11, %12, %13, %14, %15, "
        "%16, %17, %18, %19, %20, %21, %22, %23, %24, %25, %26, %27, %28, %29, %30, %31, "
        "%32, %33, %34, %35, %36, %37, %38, %39, %40, %41, %42, %43, %44, %45, %46, %47}, "
        "{%48, %49, %50, %51}, db, p, 1, 1, 1;\n}\n"
        : "+f"(d[0]), "+f"(d[1]), "+f"(d[2]), "+f"(d[3]), "+f"(d[4]), "+f"(d[5]), "+f"(d[6]), "+f"(d[7]),
          "+f"(d[8]), "+f"(d[9]), "+f"(d[10]), "+f"(d[11]), "+f"(d[12]), "+f"(d[13]), "+f"(d[14]), "+f"(d[15]),
          "+f"(d[16]), "+f"(d[17]), "+f"(d[18]), "+f"(d[19]), "+f"(d[20]), "+f"(d[21]), "+f"(d[22]), "+f"(d[23]),
          "+f"(d[24]), "+f"(d[25]), "+f"(d[26]), "+f"(d[27]), "+f"(d[28]), "+f"(d[29]), "+f"(d[30]), "+f"(d[31]),
          "+f"(d[32]), "+f"(d[33]), "+f"(d[34]), "+f"(d[35]), "+f"(d[36]), "+f"(d[37]), "+f"(d[38]), "+f"(d[39]),
          "+f"(d[40]), "+f"(d[41]), "+f"(d[42]), "+f"(d[43]), "+f"(d[44]), "+f"(d[45]), "+f"(d[46]), "+f"(d[47])
        : "r"(a.x), "r"(a.y), "r"(a.z), "r"(a.w), "r"(descB), "n"(BHI));
}

__device__ __forceinline__ uint32_t opq(uint32_t v) { asm volatile("" : "+r"(v)); return v; }
template <int I> struct IC { static constexpr int value = I; };
template <int B, int E, class F> __device__ __forceinline__ void static_for(F&& f) {
    if constexpr (B < E) { f(IC<B>{}); static_for<B + 1, E>(f); }
}

__device__ __forceinline__ void tma_store_2d(const CUtensorMap* tm, uint32_t src, int c0, int c1) {
    asm volatile("cp.async.bulk.tensor.2d.global.shared::cta.bulk_group [%0, {%2, %3}], [%1];" ::"l"(tm), "r"(src), "r"(c0), "r"(c1) : "memory");
}
__device__ __forceinline__ void bulk_store(void* dst, uint32_t src, uint32_t bytes) {
    asm volatile("cp.async.bulk.global.shared::cta.bulk_group [%0], [%1], %2;" ::"l"(dst), "r"(src), "r"(bytes) : "memory");
}
__device__ __forceinline__ void bulk_commit() { asm volatile("cp.async.bulk.commit_group;" ::: "memory"); }
template <int N> __device__ __forceinline__ void bulk_wait_read() { asm volatile("cp.async.bulk.wait_group.read %0;" ::"n"(N) : "memory"); }
__device__ __forceinline__ void bar_arrive(int id) { asm volatile("bar.arrive %0, 256;" ::"r"(id) : "memory"); }
__device__ __forceinline__ void bar_sync(int id) { asm volatile("bar.sync %0, 256;" ::"r"(id) : "memory"); }
template <int NC, int OFF, int N>
__device__ __forceinline__ void stage_cols(const float (&acc)[N], uint32_t stg) {
    int lane; asm volatile("mov.u32 %0, %%laneid;" : "=r"(lane));
    const int r = lane & 15;
    const uint32_t a0 = NC == 64 ? stg + r * 128 + (((lane >> 4) ^ (r & 7)) << 4) : stg + r * 64 + (((lane >> 4) ^ ((r >> 1) & 3)) << 4);
#pragma unroll
    for (int j = 0; j < NC / 16; j++) {
        const int i = OFF + 8 * j;
        stmatrix_x4(a0 ^ (j * 32), pack_bf16(acc[i], acc[i + 1]), pack_bf16(acc[i + 2], acc[i + 3]), pack_bf16(acc[i + 4], acc[i + 5]), pack_bf16(acc[i + 6], acc[i + 7]));
    }
}
__device__ __forceinline__ void send(uint32_t stg, const CUtensorMap* tmo, int col, int row) {
    fence_async_smem();
    __syncwarp();
    if (elect()) { tma_store_2d(tmo, stg, col, row); bulk_commit(); }
    __syncwarp();
}

__host__ __device__ constexpr int rslot(int u) { return (2 * u) % 3; }
__host__ __device__ constexpr int roff(int slot) { return slot < 2 ? slot * UNIT : RAW2_OFF - RAW_OFF; }
__host__ __device__ constexpr int rpar(int u) { return (u / 3 - (u % 3 == 0)) & 1; }
__host__ __device__ constexpr int sslot(int c) { return c < 3 ? c + 3 : c % 3; }
__host__ __device__ constexpr int vturn(int v) {
    return v < 20 ? v : v == 20 ? -21 : v == 21 ? -22 : v == 22 ? 21 : v == 23 ? -20 : v == 24 ? 20 : v < 29 ? v - 3 : v == 29 ? -24 : v == 30 ? -25 : 27;
}
__host__ __device__ constexpr int uoff(int v) { return vturn(v) < 0 ? RAW_OFF + roff(rslot(-vturn(v))) : W_OFF + (vturn(v) % NW) * UNIT; }
__host__ __device__ constexpr int ubar(int v) { return vturn(v) < 0 ? 96 + 8 * rslot(-vturn(v)) : 16 * (vturn(v) % NW); }
__host__ __device__ constexpr int upar(int v) { return vturn(v) < 0 ? rpar(-vturn(v)) : (vturn(v) / NW) & 1; }
__host__ __device__ constexpr int utime(int v) {
    return v < 22 ? CK0 : v == 22 || v == 25 ? 38 : v < 25 ? 40 : v < 28 ? 42 : v == 28 ? 44 : 2 * v - 14;
}
__host__ __device__ constexpr uint32_t bdesc(int s) { return (uint32_t)(((0x400 + uoff(s >> 1)) >> 4) | ((7168u >> 4) << 16)) + (s & 1) * 224; }

__global__ void __cluster_dims__(2, 1, 1) __launch_bounds__(256, 1)
nf4_gemm_kernel(const int* __restrict__ qw, const __nv_bfloat16* __restrict__ cb, const __nv_bfloat16* __restrict__ absmax,
                uint8_t* __restrict__ wimg, unsigned* __restrict__ gflag,
                const __grid_constant__ CUtensorMap tmx, const __grid_constant__ CUtensorMap tmq, const __grid_constant__ CUtensorMap tmo64,
                const __grid_constant__ CUtensorMap tmo32, const __grid_constant__ CUtensorMap tmqp, const __grid_constant__ CUtensorMap tmx16,
                const __grid_constant__ CUtensorMap tmx64, const __grid_constant__ CUtensorMap tmq1) {
    extern __shared__ __align__(1024) uint8_t smem[];
    const uint32_t sbase = smem_u32(smem);
    const int rank = blockIdx.x, nt = blockIdx.y, pair = blockIdx.z;
    uint4 q[4], c0, c1;
    uint2 sf;
    if (threadIdx.x < 224) {
        const uint32_t t = threadIdx.x;
        const int* p = qw + (uint32_t)((t & 3) * (N_ - 1) + t + blockIdx.x * (8 * N_) + blockIdx.y * BN);
        q[0] = ldg128(p); q[1] = ldg128(p + 4 * N_);
        q[2] = ldg128(p + 16 * N_); q[3] = ldg128(p + 20 * N_);
        const void* ps = absmax + (uint32_t)(opq(t & ~3u) + blockIdx.y * BN);
        asm volatile("ld.global.nc.v2.b32 {%0, %1}, [%2];" : "=r"(sf.x), "=r"(sf.y) : "l"(ps) : "memory");
        c0 = ldg128(cb); c1 = ldg128(cb + 8);
    }
    const unsigned tstart = clk();
    const int mt = pair * 2 + rank;
    const int lane = threadIdx.x & 31;
    const int warp = __reduce_max_sync(~0u, threadIdx.x >> 5);
    const int wg = warp >> 2;
    const uint32_t bars = sbase + BAR_OFF;
    const uint32_t full = bars, rawfull = bars + 96, written = bars + 120, xbar = bars + 144, gbar = bars + 160 + wg * 16;
    const uint32_t rawh = bars + 192 - 8, ebar = bars + 216, ones = bars + 256;
    const uint32_t wbase = sbase + W_OFF;
    TS_INIT();
    __syncwarp();
    TSW(0, 0);

    auto insert = [](uint64_t m, int pos, int v) { const uint64_t low = (1ull << (4 * pos)) - 1; return (m & low) | ((m & ~low) << 4) | ((uint64_t)v << (4 * pos)); };
    const uint64_t others = (0xedcfedu >> (4 * pair)) & 0xfff;
    const uint64_t cmap = NG == 1 ? insert(0xba9876543210ull, G1, 12 + pair) | (others << 52)
                                  : insert(insert(0x76543210ull, G1, 8 + pair), G2, 12 + pair) | ((others - 0x444) << 40) | (others << 52);
    auto chunk = [&](int i) { return (int)(cmap >> (4 * i)) & 15; };
    unsigned* flag = gflag + nt * 32;
    uint8_t* wpan = wimg + nt * (8 * NG * UNIT);
    auto load_x = [&](int i, int slot, uint32_t bar) {
        tma_load_2d(sbase + slot * 32768, &tmx, chunk(i) * 64, mt * BM, bar);
        tma_load_2d(sbase + slot * 32768 + 16384, &tmx, chunk(i) * 64, mt * BM + 128, bar);
    };
    auto load_l = [&](int i, int slot, int g, uint32_t bar) {
        tma_load_2d(sbase + slot * 32768 + g * 16384, &tmx64, chunk(i) * 64, mt * BM + g * 128, bar);
        tma_load_2d(sbase + slot * 32768 + g * 16384 + 8192, &tmx64, chunk(i + 1) * 64, mt * BM + g * 128, bar);
    };
    auto snap = [&](int ss, uint32_t bar) { bulk_load(sbase + SC_OFF + ss * SC_STRIDE + 448, flag, 16, bar); };
    auto load_sc = [&](int i, int ss, uint32_t bar) {
        bulk_load(sbase + SC_OFF + ss * SC_STRIDE, absmax + chunk(i) * N_ + nt * BN, 448, bar);
    };
    auto load_raw = [&](int u, int slot) {
        mbar_expect_tx(rawfull + 8 * slot, UNIT);
        tma_load_5d(sbase + RAW_OFF + roff(slot), &tmq, 0, 0, nt * 7, rank, 4 * chunk(u >> 1) + 2 * (u & 1), rawfull + 8 * slot);
    };
    auto load_half = [&](int b, uint32_t more) {
        const uint32_t bar = (b & 1) ? rawfull + 8 * rslot(b >> 1) : rawh + 8 * (b >> 1);
        mbar_expect_tx(bar, 7168 + more);
        tma_load_5d(sbase + RAW_OFF + roff(rslot(b >> 1)) + (b & 1) * 7168, &tmq1, 0, 0, nt * 7, rank, b, bar);
    };
    auto load_w = [&](int v) {
        mbar_expect_tx(bars + ubar(v), UNIT + (!(v & 1) && v <= 24 ? 32768 : 0) + (v == 21 ? 16 : 0));
        bulk_load(sbase + uoff(v), wpan + (2 * (chunk(v >> 1) - NC) + (v & 1)) * UNIT, UNIT, bars + ubar(v));
    };
    auto prefetch_q = [&](int c) { if (c + PFQ < NC) tma_prefetch_2d(&tmqp, nt * BN, (c + PFQ) * 64 + pair * 16 + rank * 8); };
    auto prefetch_g = [&](int c) {
        if ((unsigned)(c - PFG) < 6) {
            const int k = c - PFG, k0 = k + (k >= 3);
            tma_prefetch_2d(&tmqp, nt * BN, (8 + (k0 & 4) + pair) * 64 + (k0 & 3) * 16 + rank * 8);
            if (k == 1 || k == 4) tma_prefetch_2d(&tmqp, nt * BN, (8 + (k0 & 4) + pair) * 64 + 48 + rank * 8);
        }
    };
    auto prefetch_x = [&](int i) { tma_prefetch_2d(&tmx16, chunk(i) * 64, mt * BM + nt * 16); };
    if (warp == 7) {
        if (elect()) {
            mbar_init(xbar, 1); mbar_init(rawh + 8, 1); mbar_init(rawfull + 8 * rslot(1), 1); mbar_init(xbar + 8, 1);
            fence_async_smem();
            load_half(2, 448);
            bulk_load(sbase + SC_OFF + sslot(0) * SC_STRIDE, absmax + nt * BN, 448, rawh + 8);
            load_half(3, 0);
            mbar_expect_tx(xbar, 16384);
            tma_load_2d(sbase, &tmx, 0, mt * BM, xbar);
            mbar_expect_tx(xbar + 8, 16384);
            tma_load_2d(sbase + 16384, &tmx, 0, mt * BM + 128, xbar + 8);
            mbar_init(rawfull + 8 * rslot(2), 1); mbar_init(rawfull + 8 * rslot(3), 1); mbar_init(rawh + 16, 1); mbar_init(rawh + 24, 1);
            mbar_init(ebar, 7); mbar_init(ebar + 8, 7);
            sts128(ones, make_uint4(1, 0, 0, 0)); sts128(ones + 16, make_uint4(0, 1, 0, 0));
#pragma unroll
            for (int s = 0; s < 12; s++) { mbar_init(full + 8 * s, 1); if (s < 4) mbar_arrive(full + 8 * s); }
#pragma unroll
            for (int s = 0; s < 3; s++) mbar_init(written + 8 * s, 7);
#pragma unroll
            for (int s = 0; s < 4; s++) mbar_init(bars + 160 + 8 * s, 4);
            asm volatile("fence.mbarrier_init.release.cluster;" ::: "memory");
            fence_async_smem();
            if ((sbase & 0xffffff) != 0x400) __trap();
        }
        __syncwarp();
        cluster_arrive();
        if (elect()) {
            asm volatile("prefetch.tensormap [%0];" ::"l"(&tmq) : "memory");
            asm volatile("prefetch.tensormap [%0];" ::"l"(&tmqp) : "memory");
            asm volatile("prefetch.tensormap [%0];" ::"l"(&tmx16) : "memory");
            asm volatile("prefetch.tensormap [%0];" ::"l"(&tmx64) : "memory");
            while (clk() - tstart < T2) { }
            load_half(4, 2 * 448 + 16);
            load_sc(1, sslot(1), rawh + 16); load_sc(2, sslot(2), rawh + 16); snap(sslot(1), rawh + 16);
            load_half(5, 0);
            while (clk() - tstart < T2B) { }
            tma_load_2d(sbase + 32768, &tmx, 64, mt * BM, full + 32);
            load_half(6, 0); load_half(7, 0);
            tma_load_2d(sbase + 32768 + 16384, &tmx, 64, mt * BM + 128, full + 32);
            load_sc(3, sslot(3), full + 48);
            while (clk() - tstart < T3) { }
            if (PFQ == 4) prefetch_q(-2);
            prefetch_q(-1);
        }
        __syncwarp();
        TSL(33);
        cluster_wait();
    } else {
        cluster_arrive();
    }
    const uint32_t rsrc = __shfl_sync(~0u, sbase + RAW_OFF + warp * 1024 + (lane & 7) * 128 + ((((lane >> 3) * 2) ^ (lane & 7)) << 4), lane);
    const uint32_t ssrc = sbase + SC_OFF + warp * 64;
    const int wpos = (nt & 1) ? (0x73210546 >> (4 * warp)) & 7 : warp;
    const uint32_t wown = wbase + rank * 7168 + wpos * 512;
    const uint32_t wdst = __shfl_sync(~0u, wown + lane * 16, lane);
    auto get_sc = [&](int ss) { return lds128(((opq(wdst) >> 3) & 0x30) + ssrc + ss * SC_STRIDE); };
    const uint32_t whalf = wbase + rank * 7168;
    const uint32_t pwhalf = mapa(whalf, rank ^ 1), pbars = mapa(bars, rank ^ 1);
    Lut lut;
    uint4 sc;
    uint4 q0, q1;
    auto fetch = [&](int slot, int h) {
        q0 = lds128(rsrc + roff(slot) + h * 7168);
        q1 = lds128((opq(rsrc) ^ 16) + roff(slot) + h * 7168);
    };
    auto signal = [&](uint32_t bar) { __syncwarp(); if (elect()) mbar_arrive(bar); __syncwarp(); };
    auto convert = [&](int ws, int h, bool w1, uint32_t bar1, uint32_t par1, bool w2, uint32_t bar2, uint32_t par2, bool next, int rsn,
                       bool sig, uint32_t sbar, bool scales, int cs) {
        bool ok1 = true, ok2 = true;
        if (w2) ok2 = mbar_try(bar2, par2);
        if (w1) ok1 = mbar_try(bar1, par1);
        uint4 w = dequant8(pack4(q0), pack4(q1), sc, lut);
        asm volatile("" : "+r"(w.x), "+r"(w.y), "+r"(w.z), "+r"(w.w));
        if (w1 && w2) mbar_wait2(bar2, par2, bar1, par1, ok1 && ok2);
        else if (w2) mbar_wait1(bar2, par2, ok2);
        else if (w1) mbar_wait1(bar1, par1, ok1);
        if (next) fetch(rsn, h ^ 1);
        sts128(wdst + ws * UNIT + h * 3584, w);
        if (sig) signal(sbar);
        if (scales) sc = get_sc(cs);
    };
    auto hand_over = [&](uint32_t sbar, uint32_t par, int ws, int h, uint32_t more, bool raw, int un, int rs, auto extra) {
        mbar_wait(sbar, par);
        fence_async_smem();
        if (elect()) {
            if (raw && RAWFIRST) load_raw(un, rs);
            copy_to_peer(pwhalf + ws * UNIT + h * 3584, whalf + ws * UNIT + h * 3584, 3584, pbars + 8 * (2 * ws + h));
            mbar_expect_tx(full + 8 * (2 * ws + h), 3584 + more);
            if (raw && !RAWFIRST) load_raw(un, rs);
            extra();
        }
        __syncwarp();
    };
    auto share = [&](int g, uint32_t o, uint32_t n) {
        bulk_store(wpan + 2 * (chunk(g) - NC) * UNIT + rank * 7168 + o, whalf + 2 * (g % 3) * UNIT + o, n);
        bulk_commit();
    };
    auto publish = [&](int k) {
        asm volatile("cp.async.bulk.wait_group 0;" ::: "memory");
        asm volatile("cp.reduce.async.bulk.global.shared::cta.bulk_group.add.u32 [%0], [%1], 16;" ::"l"(flag), "r"(ones + 16 * k) : "memory");
    };
    auto check = [&](int k, int ss) {
        unsigned f0, f1;
        asm volatile("ld.shared.u32 %0, [%1];" : "=r"(f0) : "r"(sbase + SC_OFF + sslot(1) * SC_STRIDE + 448 + 4 * k) : "memory");
        asm volatile("ld.shared.u32 %0, [%1];" : "=r"(f1) : "r"(sbase + SC_OFF + ss * SC_STRIDE + 448 + 4 * k) : "memory");
        asm volatile("{\n.reg .pred p;\n.reg .u32 n, d;\nmov.u32 n, 0;\nLAB_POLL:\nsub.u32 d, %0, %1;\nsetp.ge.u32 p, d, 8;\n@p bra.uni LAB_DONE;\n"
                     "ld.relaxed.gpu.global.u32 %0, [%2];\nadd.u32 n, n, 1;\nsetp.lt.u32 p, n, 0x10000;\n@p bra.uni LAB_POLL;\nLAB_DONE:\n}\n"
                     : "+r"(f1) : "r"(f0 & ~7u), "l"(flag + k) : "memory");
    };
    auto sig_bar = [&](int b) { return written + 8 * (b % 3); };
    auto sig_par = [](int b) { return (b / 3 - 1) & 1; };
    auto see = [&](int s) { if (s < 2 * NU) mbar_wait(full + 8 * (s % 12), (s / 12) & 1); else mbar_wait(bars + ubar(s >> 1), upar(s >> 1)); };
    auto block = [&](int b, int sn) {
        const int u = b >> 1, h = b & 1;
        const bool next = b + 1 < 2 * NU;
        convert(u % NW, h, sn == 2 || sn >= 4, sn == 2 ? ebar + 8 : full + 8 * (sn % 12), (sn / 12) & 1,
                next && (h || b < 8), b == 5 ? rawh + 24 : rawfull + 8 * rslot((b + 1) >> 1), b == 5 ? 0 : rpar((b + 1) >> 1),
                next, rslot((b + 1) >> 1), true, sig_bar(b), (b & 3) == 3 && next, sslot((b + 1) >> 2));
    };
    auto hand = [&](int b, auto extra) {
        const int u = b >> 1;
        hand_over(sig_bar(b), sig_par(b), u % NW, b & 1, (b & 3) == 0 ? 32768 : (b & 3) == 2 && b < 36 ? 448 : b == SN0 + 3 ? 16 : 0, (b & 1) && u + NR < NU, u + NR, rslot(u), extra);
    };
    auto pass_on = [&](int u) {
        fence_async_smem();
        __syncwarp();
        if (elect()) {
            const uint32_t o = wpos * 512 + u * UNIT;
            copy_to_peer(pwhalf + o, whalf + o, 512, pbars + 216 + 8 * u);
            copy_to_peer(pwhalf + o + 3584, whalf + o + 3584, 512, pbars + 216 + 8 * u);
            if (u == 1) mbar_arrive(sig_bar(3));
            mbar_expect_tx(ebar + 8 * u, 1024);
        }
        __syncwarp();
    };
    bool ok0 = false;
    if (warp < 7) {
        lut.lo[0] = __byte_perm(c0.x, c0.y, 0x6420); lut.hi[0] = __byte_perm(c0.x, c0.y, 0x7531);
        lut.lo[1] = __byte_perm(c0.z, c0.w, 0x6420); lut.hi[1] = __byte_perm(c0.z, c0.w, 0x7531);
        lut.lo[2] = __byte_perm(c1.x, c1.y, 0x6420); lut.hi[2] = __byte_perm(c1.x, c1.y, 0x7531);
        lut.lo[3] = __byte_perm(c1.z, c1.w, 0x6420); lut.hi[3] = __byte_perm(c1.z, c1.w, 0x7531);
        const uint32_t d = wown + (lane >> 3) * 128 + (lane & 3) * 16 + (lane & 4) * 2;
#pragma unroll
        for (int j = 0; j < 4; j++) {
            uint32_t a, b;
            lookup4(pack4(q[j]), lut, a, b);
            asm volatile("st.shared.v2.b32 [%0], {%1, %2};" ::"r"(d + (j >> 1) * 3584 + (j & 1) * 64), "r"(mul_bf16x2(a, sf.x)), "r"(mul_bf16x2(b, sf.y)) : "memory");
        }
        TSL(33);
        cluster_wait();
        pass_on(0);
        TSL(34);
        mbar_wait(rawh + 8, 0);
        const uint4 a0 = lds128(rsrc + roff(rslot(1))), a1 = lds128((rsrc ^ 16) + roff(rslot(1))), s0 = get_sc(sslot(0));
        mbar_wait(rawfull + 8 * rslot(1), 0);
        const uint4 a2 = lds128(rsrc + roff(rslot(1)) + 7168), a3 = lds128((rsrc ^ 16) + roff(rslot(1)) + 7168);
        sts128(wdst + UNIT, dequant8(pack4(a0), pack4(a1), s0, lut));
        sts128(wdst + UNIT + 3584, dequant8(pack4(a2), pack4(a3), s0, lut));
        ok0 = mbar_try(xbar + 8 * wg, 0) & mbar_try(ebar, 0);
        pass_on(1);
    }
    TSL(31);
    mbar_wait2(xbar + 8 * wg, 0, ebar, 0, ok0);
    TSL(32);

    float acc0[112], acc1[112];
    const uint32_t descA = ((0x400 + wg * 16384) >> 4) | (1u << 16);
    auto mma = [&](int s) {
        const uint32_t da = opq(descA) + ((s >> 2) % 3) * (32768 >> 4) + (s & 3) * 2;
        wgmma_fence();
        wgmma224<1, 8>(acc0, da, bdesc(s)); wgmma224<1, 8>(acc1, da + 512, bdesc(s));
        wgmma_commit();
        wgmma_wait<2>();
    };
    wgmma_fence();
    wgmma224<0, 8>(acc0, descA, bdesc(0)); wgmma224<0, 8>(acc1, descA + 512, bdesc(0));
    wgmma_commit();
    TSL(0);
    mma(1); TSL(1);
    if (warp < 7) {
        mbar_wait(rawh + 16, 0); fetch(rslot(2), 0); sc = get_sc(sslot(1));
        block(4, -1); block(5, 2);
    } else {
        mbar_wait(sig_bar(3), sig_par(3));
        if (elect()) { load_raw(4, rslot(4)); load_x(2, 2, full + 64); prefetch_q(0); prefetch_x(3); prefetch_g(0); }
        __syncwarp();
        hand(4, [] {});
        mbar_wait(ebar + 8, 0);
    }
    static_for<2, 8>([&](auto S) {
        constexpr int s = S.value;
        mma(s); TSL(s);
        if (warp < 7) block(s + 4, s + 1);
        else {
            hand(s + 3, [&] {
                if (s == 4) prefetch_q(1);
                if (s == 5) { load_sc(4, sslot(4), full + 80); prefetch_g(1); }
                if (s == 6) prefetch_x(4);
                if (s == 7) load_x(3, 0, full);
            });
            if (s >= 3) see(s + 1);
        }
    });
    {
        uint32_t ph = 0;
#pragma unroll 1
        for (int cb = 2; cb < 8; cb += 3)
          static_for<2, 5>([&](auto I) {
            constexpr int cc = I.value;
            constexpr int j0 = cc % 3, j1 = (cc + 1) % 3, j2 = (cc + 2) % 3;
            const int c = cb + cc - 2;
            auto sh = [&](int h) {
                if (SHE) {
                    if ((cc - G1 + 1) % 3 == 0 && c == G1 - 1) share(G1, h * 3584, 3584);
                    if ((cc - G1) % 3 == 0 && c == G1) share(G1, UNIT + h * 3584, 3584);
                    if ((cc - G1 - 1) % 3 == 0 && h == 0 && c == G1 + 1) publish(0);
                } else {
                if ((cc - G1 + 1) % 3 == 0 && h == 1 && c == G1 - 1) share(G1, 0, 3584);
                if ((cc - G1) % 3 == 0 && c == G1) share(G1, h ? UNIT : 3584, 3584);
                if ((cc - G1 - 1) % 3 == 0 && h == 0 && c == G1 + 1) share(G1, UNIT + 3584, 3584);
                if ((cc - G1 - 1) % 3 == 0 && h == 1 && c == G1 + 1) publish(0);
                }
                if ((cc - G2 + 1) % 3 == 0 && h == 1 && c == G2 - 1) share(G2, 0, 3584);
            };
            if (cc == 2) TSL(c < 8 ? 36 : 37);
            mma(4 * j0); TSL(cb == TLIT ? 4 * cc : 30);
            if (warp < 7) convert(2 * j1, 0, true, full + 32 * j0 + 8, ph, false, 0, 0, true, j1, true, sig_bar(4 * cc + 4), false, 0);
            else {
                const bool ok = mbar_try(full + 32 * j0 + 8, ph);
                hand_over(sig_bar(4 * cc + 3), sig_par(4 * cc + 3), 2 * j0 + 1, 1, 0, true, 2 * c + 4, j2, [&] { prefetch_q(c); });
                mbar_wait1(full + 32 * j0 + 8, ph, ok);
            }
            mma(4 * j0 + 1); TSL(cb == TLIT ? 4 * cc + 1 : 30);
            if (warp < 7) convert(2 * j1, 1, true, full + 32 * j0 + 16, ph, true, rawfull + 8 * j0, rpar(2 * cc + 3), true, j0, true, sig_bar(4 * cc + 5), false, 0);
            else {
                const bool ok = mbar_try(full + 32 * j0 + 16, ph);
                hand_over(sig_bar(4 * cc + 4), sig_par(4 * cc + 4), 2 * j1, 0, 32768, false, 0, 0, [&] { load_sc(c + 3, j0, full + 32 * j1 + 16); prefetch_g(c); sh(0); });
                mbar_wait1(full + 32 * j0 + 16, ph, ok);
            }
            mma(4 * j0 + 2); TSL(cb == TLIT ? 4 * cc + 2 : 30);
            if (warp < 7) convert(2 * j1 + 1, 0, true, full + 32 * j0 + 24, ph, false, 0, 0, true, j0, true, sig_bar(4 * cc + 6), false, 0);
            else {
                const bool ok = mbar_try(full + 32 * j0 + 24, ph);
                hand_over(sig_bar(4 * cc + 5), sig_par(4 * cc + 5), 2 * j1, 1, 0, true, 2 * c + 5, j1, [&] { prefetch_x(c + PFX); });
                mbar_wait1(full + 32 * j0 + 24, ph, ok);
            }
            if (j1 == 0) asm volatile("xor.b32 %0, %0, 1;" : "+r"(ph));
            mma(4 * j0 + 3); TSL(cb == TLIT ? 4 * cc + 3 : 30);
            if (warp < 7) convert(2 * j1 + 1, 1, true, full + 32 * j1, ph, true, rawfull + 8 * j2, rpar(2 * cc + 4), true, j2, true, sig_bar(4 * cc + 7), true, j2);
            else {
                const bool ok = mbar_try(full + 32 * j1, ph);
                hand_over(sig_bar(4 * cc + 6), sig_par(4 * cc + 6), 2 * j1 + 1, 0, 448, false, 0, 0, [&] { load_x(c + 2, j2, full + 32 * j2); sh(1); });
                mbar_wait1(full + 32 * j1, ph, ok);
            }
          });
    }
    uint4 fa[4 * NF];
    auto get_frag = [&](int f, uint32_t rows, int j0 = 0, int j1 = 4) {
        int ln; asm volatile("mov.u32 %0, %%laneid;" : "=r"(ln));
        const uint32_t a = rows + (ln & 15) * 128 + (((ln >> 4) ^ (ln & 7)) << 4);
#pragma unroll
        for (int j = j0; j < j1; j++) fa[4 * f + j] = ldmatrix_x4(a ^ (j * 32));
    };
    static_assert(NG == 2 && G2 == 8 && G1 <= 6, "");
    static_for<32, 46>([&](auto S) {
        constexpr int s = S.value;
        constexpr int vb = 40 + (s - 37) / 2;
        mma(s);
        if (TLIT == 99) TSL(s - 26);
        if (s == 39) cluster_arrive();
        if (s == 41) cluster_wait();
        if (s == 36) mbar_wait(rawh + 8, 1);
        if (s >= 36 && s < 40) get_frag(0, sbase + uoff(24) + wg * (uoff(23) - uoff(24)) + (warp & 3) * 2048, s - 36, s - 35);
        if (warp < 7) {
            if (s < 36) block(s + 4, s + 1);
            else {
                if (s & 1) signal(sig_bar(vb));
                if (s < 39 || (s & 1)) see(s + 1);
            }
        } else {
            auto loads = [&] {
                if (s == 32) { share(G2, 3584, 3584); prefetch_x(11); }
                if (s == 33) {
                    mbar_expect_tx(rawh + 8, 16384);
                    tma_load_2d(sbase + uoff(24), &tmx64, chunk(12) * 64, mt * BM + 64, rawh + 8);
                    tma_load_2d(sbase + uoff(23), &tmx64, chunk(12) * 64, mt * BM + 192, rawh + 8);
                    share(G2, UNIT, 3584);
                }
                if (s == 34) share(G2, UNIT + 3584, 3584);
                if (s == 36) publish(1);
                if (s == 37) { prefetch_x(12); prefetch_x(13); }
                if (s == 39) snap(1, bars + ubar(21));
                if (s == 41) { prefetch_x(14); prefetch_x(15); }
                if (s == 43) { load_l(12, 0, 0, bars + ubar(24)); load_l(12, 0, 1, bars + ubar(24)); }
                else if ((s & 3) == 3) load_x((s >> 2) + 2, ((s >> 2) + 2) % 3, bars + ubar(2 * (s >> 2) + 4));
                if (s == 44) {
                    asm volatile("prefetch.tensormap [%0];" ::"l"(&tmo64) : "memory");
                    asm volatile("prefetch.tensormap [%0];" ::"l"(&tmo32) : "memory");
                }
                if (s == 45) { mbar_expect_tx(xbar, 16384); load_l(14, 1, 0, xbar); }
                static_for<NU, 31>([&](auto V) { if constexpr (utime(V.value) == (s == 45 ? 46 : s)) load_w(V.value); });
            };
            if (s == SN0) { if (elect()) snap(0, full + 8 * ((SN0 + 3) % 12)); __syncwarp(); }
            if (s == CK0) check(0, 0);
            if (s == 42) check(1, 1);
            if (s <= 36) hand(s + 3, loads);
            else {
                if (!(s & 1)) mbar_wait(sig_bar(40 + (s - 38) / 2), sig_par(40 + (s - 38) / 2));
                if (s == 45) mbar_wait(sig_bar(vb), sig_par(vb));
                if (elect()) loads();
                __syncwarp();
            }
            if (s < 39 || (s & 1)) see(s + 1);
        }
    });
    if (wg == 1) bar_sync(8);
    mma(46);
    if (warp == 7) {
        wgmma_wait<1>();
        see(48);
        if (elect()) { load_w(31); mbar_expect_tx(xbar + 8, 16384); load_l(14, 1, 1, xbar + 8); }
        __syncwarp();
    }
    mma(47);
    if (wg == 0) bar_arrive(8);
    const uint32_t slice0 = sbase + wg * 16384 + (warp & 3) * 2048;
    auto slc = [&](int p) { return slice0 + (p >> 1) * 32768 + (p & 1) * 8192; };
    const int row0 = mt * BM + wg * 128 + (warp & 3) * 16, odd = nt & 1;
    const int colL = nt * BN + odd * 96, colA = nt * BN + (odd ? 32 : 128), colB = nt * BN + (odd ? 0 : 192);
    auto load_s = [&](int i, int p, uint32_t bar) { tma_load_2d(slc(p), &tmx16, chunk(i) * 64, row0 + 64, bar); };
    const uint32_t tA = opq(descA);
    see(48);
    wgmma_wait<0>();
    RT(0);
    float lo0[64], hi0[48], lo1[64], hi1[48];
#pragma unroll
    for (int i = 0; i < 64; i++) { asm volatile("mov.b32 %0, %1;" : "=f"(lo0[i]) : "f"(acc0[i])); asm volatile("mov.b32 %0, %1;" : "=f"(lo1[i]) : "f"(acc1[i])); }
#pragma unroll
    for (int i = 0; i < 48; i++) { asm volatile("mov.b32 %0, %1;" : "=f"(hi0[i]) : "f"(acc0[64 + i])); asm volatile("mov.b32 %0, %1;" : "=f"(hi1[i]) : "f"(acc1[64 + i])); }
    auto tdesc = [&](int p, int s) { return tA + (p >> 1) * (32768 >> 4) + (p & 1) * 512 + (s & 3) * 2; };
    auto ldesc = [&](int s) { return tdesc(s >> 2, s); };
    auto gdesc = [&](int s) { return tdesc(((s >> 2) + 3) % 6, s); };
    if (wg == 1) { mbar_wait(xbar + 8, 1); bar_sync(1); }
    static_for<0, 8>([&](auto V) {
        constexpr int v = 24 + (V.value == 0 || V.value > 3 ? V.value : V.value == 3 ? 1 : V.value + 1), s = 2 * (v - 24);
        if (v == 26) mbar_wait2(bars + ubar(26), upar(26), bars + ubar(27), upar(27), wg);
        else if (v == 28) mbar_wait2(bars + ubar(28), upar(28), xbar, 1, wg);
        else if (v != 24 && v != 27) mbar_wait1(bars + ubar(v), upar(v), wg);
        wgmma_fence();
        wgmma96<1, 8>(hi0, ldesc(s), bdesc(48 + s) + 128);
        wgmma96<1, 8>(hi0, ldesc(s + 1), bdesc(49 + s) + 128);
    });
    wgmma_commit();
    bar_arrive(1 + wg);
    if (NG == 1) cluster_arrive();
    wgmma_wait<0>();
    RT(1);
    stage_cols<64, 0>(hi0, slc(4)); send(slc(4), &tmo64, colA, row0);
    stage_cols<32, 32>(hi0, slc(5));
    RT(2);
    bar_sync(2 + wg);
    RT(3);
    wgmma_fence();
    static_for<0, 7>([&](auto S) { wgmma128<1, 8>(lo0, ldesc(S.value), bdesc(48 + S.value)); });
    wgmma_commit();
    send(slc(5), &tmo32, colB, row0);
    wgmma_fence();
    static_for<7, 16>([&](auto S) { wgmma128<1, 8>(lo0, ldesc(S.value), bdesc(48 + S.value)); });
    wgmma_commit();
    bar_arrive(3 + wg);
    RT(4);
    {
        const uint32_t zero = opq(gridDim.x - 2);
#pragma unroll
        for (int j = 0; j < 4; j++) { fa[j].x ^= zero; fa[j].y ^= zero; fa[j].z ^= zero; fa[j].w ^= zero; asm volatile("" : "+r"(fa[j].x), "+r"(fa[j].y), "+r"(fa[j].z), "+r"(fa[j].w)); }
    }
    if (elect()) { mbar_expect_tx(gbar, 4096); bulk_wait_read<0>(); load_s(13, 4, gbar); load_s(14, 5, gbar); }
    __syncwarp();
    wgmma_wait<0>();
    RT(5);
    stage_cols<64, 0>(lo0, slc(2));
    if (elect()) { mbar_expect_tx(gbar + 8, 2048); load_s(15, 0, gbar + 8); }
    __syncwarp();
    const bool okg = mbar_try(gbar, 0);
    send(slc(2), &tmo64, colL, row0);
    stage_cols<64, 32>(lo0, slc(3));
    mbar_wait1(gbar, 0, okg);
    if (NF > 1 && FAT == 0) get_frag(1, slc(4));
    RT(6);
    constexpr int NF2 = FAT == 0 ? NF : 1;
    auto ord2 = [](int i) { return MIX && i < 8 * NF2 ? ((i & 1) ? 4 * NF2 + (i >> 1) : i >> 1) : i; };
    auto ord3 = [](int i) { return MIX == 2 ? ((i % (4 / NF)) == 0 ? i / (4 / NF) : 4 * NF + i - i / (4 / NF) - 1) : MIX && i < 8 * NF ? ((i & 1) ? 4 * NF + (i >> 1) : i >> 1) : i; };
    auto mma2 = [&](auto I) { constexpr int s = ord2(I.value); if constexpr (s < 4 * NF2) wgmma128r<8>(lo1, fa[s], bdesc(48 + s)); else wgmma128<1, 8>(lo1, gdesc(s), bdesc(48 + s)); };
    auto mma3 = [&](auto I) { constexpr int s = ord3(I.value); if constexpr (s < 4 * NF) wgmma96r<8>(hi1, fa[s], bdesc(48 + s) + 128); else wgmma96<1, 8>(hi1, gdesc(s), bdesc(48 + s) + 128); };
    bar_sync(4 + wg);
    RT(7);
    wgmma_fence();
    static_for<0, 8>(mma2);
    wgmma_commit();
    const bool okg2 = mbar_try(gbar + 8, 0);
    send(slc(3), &tmo64, colL + 64, row0);
    mbar_wait1(gbar + 8, 0, okg2);
    wgmma_fence();
    static_for<8, 16>(mma2);
    wgmma_commit();
    bar_arrive(5 + wg);
    RT(8);
    if (NF > 1 && FAT == 1) get_frag(1, slc(4));
    if (NF > 2) get_frag(2, slc(5));
    if (NF > 3) get_frag(3, slc(0));
    if (elect()) bulk_wait_read<1>();
    __syncwarp();
    wgmma_wait<0>();
    RT(9);
    stage_cols<64, 0>(lo1, slc(1)); send(slc(1), &tmo64, colL, row0 + 64);
    stage_cols<64, 32>(lo1, slc(2));
    if (E2) send(slc(2), &tmo64, colL + 64, row0 + 64);
    RT(10);
    bar_sync(6 + wg);
    RT(11);
    wgmma_fence();
    static_for<0, GG3>(mma3);
    wgmma_commit();
    if (!E2) send(slc(2), &tmo64, colL + 64, row0 + 64);
    wgmma_fence();
    static_for<GG3, 16>(mma3);
    wgmma_commit();
    if (wg == 0) bar_arrive(7);
    RT(12);
    wgmma_wait<0>();
    RT(13);
    if (LASTO) { stage_cols<32, 32>(hi1, slc(5)); send(slc(5), &tmo32, colB, row0 + 64); }
    stage_cols<64, 0>(hi1, slc(4)); send(slc(4), &tmo64, colA, row0 + 64);
    if (!LASTO) { stage_cols<32, 32>(hi1, slc(5)); send(slc(5), &tmo32, colB, row0 + 64); }
    RT(14);
    if (elect()) bulk_wait_read<0>();
    __syncwarp();
    RT(15);
    TSW(wg * 4, 38 + wg);
    TS_DUMP();
    TL_DUMP();
    if (NG == 1) cluster_wait();
}

typedef CUresult (*EncodeFn)(CUtensorMap*, CUtensorMapDataType, cuuint32_t, void*, const cuuint64_t*, const cuuint64_t*,
                             const cuuint32_t*, const cuuint32_t*, CUtensorMapInterleave, CUtensorMapSwizzle,
                             CUtensorMapL2promotion, CUtensorMapFloatOOBfill);

extern "C" void kernel_launch(void* const* d_in, const int* in_sizes, int n_in, void* d_out, int out_size) {
    const __nv_bfloat16* x = (const __nv_bfloat16*)d_in[0];
    const int* qw = (const int*)d_in[1];
    const __nv_bfloat16* cb = (const __nv_bfloat16*)d_in[2];
    const __nv_bfloat16* absmax = (const __nv_bfloat16*)d_in[3];
    static EncodeFn encode = nullptr;
    static void *wimg = nullptr, *gflag = nullptr;
    if (!encode) {
        cudaGetSymbolAddress(&wimg, g_wimg);
        cudaGetSymbolAddress(&gflag, g_flag);
        void* fn = nullptr;
        cudaDriverEntryPointQueryResult qr;
        cudaGetDriverEntryPoint("cuTensorMapEncodeTiled", &fn, cudaEnableDefault, &qr);
        encode = (EncodeFn)fn;
        cudaFuncSetAttribute(nf4_gemm_kernel, cudaFuncAttributeMaxDynamicSharedMemorySize, SMEM_BYTES);
    }
    CUtensorMap tmx, tmq, tmo64, tmo32, tmqp, tmx16, tmx64, tmq1;
    {
        cuuint64_t dims[2] = {(cuuint64_t)K_, (cuuint64_t)M_};
        cuuint64_t strides[1] = {(cuuint64_t)K_ * 2};
        cuuint32_t box[2] = {64, 128};
        cuuint32_t es[2] = {1, 1};
        encode(&tmx, CU_TENSOR_MAP_DATA_TYPE_BFLOAT16, 2, (void*)x, dims, strides, box, es, CU_TENSOR_MAP_INTERLEAVE_NONE,
               CU_TENSOR_MAP_SWIZZLE_128B, CU_TENSOR_MAP_L2_PROMOTION_L2_128B, CU_TENSOR_MAP_FLOAT_OOB_FILL_NONE);
        box[1] = 64;
        encode(&tmx64, CU_TENSOR_MAP_DATA_TYPE_BFLOAT16, 2, (void*)x, dims, strides, box, es, CU_TENSOR_MAP_INTERLEAVE_NONE,
               CU_TENSOR_MAP_SWIZZLE_128B, CU_TENSOR_MAP_L2_PROMOTION_L2_128B, CU_TENSOR_MAP_FLOAT_OOB_FILL_NONE);
        box[1] = 16;
        encode(&tmx16, CU_TENSOR_MAP_DATA_TYPE_BFLOAT16, 2, (void*)x, dims, strides, box, es, CU_TENSOR_MAP_INTERLEAVE_NONE,
               CU_TENSOR_MAP_SWIZZLE_128B, CU_TENSOR_MAP_L2_PROMOTION_L2_128B, CU_TENSOR_MAP_FLOAT_OOB_FILL_NONE);
    }
    {
        cuuint64_t dims[5] = {32, 8, (cuuint64_t)(N_ / 32), 2, (cuuint64_t)(K_ / 16)};
        cuuint64_t strides[4] = {(cuuint64_t)N_ * 4, 128, (cuuint64_t)N_ * 4 * 8, (cuuint64_t)N_ * 4 * 16};
        cuuint32_t box[5] = {32, 8, 7, 1, 2};
        cuuint32_t es[5] = {1, 1, 1, 1, 1};
        encode(&tmq, CU_TENSOR_MAP_DATA_TYPE_INT32, 5, (void*)qw, dims, strides, box, es, CU_TENSOR_MAP_INTERLEAVE_NONE,
               CU_TENSOR_MAP_SWIZZLE_128B, CU_TENSOR_MAP_L2_PROMOTION_L2_128B, CU_TENSOR_MAP_FLOAT_OOB_FILL_NONE);
        box[4] = 1;
        encode(&tmq1, CU_TENSOR_MAP_DATA_TYPE_INT32, 5, (void*)qw, dims, strides, box, es, CU_TENSOR_MAP_INTERLEAVE_NONE,
               CU_TENSOR_MAP_SWIZZLE_128B, CU_TENSOR_MAP_L2_PROMOTION_L2_128B, CU_TENSOR_MAP_FLOAT_OOB_FILL_NONE);
        cuuint64_t dims2[2] = {(cuuint64_t)N_, (cuuint64_t)K_};
        cuuint32_t box2[2] = {224, 8};
        encode(&tmqp, CU_TENSOR_MAP_DATA_TYPE_INT32, 2, (void*)qw, dims2, strides, box2, es, CU_TENSOR_MAP_INTERLEAVE_NONE,
               CU_TENSOR_MAP_SWIZZLE_NONE, CU_TENSOR_MAP_L2_PROMOTION_L2_128B, CU_TENSOR_MAP_FLOAT_OOB_FILL_NONE);
    }
    {
        cuuint64_t dims[2] = {(cuuint64_t)N_, (cuuint64_t)M_};
        cuuint64_t strides[1] = {(cuuint64_t)N_ * 2};
        cuuint32_t box[2] = {64, 16};
        cuuint32_t es[2] = {1, 1};
        encode(&tmo64, CU_TENSOR_MAP_DATA_TYPE_BFLOAT16, 2, d_out, dims, strides, box, es, CU_TENSOR_MAP_INTERLEAVE_NONE,
               CU_TENSOR_MAP_SWIZZLE_128B, CU_TENSOR_MAP_L2_PROMOTION_NONE, CU_TENSOR_MAP_FLOAT_OOB_FILL_NONE);
        box[0] = 32;
        encode(&tmo32, CU_TENSOR_MAP_DATA_TYPE_BFLOAT16, 2, d_out, dims, strides, box, es, CU_TENSOR_MAP_INTERLEAVE_NONE,
               CU_TENSOR_MAP_SWIZZLE_64B, CU_TENSOR_MAP_L2_PROMOTION_NONE, CU_TENSOR_MAP_FLOAT_OOB_FILL_NONE);
    }
    nf4_gemm_kernel<<<dim3(2, 16, 4), 256, SMEM_BYTES>>>(qw, cb, absmax, (uint8_t*)wimg, (unsigned*)gflag, tmx, tmq, tmo64, tmo32, tmqp, tmx16, tmx64, tmq1);
}
```

```cpp
#include <cuda_runtime.h>
#include <cuda_bf16.h>
#include <cuda.h>
#include <stdint.h>

#define NG 2
#define G1 6
#define G2 8
#define PFG 1
#define GG3 6
#define RAWFIRST 1
#define SN0 32
#define CK0 36
#define T2 900
#define T2B 1300
#define T3 1700
#define TLPRO -2
#define TLIT 2
constexpr int M_ = 2048, K_ = 1024, N_ = 3584;
constexpr int BM = 256, BN = 224;
constexpr int UNIT = 14336;
constexpr int NW = 6, NR = 3;
constexpr int NU = 32 - 6 * NG;
constexpr int NC = 16 - 4 * NG;
constexpr int CE = NU / 2 - 2;
#define PFQ 4
constexpr int PFX = 3;
constexpr int RAW_OFF = 3 * 32768;
constexpr int SC_OFF = RAW_OFF + 2 * UNIT;
constexpr int SC_STRIDE = 464;
constexpr int W_OFF = 127 * 1024;
constexpr int RAW2_OFF = W_OFF + NW * UNIT;
constexpr int BAR_OFF = RAW2_OFF + UNIT;
constexpr int SMEM_BYTES = BAR_OFF + 320;
__device__ __align__(1024) uint8_t g_wimg[16 * 8 * NG * UNIT];
__device__ __align__(128) unsigned g_flag[16 * 32];

#define TSL(i)
#define TL_DUMP()
#define TSW(w, i)
#define TS_INIT()
#define TS_DUMP()
#define RT(i)

__device__ __forceinline__ uint32_t smem_u32(const void* p) { return (uint32_t)__cvta_generic_to_shared(p); }
__device__ __forceinline__ bool elect() {
    uint32_t ok;
    asm volatile("{\n.reg .pred p;\nelect.sync _|p, 0xffffffff;\nselp.u32 %0, 1, 0, p;\n}\n" : "=r"(ok));
    return ok != 0;
}
__device__ __forceinline__ void mbar_init(uint32_t bar, uint32_t cnt) { asm volatile("mbarrier.init.shared::cta.b64 [%0], %1;" ::"r"(bar), "r"(cnt) : "memory"); }
__device__ __forceinline__ void mbar_expect_tx(uint32_t bar, uint32_t bytes) { asm volatile("mbarrier.arrive.expect_tx.shared::cta.b64 _, [%0], %1;" ::"r"(bar), "r"(bytes) : "memory"); }
__device__ __forceinline__ void mbar_arrive(uint32_t bar) { asm volatile("mbarrier.arrive.shared::cta.b64 _, [%0];" ::"r"(bar) : "memory"); }
#define BOUNDED
#define WAIT_INIT "mov.u32 n, 0;\n"
#define WAIT_NEXT "@p bra.uni LAB_DONE;\nadd.u32 n, n, 1;\nsetp.lt.u32 p, n, 0x4000;\n@p bra.uni LAB_WAIT;\n"
__device__ __forceinline__ void mbar_wait(uint32_t bar, uint32_t parity) {
    asm volatile(
        "{\n.reg .pred p;\n.reg .u32 n;\n"
        WAIT_INIT
        "LAB_WAIT:\n"
        "mbarrier.try_wait.parity.shared::cta.b64 p, [%0], %1;\n"
        WAIT_NEXT
        "LAB_DONE:\n}\n" ::"r"(bar), "r"(parity) : "memory");
}
__device__ __forceinline__ bool mbar_try(uint32_t bar, uint32_t parity) {
    uint32_t ok;
    asm volatile("{\n.reg .pred p;\nmbarrier.test_wait.parity.shared::cta.b64 p, [%1], %2;\nselp.u32 %0, 1, 0, p;\n}\n" : "=r"(ok) : "r"(bar), "r"(parity) : "memory");
    return ok != 0;
}
__device__ __forceinline__ void mbar_wait1(uint32_t b0, uint32_t p0, bool skip) {
    asm volatile(
        "{\n.reg .pred p;\n.reg .u32 n;\n"
        "setp.ne.u32 p, %2, 0;\n@p bra.uni LAB_DONE;\n"
        WAIT_INIT
        "LAB_WAIT:\n"
        "mbarrier.try_wait.parity.shared::cta.b64 p, [%0], %1;\n"
        WAIT_NEXT
        "LAB_DONE:\n}\n" ::"r"(b0), "r"(p0), "r"((uint32_t)skip) : "memory");
}
__device__ __forceinline__ void mbar_wait2(uint32_t b0, uint32_t p0, uint32_t b1, uint32_t p1, bool skip = false) {
    asm volatile(
        "{\n.reg .pred p, q;\n.reg .u32 n;\n"
        "setp.ne.u32 p, %4, 0;\n@p bra.uni LAB_DONE;\n"
        WAIT_INIT
        "LAB_WAIT:\n"
        "mbarrier.try_wait.parity.shared::cta.b64 p, [%0], %1;\n"
        "mbarrier.try_wait.parity.shared::cta.b64 q, [%2], %3;\n"
        "and.pred p, p, q;\n"
        WAIT_NEXT
        "LAB_DONE:\n}\n" ::"r"(b0), "r"(p0), "r"(b1), "r"(p1), "r"((uint32_t)skip) : "memory");
}
__device__ __forceinline__ void tma_load_2d(uint32_t dst, const CUtensorMap* tm, int c0, int c1, uint32_t bar) {
    asm volatile("cp.async.bulk.tensor.2d.shared::cluster.global.mbarrier::complete_tx::bytes [%0], [%1, {%2, %3}], [%4];"
                 ::"r"(dst), "l"(tm), "r"(c0), "r"(c1), "r"(bar) : "memory");
}
__device__ __forceinline__ void tma_load_5d(uint32_t dst, const CUtensorMap* tm, int c0, int c1, int c2, int c3, int c4, uint32_t bar) {
    asm volatile("cp.async.bulk.tensor.5d.shared::cluster.global.mbarrier::complete_tx::bytes [%0], [%1, {%2, %3, %4, %5, %6}], [%7];"
                 ::"r"(dst), "l"(tm), "r"(c0), "r"(c1), "r"(c2), "r"(c3), "r"(c4), "r"(bar) : "memory");
}
__device__ __forceinline__ void tma_prefetch_2d(const CUtensorMap* tm, int c0, int c1) {
    asm volatile("cp.async.bulk.prefetch.tensor.2d.L2.global [%0, {%1, %2}];" ::"l"(tm), "r"(c0), "r"(c1) : "memory");
}
__device__ __forceinline__ void bulk_load(uint32_t dst, const void* src, uint32_t bytes, uint32_t bar) {
    asm volatile("cp.async.bulk.shared::cluster.global.mbarrier::complete_tx::bytes [%0], [%1], %2, [%3];"
                 ::"r"(dst), "l"(src), "r"(bytes), "r"(bar) : "memory");
}
__device__ __forceinline__ void cluster_arrive() { asm volatile("barrier.cluster.arrive.relaxed.aligned;" ::: "memory"); }
__device__ __forceinline__ void cluster_wait() { asm volatile("barrier.cluster.wait.acquire.aligned;" ::: "memory"); }
__device__ __forceinline__ uint32_t mapa(uint32_t addr, uint32_t cta) {
    uint32_t r; asm("mapa.shared::cluster.u32 %0, %1, %2;" : "=r"(r) : "r"(addr), "r"(cta)); return r;
}
__device__ __forceinline__ void copy_to_peer(uint32_t cdst, uint32_t src, uint32_t bytes, uint32_t cbar) {
    asm volatile("cp.async.bulk.shared::cluster.shared::cta.mbarrier::complete_tx::bytes [%0], [%1], %2, [%3];"
                 ::"r"(cdst), "r"(src), "r"(bytes), "r"(cbar) : "memory");
}
__device__ __forceinline__ void wgmma_fence() { asm volatile("wgmma.fence.sync.aligned;" ::: "memory"); }
__device__ __forceinline__ void wgmma_commit() { asm volatile("wgmma.commit_group.sync.aligned;" ::: "memory"); }
template <int N> __device__ __forceinline__ void wgmma_wait() { asm volatile("wgmma.wait_group.sync.aligned %0;" ::"n"(N) : "memory"); }
__device__ __forceinline__ uint32_t pack_bf16(float lo, float hi) {
    uint32_t r; asm("cvt.rn.bf16x2.f32 %0, %1, %2;" : "=r"(r) : "f"(hi), "f"(lo)); return r;
}
__device__ __forceinline__ void stmatrix_x4(uint32_t addr, uint32_t a, uint32_t b, uint32_t c, uint32_t d) {
    asm volatile("stmatrix.sync.aligned.m8n8.x4.shared.b16 [%0], {%1, %2, %3, %4};" ::"r"(addr), "r"(a), "r"(b), "r"(c), "r"(d) : "memory");
}
__device__ __forceinline__ uint4 ldmatrix_x4(uint32_t a) {
    uint4 v; asm volatile("ldmatrix.sync.aligned.m8n8.x4.shared.b16 {%0, %1, %2, %3}, [%4];" : "=r"(v.x), "=r"(v.y), "=r"(v.z), "=r"(v.w) : "r"(a) : "memory"); return v;
}
__device__ __forceinline__ uint4 lds128(uint32_t a) {
    uint4 v; asm volatile("ld.shared.v4.b32 {%0, %1, %2, %3}, [%4];" : "=r"(v.x), "=r"(v.y), "=r"(v.z), "=r"(v.w) : "r"(a) : "memory"); return v;
}
__device__ __forceinline__ void sts128(uint32_t a, uint4 v) {
    asm volatile("st.shared.v4.b32 [%0], {%1, %2, %3, %4};" ::"r"(a), "r"(v.x), "r"(v.y), "r"(v.z), "r"(v.w) : "memory");
}
__device__ __forceinline__ uint4 ldg128(const void* p) {
    uint4 v; asm volatile("ld.global.nc.v4.b32 {%0, %1, %2, %3}, [%4];" : "=r"(v.x), "=r"(v.y), "=r"(v.z), "=r"(v.w) : "l"(p) : "memory"); return v;
}
__device__ __forceinline__ unsigned clk() { unsigned c; asm volatile("mov.u32 %0, %%clock;" : "=r"(c) :: "memory"); return c; }
__device__ __forceinline__ uint32_t mul_bf16x2(uint32_t a, uint32_t b) { uint32_t r; asm("mul.rn.bf16x2 %0, %1, %2;" : "=r"(r) : "r"(a), "r"(b)); return r; }
struct Lut { uint32_t lo[4], hi[4]; };
__device__ __forceinline__ uint32_t prmt(uint32_t a, uint32_t b, uint32_t s) { uint32_t r; asm("prmt.b32 %0, %1, %2, %3;" : "=r"(r) : "r"(a), "r"(b), "r"(s)); return r; }
__device__ __forceinline__ uint32_t pack4(const uint4& q) {
    uint32_t ab, cd, p;
    asm volatile("mad.lo.u32 %0, %1, 16, %2;" : "=r"(ab) : "r"(q.y), "r"(q.x));
    asm volatile("mad.lo.u32 %0, %1, 16, %2;" : "=r"(cd) : "r"(q.w), "r"(q.z));
    asm volatile("mad.lo.u32 %0, %1, 256, %2;" : "=r"(p) : "r"(cd), "r"(ab));
    return p;
}
__device__ __forceinline__ void lookup4(uint32_t p, const Lut& t, uint32_t& w01, uint32_t& w23) {
    const uint32_t t8 = p & 0x8888u, s7 = p & 0x7777u;
    const uint32_t sel = (t8 >> 1) + 0x3210u;
    const uint32_t lo = prmt(prmt(t.lo[0], t.lo[1], p), prmt(t.lo[2], t.lo[3], s7), sel);
    const uint32_t hi = prmt(prmt(t.hi[0], t.hi[1], p), prmt(t.hi[2], t.hi[3], s7), sel);
    w01 = prmt(lo, hi, 0x5140);
    w23 = prmt(lo, hi, 0x7362);
}
__device__ __forceinline__ uint4 dequant8(uint32_t p0, uint32_t p1, const uint4& sc, const Lut& t) {
    uint4 r;
    lookup4(p0, t, r.x, r.y);
    lookup4(p1, t, r.z, r.w);
    r.x = mul_bf16x2(r.x, sc.x); r.y = mul_bf16x2(r.y, sc.y); r.z = mul_bf16x2(r.z, sc.z); r.w = mul_bf16x2(r.w, sc.w);
    return r;
}
__device__ __forceinline__ void fence_async_smem() { asm volatile("fence.proxy.async.shared::cta;" ::: "memory"); }

template <int SCALE_D, int BHI, uint32_t AHI = 0x40000040u>
__device__ __forceinline__ void wgmma224(float (&d)[112], uint32_t descA, uint32_t descB) {
    asm volatile(
        "{\n.reg .pred p;\n.reg .b64 da, db;\nsetp.ne.b32 p, %114, 0;\n"
        "mov.b64 da, {%112, %116};\nmov.b64 db, {%113, %115};\n"
        "wgmma.mma_async.sync.aligned.m64n224k16.f32.bf16.bf16 "
        "{%0, %1, %2, %3, %4, %5, %6, %7, %8, %9, %10, %11, %12, %13, %14, %15, "
        "%16, %17, %18, %19, %20, %21, %22, %23, %24, %25, %26, %27, %28, %29, %30, %31, "
        "%32, %33, %34, %35, %36, %37, %38, %39, %40, %41, %42, %43, %44, %45, %46, %47, "
        "%48, %49, %50, %51, %52, %53, %54, %55, %56, %57, %58, %59, %60, %61, %62, %63, "
        "%64, %65, %66, %67, %68, %69, %70, %71, %72, %73, %74, %75, %76, %77, %78, %79, "
        "%80, %81, %82, %83, %84, %85, %86, %87, %88, %89, %90, %91, %92, %93, %94, %95, "
        "%96, %97, %98, %99, %100, %101, %102, %103, %104, %105, %106, %107, %108, %109, %110, %111}, "
        "da, db, p, 1, 1, 0, 1;\n}\n"
        : "+f"(d[0]), "+f"(d[1]), "+f"(d[2]), "+f"(d[3]), "+f"(d[4]), "+f"(d[5]), "+f"(d[6]), "+f"(d[7]),
          "+f"(d[8]), "+f"(d[9]), "+f"(d[10]), "+f"(d[11]), "+f"(d[12]), "+f"(d[13]), "+f"(d[14]), "+f"(d[15]),
          "+f"(d[16]), "+f"(d[17]), "+f"(d[18]), "+f"(d[19]), "+f"(d[20]), "+f"(d[21]), "+f"(d[22]), "+f"(d[23]),
          "+f"(d[24]), "+f"(d[25]), "+f"(d[26]), "+f"(d[27]), "+f"(d[28]), "+f"(d[29]), "+f"(d[30]), "+f"(d[31]),
          "+f"(d[32]), "+f"(d[33]), "+f"(d[34]), "+f"(d[35]), "+f"(d[36]), "+f"(d[37]), "+f"(d[38]), "+f"(d[39]),
          "+f"(d[40]), "+f"(d[41]), "+f"(d[42]), "+f"(d[43]), "+f"(d[44]), "+f"(d[45]), "+f"(d[46]), "+f"(d[47]),
          "+f"(d[48]), "+f"(d[49]), "+f"(d[50]), "+f"(d[51]), "+f"(d[52]), "+f"(d[53]), "+f"(d[54]), "+f"(d[55]),
          "+f"(d[56]), "+f"(d[57]), "+f"(d[58]), "+f"(d[59]), "+f"(d[60]), "+f"(d[61]), "+f"(d[62]), "+f"(d[63]),
          "+f"(d[64]), "+f"(d[65]), "+f"(d[66]), "+f"(d[67]), "+f"(d[68]), "+f"(d[69]), "+f"(d[70]), "+f"(d[71]),
          "+f"(d[72]), "+f"(d[73]), "+f"(d[74]), "+f"(d[75]), "+f"(d[76]), "+f"(d[77]), "+f"(d[78]), "+f"(d[79]),
          "+f"(d[80]), "+f"(d[81]), "+f"(d[82]), "+f"(d[83]), "+f"(d[84]), "+f"(d[85]), "+f"(d[86]), "+f"(d[87]),
          "+f"(d[88]), "+f"(d[89]), "+f"(d[90]), "+f"(d[91]), "+f"(d[92]), "+f"(d[93]), "+f"(d[94]), "+f"(d[95]),
          "+f"(d[96]), "+f"(d[97]), "+f"(d[98]), "+f"(d[99]), "+f"(d[100]), "+f"(d[101]), "+f"(d[102]), "+f"(d[103]),
          "+f"(d[104]), "+f"(d[105]), "+f"(d[106]), "+f"(d[107]), "+f"(d[108]), "+f"(d[109]), "+f"(d[110]), "+f"(d[111])
        : "r"(descA), "r"(descB), "n"(SCALE_D), "n"(BHI), "n"(AHI));
}

template <int SCALE_D, int BHI, uint32_t AHI = 0x40000040u>
__device__ __forceinline__ void wgmma128(float (&d)[64], uint32_t descA, uint32_t descB) {
    asm volatile(
        "{\n.reg .pred p;\n.reg .b64 da, db;\nsetp.ne.b32 p, %66, 0;\n"
        "mov.b64 da, {%64, %68};\nmov.b64 db, {%65, %67};\n"
        "wgmma.mma_async.sync.aligned.m64n128k16.f32.bf16.bf16 "
        "{%0, %1, %2, %3, %4, %5, %6, %7, %8, %9, %10, %11, %12, %13, %14, %15, "
        "%16, %17, %18, %19, %20, %21, %22, %23, %24, %25, %26, %27, %28, %29, %30, %31, "
        "%32, %33, %34, %35, %36, %37, %38, %39, %40, %41, %42, %43, %44, %45, %46, %47, "
        "%48, %49, %50, %51, %52, %53, %54, %55, %56, %57, %58, %59, %60, %61, %62, %63}, "
        "da, db, p, 1, 1, 0, 1;\n}\n"
        : "+f"(d[0]), "+f"(d[1]), "+f"(d[2]), "+f"(d[3]), "+f"(d[4]), "+f"(d[5]), "+f"(d[6]), "+f"(d[7]),
          "+f"(d[8]), "+f"(d[9]), "+f"(d[10]), "+f"(d[11]), "+f"(d[12]), "+f"(d[13]), "+f"(d[14]), "+f"(d[15]),
          "+f"(d[16]), "+f"(d[17]), "+f"(d[18]), "+f"(d[19]), "+f"(d[20]), "+f"(d[21]), "+f"(d[22]), "+f"(d[23]),
          "+f"(d[24]), "+f"(d[25]), "+f"(d[26]), "+f"(d[27]), "+f"(d[28]), "+f"(d[29]), "+f"(d[30]), "+f"(d[31]),
          "+f"(d[32]), "+f"(d[33]), "+f"(d[34]), "+f"(d[35]), "+f"(d[36]), "+f"(d[37]), "+f"(d[38]), "+f"(d[39]),
          "+f"(d[40]), "+f"(d[41]), "+f"(d[42]), "+f"(d[43]), "+f"(d[44]), "+f"(d[45]), "+f"(d[46]), "+f"(d[47]),
          "+f"(d[48]), "+f"(d[49]), "+f"(d[50]), "+f"(d[51]), "+f"(d[52]), "+f"(d[53]), "+f"(d[54]), "+f"(d[55]),
          "+f"(d[56]), "+f"(d[57]), "+f"(d[58]), "+f"(d[59]), "+f"(d[60]), "+f"(d[61]), "+f"(d[62]), "+f"(d[63])
        : "r"(descA), "r"(descB), "n"(SCALE_D), "n"(BHI), "n"(AHI));
}

template <int SCALE_D, int BHI, uint32_t AHI = 0x40000040u>
__device__ __forceinline__ void wgmma96(float (&d)[48], uint32_t descA, uint32_t descB) {
    asm volatile(
        "{\n.reg .pred p;\n.reg .b64 da, db;\nsetp.ne.b32 p, %50, 0;\n"
        "mov.b64 da, {%48, %52};\nmov.b64 db, {%49, %51};\n"
        "wgmma.mma_async.sync.aligned.m64n96k16.f32.bf16.bf16 "
        "{%0, %1, %2, %3, %4, %5, %6, %7, %8, %9, %10, %11, %12, %13, %14, %15, "
        "%16, %17, %18, %19, %20, %21, %22, %23, %24, %25, %26, %27, %28, %29, %30, %31, "
        "%32, %33, %34, %35, %36, %37, %38, %39, %40, %41, %42, %43, %44, %45, %46, %47}, "
        "da, db, p, 1, 1, 0, 1;\n}\n"
        : "+f"(d[0]), "+f"(d[1]), "+f"(d[2]), "+f"(d[3]), "+f"(d[4]), "+f"(d[5]), "+f"(d[6]), "+f"(d[7]),
          "+f"(d[8]), "+f"(d[9]), "+f"(d[10]), "+f"(d[11]), "+f"(d[12]), "+f"(d[13]), "+f"(d[14]), "+f"(d[15]),
          "+f"(d[16]), "+f"(d[17]), "+f"(d[18]), "+f"(d[19]), "+f"(d[20]), "+f"(d[21]), "+f"(d[22]), "+f"(d[23]),
          "+f"(d[24]), "+f"(d[25]), "+f"(d[26]), "+f"(d[27]), "+f"(d[28]), "+f"(d[29]), "+f"(d[30]), "+f"(d[31]),
          "+f"(d[32]), "+f"(d[33]), "+f"(d[34]), "+f"(d[35]), "+f"(d[36]), "+f"(d[37]), "+f"(d[38]), "+f"(d[39]),
          "+f"(d[40]), "+f"(d[41]), "+f"(d[42]), "+f"(d[43]), "+f"(d[44]), "+f"(d[45]), "+f"(d[46]), "+f"(d[47])
        : "r"(descA), "r"(descB), "n"(SCALE_D), "n"(BHI), "n"(AHI));
}

template <int BHI>
__device__ __forceinline__ void wgmma128r(float (&d)[64], const uint4& a, uint32_t descB) {
    asm volatile(
        "{\n.reg .pred p;\n.reg .b64 db;\nsetp.eq.b32 p, 0, 0;\n"
        "mov.b64 db, {%68, %69};\n"
        "wgmma.mma_async.sync.aligned.m64n128k16.f32.bf16.bf16 "
        "{%0, %1, %2, %3, %4, %5, %6, %7, %8, %9, %10, %11, %12, %13, %14, %15, "
        "%16, %17, %18, %19, %20, %21, %22, %23, %24, %25, %26, %27, %28, %29, %30, %31, "
        "%32, %33, %34, %35, %36, %37, %38, %39, %40, %41, %42, %43, %44, %45, %46, %47, "
        "%48, %49, %50, %51, %52, %53, %54, %55, %56, %57, %58, %59, %60, %61, %62, %63}, "
        "{%64, %65, %66, %67}, db, p, 1, 1, 1;\n}\n"
        : "+f"(d[0]), "+f"(d[1]), "+f"(d[2]), "+f"(d[3]), "+f"(d[4]), "+f"(d[5]), "+f"(d[6]), "+f"(d[7]),
          "+f"(d[8]), "+f"(d[9]), "+f"(d[10]), "+f"(d[11]), "+f"(d[12]), "+f"(d[13]), "+f"(d[14]), "+f"(d[15]),
          "+f"(d[16]), "+f"(d[17]), "+f"(d[18]), "+f"(d[19]), "+f"(d[20]), "+f"(d[21]), "+f"(d[22]), "+f"(d[23]),
          "+f"(d[24]), "+f"(d[25]), "+f"(d[26]), "+f"(d[27]), "+f"(d[28]), "+f"(d[29]), "+f"(d[30]), "+f"(d[31]),
          "+f"(d[32]), "+f"(d[33]), "+f"(d[34]), "+f"(d[35]), "+f"(d[36]), "+f"(d[37]), "+f"(d[38]), "+f"(d[39]),
          "+f"(d[40]), "+f"(d[41]), "+f"(d[42]), "+f"(d[43]), "+f"(d[44]), "+f"(d[45]), "+f"(d[46]), "+f"(d[47]),
          "+f"(d[48]), "+f"(d[49]), "+f"(d[50]), "+f"(d[51]), "+f"(d[52]), "+f"(d[53]), "+f"(d[54]), "+f"(d[55]),
          "+f"(d[56]), "+f"(d[57]), "+f"(d[58]), "+f"(d[59]), "+f"(d[60]), "+f"(d[61]), "+f"(d[62]), "+f"(d[63])
        : "r"(a.x), "r"(a.y), "r"(a.z), "r"(a.w), "r"(descB), "n"(BHI));
}

template <int BHI>
__device__ __forceinline__ void wgmma96r(float (&d)[48], const uint4& a, uint32_t descB) {
    asm volatile(
        "{\n.reg .pred p;\n.reg .b64 db;\nsetp.eq.b32 p, 0, 0;\n"
        "mov.b64 db, {%52, %53};\n"
        "wgmma.mma_async.sync.aligned.m64n96k16.f32.bf16.bf16 "
        "{%0, %1, %2, %3, %4, %5, %6, %7, %8, %9, %10, %11, %12, %13, %14, %15, "
        "%16, %17, %18, %19, %20, %21, %22, %23, %24, %25, %26, %27, %28, %29, %30, %31, "
        "%32, %33, %34, %35, %36, %37, %38, %39, %40, %41, %42, %43, %44, %45, %46, %47}, "
        "{%48, %49, %50, %51}, db, p, 1, 1, 1;\n}\n"
        : "+f"(d[0]), "+f"(d[1]), "+f"(d[2]), "+f"(d[3]), "+f"(d[4]), "+f"(d[5]), "+f"(d[6]), "+f"(d[7]),
          "+f"(d[8]), "+f"(d[9]), "+f"(d[10]), "+f"(d[11]), "+f"(d[12]), "+f"(d[13]), "+f"(d[14]), "+f"(d[15]),
          "+f"(d[16]), "+f"(d[17]), "+f"(d[18]), "+f"(d[19]), "+f"(d[20]), "+f"(d[21]), "+f"(d[22]), "+f"(d[23]),
          "+f"(d[24]), "+f"(d[25]), "+f"(d[26]), "+f"(d[27]), "+f"(d[28]), "+f"(d[29]), "+f"(d[30]), "+f"(d[31]),
          "+f"(d[32]), "+f"(d[33]), "+f"(d[34]), "+f"(d[35]), "+f"(d[36]), "+f"(d[37]), "+f"(d[38]), "+f"(d[39]),
          "+f"(d[40]), "+f"(d[41]), "+f"(d[42]), "+f"(d[43]), "+f"(d[44]), "+f"(d[45]), "+f"(d[46]), "+f"(d[47])
        : "r"(a.x), "r"(a.y), "r"(a.z), "r"(a.w), "r"(descB), "n"(BHI));
}

__device__ __forceinline__ uint32_t opq(uint32_t v) { asm volatile("" : "+r"(v)); return v; }
template <int I> struct IC { static constexpr int value = I; };
template <int B, int E, class F> __device__ __forceinline__ void static_for(F&& f) {
    if constexpr (B < E) { f(IC<B>{}); static_for<B + 1, E>(f); }
}

__device__ __forceinline__ void tma_store_2d(const CUtensorMap* tm, uint32_t src, int c0, int c1) {
    asm volatile("cp.async.bulk.tensor.2d.global.shared::cta.bulk_group [%0, {%2, %3}], [%1];" ::"l"(tm), "r"(src), "r"(c0), "r"(c1) : "memory");
}
__device__ __forceinline__ void bulk_store(void* dst, uint32_t src, uint32_t bytes) {
    asm volatile("cp.async.bulk.global.shared::cta.bulk_group [%0], [%1], %2;" ::"l"(dst), "r"(src), "r"(bytes) : "memory");
}
__device__ __forceinline__ void bulk_commit() { asm volatile("cp.async.bulk.commit_group;" ::: "memory"); }
template <int N> __device__ __forceinline__ void bulk_wait_read() { asm volatile("cp.async.bulk.wait_group.read %0;" ::"n"(N) : "memory"); }
__device__ __forceinline__ void bar_arrive(int id) { asm volatile("bar.arrive %0, 256;" ::"r"(id) : "memory"); }
__device__ __forceinline__ void bar_sync(int id) { asm volatile("bar.sync %0, 256;" ::"r"(id) : "memory"); }
template <int NC, int OFF, int N>
__device__ __forceinline__ void stage_cols(const float (&acc)[N], uint32_t stg) {
    int lane; asm volatile("mov.u32 %0, %%laneid;" : "=r"(lane));
    const int r = lane & 15;
    const uint32_t a0 = NC == 64 ? stg + r * 128 + (((lane >> 4) ^ (r & 7)) << 4) : stg + r * 64 + (((lane >> 4) ^ ((r >> 1) & 3)) << 4);
#pragma unroll
    for (int j = 0; j < NC / 16; j++) {
        const int i = OFF + 8 * j;
        stmatrix_x4(a0 ^ (j * 32), pack_bf16(acc[i], acc[i + 1]), pack_bf16(acc[i + 2], acc[i + 3]), pack_bf16(acc[i + 4], acc[i + 5]), pack_bf16(acc[i + 6], acc[i + 7]));
    }
}
__device__ __forceinline__ void send(uint32_t stg, const CUtensorMap* tmo, int col, int row) {
    fence_async_smem();
    __syncwarp();
    if (elect()) { tma_store_2d(tmo, stg, col, row); bulk_commit(); }
    __syncwarp();
}

__host__ __device__ constexpr int rslot(int u) { return (2 * u) % 3; }
__host__ __device__ constexpr int roff(int slot) { return slot < 2 ? slot * UNIT : RAW2_OFF - RAW_OFF; }
__host__ __device__ constexpr int rpar(int u) { return (u / 3 - (u % 3 == 0)) & 1; }
__host__ __device__ constexpr int sslot(int c) { return c < 3 ? c + 3 : c % 3; }
__host__ __device__ constexpr int vturn(int v) {
    return v < 20 ? v : v == 20 ? -21 : v == 21 ? -22 : v == 22 ? 21 : v == 23 ? -20 : v == 24 ? 20 : v < 29 ? v - 3 : v == 29 ? -24 : v == 30 ? -25 : 27;
}
__host__ __device__ constexpr int uoff(int v) { return vturn(v) < 0 ? RAW_OFF + roff(rslot(-vturn(v))) : W_OFF + (vturn(v) % NW) * UNIT; }
__host__ __device__ constexpr int ubar(int v) { return vturn(v) < 0 ? 96 + 8 * rslot(-vturn(v)) : 16 * (vturn(v) % NW); }
__host__ __device__ constexpr int upar(int v) { return vturn(v) < 0 ? rpar(-vturn(v)) : (vturn(v) / NW) & 1; }
__host__ __device__ constexpr int utime(int v) {
    return v < 22 ? CK0 : v == 22 || v == 25 ? 38 : v < 25 ? 40 : v < 28 ? 42 : v == 28 ? 44 : 2 * v - 14;
}
__host__ __device__ constexpr uint32_t bdesc(int s) { return (uint32_t)(((0x400 + uoff(s >> 1)) >> 4) | ((7168u >> 4) << 16)) + (s & 1) * 224; }

__global__ void __cluster_dims__(2, 1, 1) __launch_bounds__(256, 1)
nf4_gemm_kernel(const int* __restrict__ qw, const __nv_bfloat16* __restrict__ cb, const __nv_bfloat16* __restrict__ absmax,
                uint8_t* __restrict__ wimg, unsigned* __restrict__ gflag,
                const __grid_constant__ CUtensorMap tmx, const __grid_constant__ CUtensorMap tmq, const __grid_constant__ CUtensorMap tmo64,
                const __grid_constant__ CUtensorMap tmo32, const __grid_constant__ CUtensorMap tmqp, const __grid_constant__ CUtensorMap tmx16,
                const __grid_constant__ CUtensorMap tmx64, const __grid_constant__ CUtensorMap tmq1) {
    extern __shared__ __align__(1024) uint8_t smem[];
    const uint32_t sbase = smem_u32(smem);
    const int rank = blockIdx.x, nt = blockIdx.y, pair = blockIdx.z;
    uint4 q[4], c0, c1;
    uint2 sf;
    if (threadIdx.x < 224) {
        const uint32_t t = threadIdx.x;
        const int* p = qw + (uint32_t)((t & 3) * (N_ - 1) + t + blockIdx.x * (8 * N_) + blockIdx.y * BN);
        q[0] = ldg128(p); q[1] = ldg128(p + 4 * N_);
        q[2] = ldg128(p + 16 * N_); q[3] = ldg128(p + 20 * N_);
        const void* ps = absmax + (uint32_t)(opq(t & ~3u) + blockIdx.y * BN);
        asm volatile("ld.global.nc.v2.b32 {%0, %1}, [%2];" : "=r"(sf.x), "=r"(sf.y) : "l"(ps) : "memory");
        c0 = ldg128(cb); c1 = ldg128(cb + 8);
    }
    const unsigned tstart = clk();
    const int mt = pair * 2 + rank;
    const int lane = threadIdx.x & 31;
    const int warp = __reduce_max_sync(~0u, threadIdx.x >> 5);
    const int wg = warp >> 2;
    const uint32_t bars = sbase + BAR_OFF;
    const uint32_t full = bars, rawfull = bars + 96, written = bars + 120, xbar = bars + 144, gbar = bars + 160 + wg * 16;
    const uint32_t rawh = bars + 192 - 8, ebar = bars + 216, ones = bars + 256;
    const uint32_t wbase = sbase + W_OFF;
    TS_INIT();
    __syncwarp();
    TSW(0, 0);

    auto insert = [](uint64_t m, int pos, int v) { const uint64_t low = (1ull << (4 * pos)) - 1; return (m & low) | ((m & ~low) << 4) | ((uint64_t)v << (4 * pos)); };
    const uint64_t others = (0xedcfedu >> (4 * pair)) & 0xfff;
    const uint64_t cmap = NG == 1 ? insert(0xba9876543210ull, G1, 12 + pair) | (others << 52)
                                  : insert(insert(0x76543210ull, G1, 8 + pair), G2, 12 + pair) | ((others - 0x444) << 40) | (others << 52);
    auto chunk = [&](int i) { return (int)(cmap >> (4 * i)) & 15; };
    unsigned* flag = gflag + nt * 32;
    uint8_t* wpan = wimg + nt * (8 * NG * UNIT);
    auto load_x = [&](int i, int slot, uint32_t bar) {
        tma_load_2d(sbase + slot * 32768, &tmx, chunk(i) * 64, mt * BM, bar);
        tma_load_2d(sbase + slot * 32768 + 16384, &tmx, chunk(i) * 64, mt * BM + 128, bar);
    };
    auto load_l = [&](int i, int slot, int g, uint32_t bar) {
        tma_load_2d(sbase + slot * 32768 + g * 16384, &tmx64, chunk(i) * 64, mt * BM + g * 128, bar);
        tma_load_2d(sbase + slot * 32768 + g * 16384 + 8192, &tmx64, chunk(i + 1) * 64, mt * BM + g * 128, bar);
    };
    auto snap = [&](int ss, uint32_t bar) { bulk_load(sbase + SC_OFF + ss * SC_STRIDE + 448, flag, 16, bar); };
    auto load_sc = [&](int i, int ss, uint32_t bar) {
        bulk_load(sbase + SC_OFF + ss * SC_STRIDE, absmax + chunk(i) * N_ + nt * BN, 448, bar);
    };
    auto load_raw = [&](int u, int slot) {
        mbar_expect_tx(rawfull + 8 * slot, UNIT);
        tma_load_5d(sbase + RAW_OFF + roff(slot), &tmq, 0, 0, nt * 7, rank, 4 * chunk(u >> 1) + 2 * (u & 1), rawfull + 8 * slot);
    };
    auto load_half = [&](int b, uint32_t more) {
        const uint32_t bar = (b & 1) ? rawfull + 8 * rslot(b >> 1) : rawh + 8 * (b >> 1);
        mbar_expect_tx(bar, 7168 + more);
        tma_load_5d(sbase + RAW_OFF + roff(rslot(b >> 1)) + (b & 1) * 7168, &tmq1, 0, 0, nt * 7, rank, b, bar);
    };
    auto load_w = [&](int v) {
        mbar_expect_tx(bars + ubar(v), UNIT + (!(v & 1) && v <= 24 ? 32768 : 0) + (v == 21 ? 16 : 0));
        bulk_load(sbase + uoff(v), wpan + (2 * (chunk(v >> 1) - NC) + (v & 1)) * UNIT, UNIT, bars + ubar(v));
    };
    auto prefetch_q = [&](int c) { if (c + PFQ < NC) tma_prefetch_2d(&tmqp, nt * BN, (c + PFQ) * 64 + pair * 16 + rank * 8); };
    auto prefetch_g = [&](int c) {
        if ((unsigned)(c - PFG) < 6) {
            const int k = c - PFG, k0 = k + (k >= 3);
            tma_prefetch_2d(&tmqp, nt * BN, (8 + (k0 & 4) + pair) * 64 + (k0 & 3) * 16 + rank * 8);
            if (k == 1 || k == 4) tma_prefetch_2d(&tmqp, nt * BN, (8 + (k0 & 4) + pair) * 64 + 48 + rank * 8);
        }
    };
    auto prefetch_x = [&](int i) { tma_prefetch_2d(&tmx16, chunk(i) * 64, mt * BM + nt * 16); };
    if (warp == 7) {
        if (elect()) {
            mbar_init(xbar, 1); mbar_init(rawh + 8, 1); mbar_init(rawfull + 8 * rslot(1), 1); mbar_init(xbar + 8, 1);
            fence_async_smem();
            load_half(2, 448);
            bulk_load(sbase + SC_OFF + sslot(0) * SC_STRIDE, absmax + nt * BN, 448, rawh + 8);
            load_half(3, 0);
            mbar_expect_tx(xbar, 16384);
            tma_load_2d(sbase, &tmx, 0, mt * BM, xbar);
            mbar_expect_tx(xbar + 8, 16384);
            tma_load_2d(sbase + 16384, &tmx, 0, mt * BM + 128, xbar + 8);
            mbar_init(rawfull + 8 * rslot(2), 1); mbar_init(rawfull + 8 * rslot(3), 1); mbar_init(rawh + 16, 1); mbar_init(rawh + 24, 1);
            mbar_init(ebar, 7); mbar_init(ebar + 8, 7);
            sts128(ones, make_uint4(1, 0, 0, 0)); sts128(ones + 16, make_uint4(0, 1, 0, 0));
#pragma unroll
            for (int s = 0; s < 12; s++) { mbar_init(full + 8 * s, 1); if (s < 4) mbar_arrive(full + 8 * s); }
#pragma unroll
            for (int s = 0; s < 3; s++) mbar_init(written + 8 * s, 7);
#pragma unroll
            for (int s = 0; s < 4; s++) mbar_init(bars + 160 + 8 * s, 4);
            asm volatile("fence.mbarrier_init.release.cluster;" ::: "memory");
            fence_async_smem();
            if ((sbase & 0xffffff) != 0x400) __trap();
        }
        __syncwarp();
        cluster_arrive();
        if (elect()) {
            asm volatile("prefetch.tensormap [%0];" ::"l"(&tmq) : "memory");
            asm volatile("prefetch.tensormap [%0];" ::"l"(&tmqp) : "memory");
            asm volatile("prefetch.tensormap [%0];" ::"l"(&tmx16) : "memory");
            asm volatile("prefetch.tensormap [%0];" ::"l"(&tmx64) : "memory");
            while (clk() - tstart < T2) { }
            load_half(4, 2 * 448 + 16);
            load_sc(1, sslot(1), rawh + 16); load_sc(2, sslot(2), rawh + 16); snap(sslot(1), rawh + 16);
            load_half(5, 0);
            while (clk() - tstart < T2B) { }
            tma_load_2d(sbase + 32768, &tmx, 64, mt * BM, full + 32);
            load_half(6, 0); load_half(7, 0);
            tma_load_2d(sbase + 32768 + 16384, &tmx, 64, mt * BM + 128, full + 32);
            load_sc(3, sslot(3), full + 48);
            while (clk() - tstart < T3) { }
            if (PFQ == 4) prefetch_q(-2);
            prefetch_q(-1);
        }
        __syncwarp();
        TSL(33);
        cluster_wait();
    } else {
        cluster_arrive();
    }
    const uint32_t rsrc = __shfl_sync(~0u, sbase + RAW_OFF + warp * 1024 + (lane & 7) * 128 + ((((lane >> 3) * 2) ^ (lane & 7)) << 4), lane);
    const uint32_t ssrc = sbase + SC_OFF + warp * 64;
    const int wpos = (nt & 1) ? (0x73210546 >> (4 * warp)) & 7 : warp;
    const uint32_t wown = wbase + rank * 7168 + wpos * 512;
    const uint32_t wdst = __shfl_sync(~0u, wown + lane * 16, lane);
    auto get_sc = [&](int ss) { return lds128(((opq(wdst) >> 3) & 0x30) + ssrc + ss * SC_STRIDE); };
    const uint32_t whalf = wbase + rank * 7168;
    const uint32_t pwhalf = mapa(whalf, rank ^ 1), pbars = mapa(bars, rank ^ 1);
    Lut lut;
    uint4 sc;
    uint4 q0, q1;
    auto fetch = [&](int slot, int h) {
        q0 = lds128(rsrc + roff(slot) + h * 7168);
        q1 = lds128((opq(rsrc) ^ 16) + roff(slot) + h * 7168);
    };
    auto signal = [&](uint32_t bar) { __syncwarp(); if (elect()) mbar_arrive(bar); __syncwarp(); };
    auto convert = [&](int ws, int h, bool w1, uint32_t bar1, uint32_t par1, bool w2, uint32_t bar2, uint32_t par2, bool next, int rsn,
                       bool sig, uint32_t sbar, bool scales, int cs) {
        bool ok1 = true, ok2 = true;
        if (w2) ok2 = mbar_try(bar2, par2);
        if (w1) ok1 = mbar_try(bar1, par1);
        uint4 w = dequant8(pack4(q0), pack4(q1), sc, lut);
        asm volatile("" : "+r"(w.x), "+r"(w.y), "+r"(w.z), "+r"(w.w));
        if (w1 && w2) mbar_wait2(bar2, par2, bar1, par1, ok1 && ok2);
        else if (w2) mbar_wait1(bar2, par2, ok2);
        else if (w1) mbar_wait1(bar1, par1, ok1);
        if (next) fetch(rsn, h ^ 1);
        sts128(wdst + ws * UNIT + h * 3584, w);
        if (sig) signal(sbar);
        if (scales) sc = get_sc(cs);
    };
    auto hand_over = [&](uint32_t sbar, uint32_t par, int ws, int h, uint32_t more, bool raw, int un, int rs, auto extra) {
        mbar_wait(sbar, par);
        fence_async_smem();
        if (elect()) {
            if (raw && RAWFIRST) load_raw(un, rs);
            copy_to_peer(pwhalf + ws * UNIT + h * 3584, whalf + ws * UNIT + h * 3584, 3584, pbars + 8 * (2 * ws + h));
            mbar_expect_tx(full + 8 * (2 * ws + h), 3584 + more);
            if (raw && !RAWFIRST) load_raw(un, rs);
            extra();
        }
        __syncwarp();
    };
    auto share = [&](int g, uint32_t o, uint32_t n) {
        bulk_store(wpan + 2 * (chunk(g) - NC) * UNIT + rank * 7168 + o, whalf + 2 * (g % 3) * UNIT + o, n);
        bulk_commit();
    };
    auto publish = [&](int k) {
        asm volatile("cp.async.bulk.wait_group 0;" ::: "memory");
        asm volatile("cp.reduce.async.bulk.global.shared::cta.bulk_group.add.u32 [%0], [%1], 16;" ::"l"(flag), "r"(ones + 16 * k) : "memory");
    };
    auto check = [&](int k, int ss) {
        unsigned f0, f1;
        asm volatile("ld.shared.u32 %0, [%1];" : "=r"(f0) : "r"(sbase + SC_OFF + sslot(1) * SC_STRIDE + 448 + 4 * k) : "memory");
        asm volatile("ld.shared.u32 %0, [%1];" : "=r"(f1) : "r"(sbase + SC_OFF + ss * SC_STRIDE + 448 + 4 * k) : "memory");
        asm volatile("{\n.reg .pred p;\n.reg .u32 n, d;\nmov.u32 n, 0;\nLAB_POLL:\nsub.u32 d, %0, %1;\nsetp.ge.u32 p, d, 8;\n@p bra.uni LAB_DONE;\n"
                     "ld.relaxed.gpu.global.u32 %0, [%2];\nadd.u32 n, n, 1;\nsetp.lt.u32 p, n, 0x10000;\n@p bra.uni LAB_POLL;\nLAB_DONE:\n}\n"
                     : "+r"(f1) : "r"(f0 & ~7u), "l"(flag + k) : "memory");
    };
    auto sig_bar = [&](int b) { return written + 8 * (b % 3); };
    auto sig_par = [](int b) { return (b / 3 - 1) & 1; };
    auto see = [&](int s) { if (s < 2 * NU) mbar_wait(full + 8 * (s % 12), (s / 12) & 1); else mbar_wait(bars + ubar(s >> 1), upar(s >> 1)); };
    auto block = [&](int b, int sn) {
        const int u = b >> 1, h = b & 1;
        const bool next = b + 1 < 2 * NU;
        convert(u % NW, h, sn == 2 || sn >= 4, sn == 2 ? ebar + 8 : full + 8 * (sn % 12), (sn / 12) & 1,
                next && (h || b < 8), b == 5 ? rawh + 24 : rawfull + 8 * rslot((b + 1) >> 1), b == 5 ? 0 : rpar((b + 1) >> 1),
                next, rslot((b + 1) >> 1), true, sig_bar(b), (b & 3) == 3 && next, sslot((b + 1) >> 2));
    };
    auto hand = [&](int b, auto extra) {
        const int u = b >> 1;
        hand_over(sig_bar(b), sig_par(b), u % NW, b & 1, (b & 3) == 0 ? 32768 : (b & 3) == 2 && b < 36 ? 448 : b == SN0 + 3 ? 16 : 0, (b & 1) && u + NR < NU, u + NR, rslot(u), extra);
    };
    auto pass_on = [&](int u) {
        fence_async_smem();
        __syncwarp();
        if (elect()) {
            const uint32_t o = wpos * 512 + u * UNIT;
            copy_to_peer(pwhalf + o, whalf + o, 512, pbars + 216 + 8 * u);
            copy_to_peer(pwhalf + o + 3584, whalf + o + 3584, 512, pbars + 216 + 8 * u);
            if (u == 1) mbar_arrive(sig_bar(3));
            mbar_expect_tx(ebar + 8 * u, 1024);
        }
        __syncwarp();
    };
    bool ok0 = false;
    if (warp < 7) {
        lut.lo[0] = __byte_perm(c0.x, c0.y, 0x6420); lut.hi[0] = __byte_perm(c0.x, c0.y, 0x7531);
        lut.lo[1] = __byte_perm(c0.z, c0.w, 0x6420); lut.hi[1] = __byte_perm(c0.z, c0.w, 0x7531);
        lut.lo[2] = __byte_perm(c1.x, c1.y, 0x6420); lut.hi[2] = __byte_perm(c1.x, c1.y, 0x7531);
        lut.lo[3] = __byte_perm(c1.z, c1.w, 0x6420); lut.hi[3] = __byte_perm(c1.z, c1.w, 0x7531);
        const uint32_t d = wown + (lane >> 3) * 128 + (lane & 3) * 16 + (lane & 4) * 2;
#pragma unroll
        for (int j = 0; j < 4; j++) {
            uint32_t a, b;
            lookup4(pack4(q[j]), lut, a, b);
            asm volatile("st.shared.v2.b32 [%0], {%1, %2};" ::"r"(d + (j >> 1) * 3584 + (j & 1) * 64), "r"(mul_bf16x2(a, sf.x)), "r"(mul_bf16x2(b, sf.y)) : "memory");
        }
        TSL(33);
        cluster_wait();
        pass_on(0);
        TSL(34);
        mbar_wait(rawh + 8, 0);
        const uint4 a0 = lds128(rsrc + roff(rslot(1))), a1 = lds128((rsrc ^ 16) + roff(rslot(1))), s0 = get_sc(sslot(0));
        mbar_wait(rawfull + 8 * rslot(1), 0);
        const uint4 a2 = lds128(rsrc + roff(rslot(1)) + 7168), a3 = lds128((rsrc ^ 16) + roff(rslot(1)) + 7168);
        sts128(wdst + UNIT, dequant8(pack4(a0), pack4(a1), s0, lut));
        sts128(wdst + UNIT + 3584, dequant8(pack4(a2), pack4(a3), s0, lut));
        ok0 = mbar_try(xbar + 8 * wg, 0) & mbar_try(ebar, 0);
        pass_on(1);
    }
    TSL(31);
    mbar_wait2(xbar + 8 * wg, 0, ebar, 0, ok0);
    TSL(32);

    float acc0[112], acc1[112];
    const uint32_t descA = ((0x400 + wg * 16384) >> 4) | (1u << 16);
    auto mma = [&](int s) {
        const uint32_t da = opq(descA) + ((s >> 2) % 3) * (32768 >> 4) + (s & 3) * 2;
        wgmma_fence();
        wgmma224<1, 8>(acc0, da, bdesc(s)); wgmma224<1, 8>(acc1, da + 512, bdesc(s));
        wgmma_commit();
        wgmma_wait<2>();
    };
    wgmma_fence();
    wgmma224<0, 8>(acc0, descA, bdesc(0)); wgmma224<0, 8>(acc1, descA + 512, bdesc(0));
    wgmma_commit();
    TSL(0);
    mma(1); TSL(1);
    if (warp < 7) {
        mbar_wait(rawh + 16, 0); fetch(rslot(2), 0); sc = get_sc(sslot(1));
        block(4, -1); block(5, 2);
    } else {
        mbar_wait(sig_bar(3), sig_par(3));
        if (elect()) { load_raw(4, rslot(4)); load_x(2, 2, full + 64); prefetch_q(0); prefetch_x(3); prefetch_g(0); }
        __syncwarp();
        hand(4, [] {});
        mbar_wait(ebar + 8, 0);
    }
    static_for<2, 8>([&](auto S) {
        constexpr int s = S.value;
        mma(s); TSL(s);
        if (warp < 7) block(s + 4, s + 1);
        else {
            hand(s + 3, [&] {
                if (s == 4) prefetch_q(1);
                if (s == 5) { load_sc(4, sslot(4), full + 80); prefetch_g(1); }
                if (s == 6) prefetch_x(4);
                if (s == 7) load_x(3, 0, full);
            });
            if (s >= 3) see(s + 1);
        }
    });
    {
        uint32_t ph = 0;
#pragma unroll 1
        for (int cb = 2; cb < 8; cb += 3)
          static_for<2, 5>([&](auto I) {
            constexpr int cc = I.value;
            constexpr int j0 = cc % 3, j1 = (cc + 1) % 3, j2 = (cc + 2) % 3;
            const int c = cb + cc - 2;
            auto sh = [&](int h) {
                if ((cc - G1 + 1) % 3 == 0 && h == 1 && c == G1 - 1) share(G1, 0, 3584);
                if ((cc - G1) % 3 == 0 && c == G1) share(G1, h ? UNIT : 3584, 3584);
                if ((cc - G1 - 1) % 3 == 0 && c == G1 + 1) {
                    if (h == 0) { share(G1, UNIT + 3584, 3584); bulk_wait_read<1>(); }
                    else publish(0);
                }
                if ((cc - G2 + 1) % 3 == 0 && h == 1 && c == G2 - 1) share(G2, 0, 3584);
            };
            if (cc == 2) TSL(c < 8 ? 36 : 37);
            mma(4 * j0); TSL(cb == TLIT ? 4 * cc : 30);
            if (warp < 7) convert(2 * j1, 0, true, full + 32 * j0 + 8, ph, false, 0, 0, true, j1, true, sig_bar(4 * cc + 4), false, 0);
            else {
                const bool ok = mbar_try(full + 32 * j0 + 8, ph);
                hand_over(sig_bar(4 * cc + 3), sig_par(4 * cc + 3), 2 * j0 + 1, 1, 0, true, 2 * c + 4, j2, [&] { prefetch_q(c); });
                mbar_wait1(full + 32 * j0 + 8, ph, ok);
            }
            mma(4 * j0 + 1); TSL(cb == TLIT ? 4 * cc + 1 : 30);
            if (warp < 7) convert(2 * j1, 1, true, full + 32 * j0 + 16, ph, true, rawfull + 8 * j0, rpar(2 * cc + 3), true, j0, true, sig_bar(4 * cc + 5), false, 0);
            else {
                const bool ok = mbar_try(full + 32 * j0 + 16, ph);
                hand_over(sig_bar(4 * cc + 4), sig_par(4 * cc + 4), 2 * j1, 0, 32768, false, 0, 0, [&] { load_sc(c + 3, j0, full + 32 * j1 + 16); prefetch_g(c); sh(0); });
                mbar_wait1(full + 32 * j0 + 16, ph, ok);
            }
            mma(4 * j0 + 2); TSL(cb == TLIT ? 4 * cc + 2 : 30);
            if (warp < 7) convert(2 * j1 + 1, 0, true, full + 32 * j0 + 24, ph, false, 0, 0, true, j0, true, sig_bar(4 * cc + 6), false, 0);
            else {
                const bool ok = mbar_try(full + 32 * j0 + 24, ph);
                hand_over(sig_bar(4 * cc + 5), sig_par(4 * cc + 5), 2 * j1, 1, 0, true, 2 * c + 5, j1, [&] { prefetch_x(c + PFX); });
                mbar_wait1(full + 32 * j0 + 24, ph, ok);
            }
            if (j1 == 0) asm volatile("xor.b32 %0, %0, 1;" : "+r"(ph));
            mma(4 * j0 + 3); TSL(cb == TLIT ? 4 * cc + 3 : 30);
            if (warp < 7) convert(2 * j1 + 1, 1, true, full + 32 * j1, ph, true, rawfull + 8 * j2, rpar(2 * cc + 4), true, j2, true, sig_bar(4 * cc + 7), true, j2);
            else {
                const bool ok = mbar_try(full + 32 * j1, ph);
                hand_over(sig_bar(4 * cc + 6), sig_par(4 * cc + 6), 2 * j1 + 1, 0, 448, false, 0, 0, [&] { load_x(c + 2, j2, full + 32 * j2); sh(1); });
                mbar_wait1(full + 32 * j1, ph, ok);
            }
          });
    }
    uint4 fa[8];
    auto get_frag = [&](int f, uint32_t rows, int j0 = 0, int j1 = 4) {
        int ln; asm volatile("mov.u32 %0, %%laneid;" : "=r"(ln));
        const uint32_t a = rows + (ln & 15) * 128 + (((ln >> 4) ^ (ln & 7)) << 4);
#pragma unroll
        for (int j = j0; j < j1; j++) fa[4 * f + j] = ldmatrix_x4(a ^ (j * 32));
    };
    static_assert(NG == 2 && G2 == 8 && G1 <= 6, "");
    static_for<32, 46>([&](auto S) {
        constexpr int s = S.value;
        constexpr int vb = 40 + (s - 37) / 2;
        mma(s);
        if (TLIT == 99) TSL(s - 26);
        if (s == 39) cluster_arrive();
        if (s == 41) cluster_wait();
        if (s == 36) mbar_wait(rawh + 8, 1);
        if (s >= 36 && s < 40) get_frag(0, sbase + uoff(24) + wg * (uoff(23) - uoff(24)) + (warp & 3) * 2048, s - 36, s - 35);
        if (warp < 7) {
            if (s < 36) block(s + 4, s + 1);
            else {
                if (s & 1) signal(sig_bar(vb));
                if (s < 39 || (s & 1)) see(s + 1);
            }
        } else {
            auto loads = [&] {
                if (s == 32) { share(G2, 3584, 3584); prefetch_x(11); }
                if (s == 33) {
                    mbar_expect_tx(rawh + 8, 16384);
                    tma_load_2d(sbase + uoff(24), &tmx64, chunk(12) * 64, mt * BM + 64, rawh + 8);
                    tma_load_2d(sbase + uoff(23), &tmx64, chunk(12) * 64, mt * BM + 192, rawh + 8);
                    share(G2, UNIT, 3584);
                }
                if (s == 34) share(G2, UNIT + 3584, 3584);
                if (s == 36) publish(1);
                if (s == 37) { prefetch_x(12); prefetch_x(13); }
                if (s == 39) snap(1, bars + ubar(21));
                if (s == 41) { prefetch_x(14); prefetch_x(15); }
                if (s == 43) { load_l(12, 0, 0, bars + ubar(24)); load_l(12, 0, 1, bars + ubar(24)); }
                else if ((s & 3) == 3) load_x((s >> 2) + 2, ((s >> 2) + 2) % 3, bars + ubar(2 * (s >> 2) + 4));
                if (s == 44) {
                    asm volatile("prefetch.tensormap [%0];" ::"l"(&tmo64) : "memory");
                    asm volatile("prefetch.tensormap [%0];" ::"l"(&tmo32) : "memory");
                }
                if (s == 45) { mbar_expect_tx(xbar, 16384); load_l(14, 1, 0, xbar); }
                static_for<NU, 31>([&](auto V) { if constexpr (utime(V.value) == (s == 45 ? 46 : s)) load_w(V.value); });
            };
            if (s == SN0) { if (elect()) snap(0, full + 8 * ((SN0 + 3) % 12)); __syncwarp(); }
            if (s == CK0) check(0, 0);
            if (s == 42) check(1, 1);
            if (s <= 36) hand(s + 3, loads);
            else {
                if (!(s & 1)) mbar_wait(sig_bar(40 + (s - 38) / 2), sig_par(40 + (s - 38) / 2));
                if (s == 45) mbar_wait(sig_bar(vb), sig_par(vb));
                if (elect()) loads();
                __syncwarp();
            }
            if (s < 39 || (s & 1)) see(s + 1);
        }
    });
    if (wg == 1) bar_sync(8);
    mma(46);
    if (warp == 7) {
        wgmma_wait<1>();
        see(48);
        if (elect()) { load_w(31); mbar_expect_tx(xbar + 8, 16384); load_l(14, 1, 1, xbar + 8); }
        __syncwarp();
    }
    mma(47);
    if (wg == 0) bar_arrive(8);
    const uint32_t slice0 = sbase + wg * 16384 + (warp & 3) * 2048;
    auto slc = [&](int p) { return slice0 + (p >> 1) * 32768 + (p & 1) * 8192; };
    const int row0 = mt * BM + wg * 128 + (warp & 3) * 16, odd = nt & 1;
    const int colL = nt * BN + odd * 96, colA = nt * BN + (odd ? 32 : 128), colB = nt * BN + (odd ? 0 : 192);
    auto load_s = [&](int i, int p, uint32_t bar) { tma_load_2d(slc(p), &tmx16, chunk(i) * 64, row0 + 64, bar); };
    const uint32_t tA = opq(descA);
    see(48);
    wgmma_wait<0>();
    RT(0);
    float lo0[64], hi0[48], lo1[64], hi1[48];
#pragma unroll
    for (int i = 0; i < 64; i++) { asm volatile("mov.b32 %0, %1;" : "=f"(lo0[i]) : "f"(acc0[i])); asm volatile("mov.b32 %0, %1;" : "=f"(lo1[i]) : "f"(acc1[i])); }
#pragma unroll
    for (int i = 0; i < 48; i++) { asm volatile("mov.b32 %0, %1;" : "=f"(hi0[i]) : "f"(acc0[64 + i])); asm volatile("mov.b32 %0, %1;" : "=f"(hi1[i]) : "f"(acc1[64 + i])); }
    auto tdesc = [&](int p, int s) { return tA + (p >> 1) * (32768 >> 4) + (p & 1) * 512 + (s & 3) * 2; };
    auto ldesc = [&](int s) { return tdesc(s >> 2, s); };
    auto gdesc = [&](int s) { return tdesc(((s >> 2) + 3) % 6, s); };
    if (wg == 1) { mbar_wait(xbar + 8, 1); bar_sync(1); }
    static_for<0, 8>([&](auto V) {
        constexpr int v = 24 + (V.value == 0 || V.value > 3 ? V.value : V.value == 3 ? 1 : V.value + 1), s = 2 * (v - 24);
        if (v == 26) mbar_wait2(bars + ubar(26), upar(26), bars + ubar(27), upar(27), wg);
        else if (v == 28) mbar_wait2(bars + ubar(28), upar(28), xbar, 1, wg);
        else if (v != 24 && v != 27) mbar_wait1(bars + ubar(v), upar(v), wg);
        wgmma_fence();
        wgmma96<1, 8>(hi0, ldesc(s), bdesc(48 + s) + 128);
        wgmma96<1, 8>(hi0, ldesc(s + 1), bdesc(49 + s) + 128);
    });
    wgmma_commit();
    bar_arrive(1 + wg);
    wgmma_wait<0>();
    RT(1);
    stage_cols<64, 0>(hi0, slc(4)); send(slc(4), &tmo64, colA, row0);
    stage_cols<32, 32>(hi0, slc(5));
    RT(2);
    bar_sync(2 + wg);
    RT(3);
    wgmma_fence();
    static_for<0, 7>([&](auto S) { wgmma128<1, 8>(lo0, ldesc(S.value), bdesc(48 + S.value)); });
    wgmma_commit();
    send(slc(5), &tmo32, colB, row0);
    wgmma_fence();
    static_for<7, 16>([&](auto S) { wgmma128<1, 8>(lo0, ldesc(S.value), bdesc(48 + S.value)); });
    wgmma_commit();
    bar_arrive(3 + wg);
    RT(4);
    {
        const uint32_t zero = opq(gridDim.x - 2);
#pragma unroll
        for (int j = 0; j < 4; j++) { fa[j].x ^= zero; fa[j].y ^= zero; fa[j].z ^= zero; fa[j].w ^= zero; asm volatile("" : "+r"(fa[j].x), "+r"(fa[j].y), "+r"(fa[j].z), "+r"(fa[j].w)); }
    }
    if (elect()) { mbar_expect_tx(gbar, 4096); bulk_wait_read<0>(); load_s(13, 4, gbar); load_s(14, 5, gbar); }
    __syncwarp();
    wgmma_wait<0>();
    RT(5);
    stage_cols<64, 0>(lo0, slc(2));
    if (elect()) { mbar_expect_tx(gbar + 8, 2048); load_s(15, 0, gbar + 8); }
    __syncwarp();
    const bool okg = mbar_try(gbar, 0);
    send(slc(2), &tmo64, colL, row0);
    stage_cols<64, 32>(lo0, slc(3));
    mbar_wait1(gbar, 0, okg);
    RT(6);
    auto mma2 = [&](auto I) { constexpr int s = I.value; if constexpr (s < 4) wgmma128r<8>(lo1, fa[s], bdesc(48 + s)); else wgmma128<1, 8>(lo1, gdesc(s), bdesc(48 + s)); };
    auto mma3 = [&](auto I) { constexpr int s = I.value; if constexpr (s < 8) wgmma96r<8>(hi1, fa[s], bdesc(48 + s) + 128); else wgmma96<1, 8>(hi1, gdesc(s), bdesc(48 + s) + 128); };
    bar_sync(4 + wg);
    RT(7);
    wgmma_fence();
    static_for<0, 8>(mma2);
    wgmma_commit();
    const bool okg2 = mbar_try(gbar + 8, 0);
    send(slc(3), &tmo64, colL + 64, row0);
    mbar_wait1(gbar + 8, 0, okg2);
    wgmma_fence();
    static_for<8, 16>(mma2);
    wgmma_commit();
    bar_arrive(5 + wg);
    RT(8);
    get_frag(1, slc(4));
    if (elect()) bulk_wait_read<1>();
    __syncwarp();
    wgmma_wait<0>();
    RT(9);
    stage_cols<64, 0>(lo1, slc(1)); send(slc(1), &tmo64, colL, row0 + 64);
    stage_cols<64, 32>(lo1, slc(2));
    RT(10);
    bar_sync(6 + wg);
    RT(11);
    wgmma_fence();
    static_for<0, GG3>(mma3);
    wgmma_commit();
    send(slc(2), &tmo64, colL + 64, row0 + 64);
    wgmma_fence();
    static_for<GG3, 16>(mma3);
    wgmma_commit();
    if (wg == 0) bar_arrive(7);
    RT(12);
    wgmma_wait<0>();
    RT(13);
    stage_cols<64, 0>(hi1, slc(4)); send(slc(4), &tmo64, colA, row0 + 64);
    stage_cols<32, 32>(hi1, slc(5)); send(slc(5), &tmo32, colB, row0 + 64);
    RT(14);
    if (elect()) bulk_wait_read<0>();
    __syncwarp();
    RT(15);
    TSW(wg * 4, 38 + wg);
    TS_DUMP();
    TL_DUMP();
}

typedef CUresult (*EncodeFn)(CUtensorMap*, CUtensorMapDataType, cuuint32_t, void*, const cuuint64_t*, const cuuint64_t*,
                             const cuuint32_t*, const cuuint32_t*, CUtensorMapInterleave, CUtensorMapSwizzle,
                             CUtensorMapL2promotion, CUtensorMapFloatOOBfill);

extern "C" void kernel_launch(void* const* d_in, const int* in_sizes, int n_in, void* d_out, int out_size) {
    const __nv_bfloat16* x = (const __nv_bfloat16*)d_in[0];
    const int* qw = (const int*)d_in[1];
    const __nv_bfloat16* cb = (const __nv_bfloat16*)d_in[2];
    const __nv_bfloat16* absmax = (const __nv_bfloat16*)d_in[3];
    static EncodeFn encode = nullptr;
    static void *wimg = nullptr, *gflag = nullptr;
    if (!encode) {
        cudaGetSymbolAddress(&wimg, g_wimg);
        cudaGetSymbolAddress(&gflag, g_flag);
        void* fn = nullptr;
        cudaDriverEntryPointQueryResult qr;
        cudaGetDriverEntryPoint("cuTensorMapEncodeTiled", &fn, cudaEnableDefault, &qr);
        encode = (EncodeFn)fn;
        cudaFuncSetAttribute(nf4_gemm_kernel, cudaFuncAttributeMaxDynamicSharedMemorySize, SMEM_BYTES);
    }
    CUtensorMap tmx, tmq, tmo64, tmo32, tmqp, tmx16, tmx64, tmq1;
    {
        cuuint64_t dims[2] = {(cuuint64_t)K_, (cuuint64_t)M_};
        cuuint64_t strides[1] = {(cuuint64_t)K_ * 2};
        cuuint32_t box[2] = {64, 128};
        cuuint32_t es[2] = {1, 1};
        encode(&tmx, CU_TENSOR_MAP_DATA_TYPE_BFLOAT16, 2, (void*)x, dims, strides, box, es, CU_TENSOR_MAP_INTERLEAVE_NONE,
               CU_TENSOR_MAP_SWIZZLE_128B, CU_TENSOR_MAP_L2_PROMOTION_L2_128B, CU_TENSOR_MAP_FLOAT_OOB_FILL_NONE);
        box[1] = 64;
        encode(&tmx64, CU_TENSOR_MAP_DATA_TYPE_BFLOAT16, 2, (void*)x, dims, strides, box, es, CU_TENSOR_MAP_INTERLEAVE_NONE,
               CU_TENSOR_MAP_SWIZZLE_128B, CU_TENSOR_MAP_L2_PROMOTION_L2_128B, CU_TENSOR_MAP_FLOAT_OOB_FILL_NONE);
        box[1] = 16;
        encode(&tmx16, CU_TENSOR_MAP_DATA_TYPE_BFLOAT16, 2, (void*)x, dims, strides, box, es, CU_TENSOR_MAP_INTERLEAVE_NONE,
               CU_TENSOR_MAP_SWIZZLE_128B, CU_TENSOR_MAP_L2_PROMOTION_L2_128B, CU_TENSOR_MAP_FLOAT_OOB_FILL_NONE);
    }
    {
        cuuint64_t dims[5] = {32, 8, (cuuint64_t)(N_ / 32), 2, (cuuint64_t)(K_ / 16)};
        cuuint64_t strides[4] = {(cuuint64_t)N_ * 4, 128, (cuuint64_t)N_ * 4 * 8, (cuuint64_t)N_ * 4 * 16};
        cuuint32_t box[5] = {32, 8, 7, 1, 2};
        cuuint32_t es[5] = {1, 1, 1, 1, 1};
        encode(&tmq, CU_TENSOR_MAP_DATA_TYPE_INT32, 5, (void*)qw, dims, strides, box, es, CU_TENSOR_MAP_INTERLEAVE_NONE,
               CU_TENSOR_MAP_SWIZZLE_128B, CU_TENSOR_MAP_L2_PROMOTION_L2_128B, CU_TENSOR_MAP_FLOAT_OOB_FILL_NONE);
        box[4] = 1;
        encode(&tmq1, CU_TENSOR_MAP_DATA_TYPE_INT32, 5, (void*)qw, dims, strides, box, es, CU_TENSOR_MAP_INTERLEAVE_NONE,
               CU_TENSOR_MAP_SWIZZLE_128B, CU_TENSOR_MAP_L2_PROMOTION_L2_128B, CU_TENSOR_MAP_FLOAT_OOB_FILL_NONE);
        cuuint64_t dims2[2] = {(cuuint64_t)N_, (cuuint64_t)K_};
        cuuint32_t box2[2] = {224, 8};
        encode(&tmqp, CU_TENSOR_MAP_DATA_TYPE_INT32, 2, (void*)qw, dims2, strides, box2, es, CU_TENSOR_MAP_INTERLEAVE_NONE,
               CU_TENSOR_MAP_SWIZZLE_NONE, CU_TENSOR_MAP_L2_PROMOTION_L2_128B, CU_TENSOR_MAP_FLOAT_OOB_FILL_NONE);
    }
    {
        cuuint64_t dims[2] = {(cuuint64_t)N_, (cuuint64_t)M_};
        cuuint64_t strides[1] = {(cuuint64_t)N_ * 2};
        cuuint32_t box[2] = {64, 16};
        cuuint32_t es[2] = {1, 1};
        encode(&tmo64, CU_TENSOR_MAP_DATA_TYPE_BFLOAT16, 2, d_out, dims, strides, box, es, CU_TENSOR_MAP_INTERLEAVE_NONE,
               CU_TENSOR_MAP_SWIZZLE_128B, CU_TENSOR_MAP_L2_PROMOTION_NONE, CU_TENSOR_MAP_FLOAT_OOB_FILL_NONE);
        box[0] = 32;
        encode(&tmo32, CU_TENSOR_MAP_DATA_TYPE_BFLOAT16, 2, d_out, dims, strides, box, es, CU_TENSOR_MAP_INTERLEAVE_NONE,
               CU_TENSOR_MAP_SWIZZLE_64B, CU_TENSOR_MAP_L2_PROMOTION_NONE, CU_TENSOR_MAP_FLOAT_OOB_FILL_NONE);
    }
    nf4_gemm_kernel<<<dim3(2, 16, 4), 256, SMEM_BYTES>>>(qw, cb, absmax, (uint8_t*)wimg, (unsigned*)gflag, tmx, tmq, tmo64, tmo32, tmqp, tmx16, tmx64, tmq1);
}
```

```cpp
#include <cuda_runtime.h>
#include <cuda_bf16.h>
#include <cuda.h>
#include <stdint.h>

#define NG 2
#define G1 5
#define G2 8
#define PFG 0
#define GG3 6
#define RAWFIRST 1
#define SN0 32
#define CK0 35
#define PFS 1
#define PF12 7
#define FS 36
#define SHE 0
#define PB1 37
#define FD 3
#define DP 0
#define OR1 0
#define XB 0
#define T2 900
#define T2B 1300
#define T3 1700
#define TLPRO -2
#define TLIT 2
constexpr int M_ = 2048, K_ = 1024, N_ = 3584;
constexpr int BM = 256, BN = 224;
constexpr int UNIT = 14336;
constexpr int NW = 6, NR = 3;
constexpr int NU = 32 - 6 * NG;
constexpr int NC = 16 - 4 * NG;
constexpr int CE = NU / 2 - 2;
#define PFQ 4
constexpr int PFX = 3;
constexpr int RAW_OFF = 3 * 32768;
constexpr int SC_OFF = RAW_OFF + 2 * UNIT;
constexpr int SC_STRIDE = 464;
constexpr int W_OFF = 127 * 1024;
constexpr int RAW2_OFF = W_OFF + NW * UNIT;
constexpr int BAR_OFF = RAW2_OFF + UNIT;
constexpr int SMEM_BYTES = BAR_OFF + 320;
__device__ __align__(1024) uint8_t g_wimg[16 * 8 * NG * UNIT];
__device__ __align__(128) unsigned g_flag[16 * 32];

#define TSL(i)
#define TL_DUMP()
#define TSW(w, i)
#define TS_INIT()
#define TS_DUMP()
#define RT(i)
#define TSB(i)

__device__ __forceinline__ uint32_t smem_u32(const void* p) { return (uint32_t)__cvta_generic_to_shared(p); }
__device__ __forceinline__ bool elect() {
    uint32_t ok;
    asm volatile("{\n.reg .pred p;\nelect.sync _|p, 0xffffffff;\nselp.u32 %0, 1, 0, p;\n}\n" : "=r"(ok));
    return ok != 0;
}
__device__ __forceinline__ void mbar_init(uint32_t bar, uint32_t cnt) { asm volatile("mbarrier.init.shared::cta.b64 [%0], %1;" ::"r"(bar), "r"(cnt) : "memory"); }
__device__ __forceinline__ void mbar_expect_tx(uint32_t bar, uint32_t bytes) { asm volatile("mbarrier.arrive.expect_tx.shared::cta.b64 _, [%0], %1;" ::"r"(bar), "r"(bytes) : "memory"); }
__device__ __forceinline__ void mbar_arrive(uint32_t bar) { asm volatile("mbarrier.arrive.shared::cta.b64 _, [%0];" ::"r"(bar) : "memory"); }
#define BOUNDED
#define WAIT_INIT "mov.u32 n, 0;\n"
#define WAIT_NEXT "@p bra.uni LAB_DONE;\nadd.u32 n, n, 1;\nsetp.lt.u32 p, n, 0x4000;\n@p bra.uni LAB_WAIT;\n"
__device__ __forceinline__ void mbar_wait(uint32_t bar, uint32_t parity) {
    asm volatile(
        "{\n.reg .pred p;\n.reg .u32 n;\n"
        WAIT_INIT
        "LAB_WAIT:\n"
        "mbarrier.try_wait.parity.shared::cta.b64 p, [%0], %1;\n"
        WAIT_NEXT
        "LAB_DONE:\n}\n" ::"r"(bar), "r"(parity) : "memory");
}
__device__ __forceinline__ bool mbar_try(uint32_t bar, uint32_t parity) {
    uint32_t ok;
    asm volatile("{\n.reg .pred p;\nmbarrier.test_wait.parity.shared::cta.b64 p, [%1], %2;\nselp.u32 %0, 1, 0, p;\n}\n" : "=r"(ok) : "r"(bar), "r"(parity) : "memory");
    return ok != 0;
}
__device__ __forceinline__ void mbar_wait1(uint32_t b0, uint32_t p0, bool skip) {
    asm volatile(
        "{\n.reg .pred p;\n.reg .u32 n;\n"
        "setp.ne.u32 p, %2, 0;\n@p bra.uni LAB_DONE;\n"
        WAIT_INIT
        "LAB_WAIT:\n"
        "mbarrier.try_wait.parity.shared::cta.b64 p, [%0], %1;\n"
        WAIT_NEXT
        "LAB_DONE:\n}\n" ::"r"(b0), "r"(p0), "r"((uint32_t)skip) : "memory");
}
__device__ __forceinline__ void mbar_wait2(uint32_t b0, uint32_t p0, uint32_t b1, uint32_t p1, bool skip = false) {
    asm volatile(
        "{\n.reg .pred p, q;\n.reg .u32 n;\n"
        "setp.ne.u32 p, %4, 0;\n@p bra.uni LAB_DONE;\n"
        WAIT_INIT
        "LAB_WAIT:\n"
        "mbarrier.try_wait.parity.shared::cta.b64 p, [%0], %1;\n"
        "mbarrier.try_wait.parity.shared::cta.b64 q, [%2], %3;\n"
        "and.pred p, p, q;\n"
        WAIT_NEXT
        "LAB_DONE:\n}\n" ::"r"(b0), "r"(p0), "r"(b1), "r"(p1), "r"((uint32_t)skip) : "memory");
}
__device__ __forceinline__ void tma_load_2d(uint32_t dst, const CUtensorMap* tm, int c0, int c1, uint32_t bar) {
    asm volatile("cp.async.bulk.tensor.2d.shared::cluster.global.mbarrier::complete_tx::bytes [%0], [%1, {%2, %3}], [%4];"
                 ::"r"(dst), "l"(tm), "r"(c0), "r"(c1), "r"(bar) : "memory");
}
__device__ __forceinline__ void tma_load_5d(uint32_t dst, const CUtensorMap* tm, int c0, int c1, int c2, int c3, int c4, uint32_t bar) {
    asm volatile("cp.async.bulk.tensor.5d.shared::cluster.global.mbarrier::complete_tx::bytes [%0], [%1, {%2, %3, %4, %5, %6}], [%7];"
                 ::"r"(dst), "l"(tm), "r"(c0), "r"(c1), "r"(c2), "r"(c3), "r"(c4), "r"(bar) : "memory");
}
__device__ __forceinline__ void tma_prefetch_2d(const CUtensorMap* tm, int c0, int c1) {
    asm volatile("cp.async.bulk.prefetch.tensor.2d.L2.global [%0, {%1, %2}];" ::"l"(tm), "r"(c0), "r"(c1) : "memory");
}
__device__ __forceinline__ void bulk_load(uint32_t dst, const void* src, uint32_t bytes, uint32_t bar) {
    asm volatile("cp.async.bulk.shared::cluster.global.mbarrier::complete_tx::bytes [%0], [%1], %2, [%3];"
                 ::"r"(dst), "l"(src), "r"(bytes), "r"(bar) : "memory");
}
__device__ __forceinline__ void cluster_arrive() { asm volatile("barrier.cluster.arrive.relaxed.aligned;" ::: "memory"); }
__device__ __forceinline__ void cluster_wait() { asm volatile("barrier.cluster.wait.acquire.aligned;" ::: "memory"); }
__device__ __forceinline__ uint32_t mapa(uint32_t addr, uint32_t cta) {
    uint32_t r; asm("mapa.shared::cluster.u32 %0, %1, %2;" : "=r"(r) : "r"(addr), "r"(cta)); return r;
}
__device__ __forceinline__ void copy_to_peer(uint32_t cdst, uint32_t src, uint32_t bytes, uint32_t cbar) {
    asm volatile("cp.async.bulk.shared::cluster.shared::cta.mbarrier::complete_tx::bytes [%0], [%1], %2, [%3];"
                 ::"r"(cdst), "r"(src), "r"(bytes), "r"(cbar) : "memory");
}
__device__ __forceinline__ void wgmma_fence() { asm volatile("wgmma.fence.sync.aligned;" ::: "memory"); }
__device__ __forceinline__ void wgmma_commit() { asm volatile("wgmma.commit_group.sync.aligned;" ::: "memory"); }
template <int N> __device__ __forceinline__ void wgmma_wait() { asm volatile("wgmma.wait_group.sync.aligned %0;" ::"n"(N) : "memory"); }
__device__ __forceinline__ uint32_t pack_bf16(float lo, float hi) {
    uint32_t r; asm("cvt.rn.bf16x2.f32 %0, %1, %2;" : "=r"(r) : "f"(hi), "f"(lo)); return r;
}
__device__ __forceinline__ void stmatrix_x4(uint32_t addr, uint32_t a, uint32_t b, uint32_t c, uint32_t d) {
    asm volatile("stmatrix.sync.aligned.m8n8.x4.shared.b16 [%0], {%1, %2, %3, %4};" ::"r"(addr), "r"(a), "r"(b), "r"(c), "r"(d) : "memory");
}
__device__ __forceinline__ uint4 ldmatrix_x4(uint32_t a) {
    uint4 v; asm volatile("ldmatrix.sync.aligned.m8n8.x4.shared.b16 {%0, %1, %2, %3}, [%4];" : "=r"(v.x), "=r"(v.y), "=r"(v.z), "=r"(v.w) : "r"(a) : "memory"); return v;
}
__device__ __forceinline__ uint4 lds128(uint32_t a) {
    uint4 v; asm volatile("ld.shared.v4.b32 {%0, %1, %2, %3}, [%4];" : "=r"(v.x), "=r"(v.y), "=r"(v.z), "=r"(v.w) : "r"(a) : "memory"); return v;
}
__device__ __forceinline__ void sts128(uint32_t a, uint4 v) {
    asm volatile("st.shared.v4.b32 [%0], {%1, %2, %3, %4};" ::"r"(a), "r"(v.x), "r"(v.y), "r"(v.z), "r"(v.w) : "memory");
}
__device__ __forceinline__ uint4 ldg128(const void* p) {
    uint4 v; asm volatile("ld.global.nc.v4.b32 {%0, %1, %2, %3}, [%4];" : "=r"(v.x), "=r"(v.y), "=r"(v.z), "=r"(v.w) : "l"(p) : "memory"); return v;
}
__device__ __forceinline__ unsigned clk() { unsigned c; asm volatile("mov.u32 %0, %%clock;" : "=r"(c) :: "memory"); return c; }
__device__ __forceinline__ uint32_t mul_bf16x2(uint32_t a, uint32_t b) { uint32_t r; asm("mul.rn.bf16x2 %0, %1, %2;" : "=r"(r) : "r"(a), "r"(b)); return r; }
struct Lut { uint32_t lo[4], hi[4]; };
__device__ __forceinline__ uint32_t prmt(uint32_t a, uint32_t b, uint32_t s) { uint32_t r; asm("prmt.b32 %0, %1, %2, %3;" : "=r"(r) : "r"(a), "r"(b), "r"(s)); return r; }
__device__ __forceinline__ uint32_t pack4(const uint4& q) {
    uint32_t ab, cd, p;
    asm volatile("mad.lo.u32 %0, %1, 16, %2;" : "=r"(ab) : "r"(q.y), "r"(q.x));
    asm volatile("mad.lo.u32 %0, %1, 16, %2;" : "=r"(cd) : "r"(q.w), "r"(q.z));
    asm volatile("mad.lo.u32 %0, %1, 256, %2;" : "=r"(p) : "r"(cd), "r"(ab));
    return p;
}
__device__ __forceinline__ void lookup4(uint32_t p, const Lut& t, uint32_t& w01, uint32_t& w23) {
    const uint32_t t8 = p & 0x8888u, s7 = p & 0x7777u;
    const uint32_t sel = (t8 >> 1) + 0x3210u;
    const uint32_t lo = prmt(prmt(t.lo[0], t.lo[1], p), prmt(t.lo[2], t.lo[3], s7), sel);
    const uint32_t hi = prmt(prmt(t.hi[0], t.hi[1], p), prmt(t.hi[2], t.hi[3], s7), sel);
    w01 = prmt(lo, hi, 0x5140);
    w23 = prmt(lo, hi, 0x7362);
}
__device__ __forceinline__ uint4 dequant8(uint32_t p0, uint32_t p1, const uint4& sc, const Lut& t) {
    uint4 r;
    lookup4(p0, t, r.x, r.y);
    lookup4(p1, t, r.z, r.w);
    r.x = mul_bf16x2(r.x, sc.x); r.y = mul_bf16x2(r.y, sc.y); r.z = mul_bf16x2(r.z, sc.z); r.w = mul_bf16x2(r.w, sc.w);
    return r;
}
__device__ __forceinline__ void fence_async_smem() { asm volatile("fence.proxy.async.shared::cta;" ::: "memory"); }

template <int SCALE_D, int BHI, uint32_t AHI = 0x40000040u>
__device__ __forceinline__ void wgmma224(float (&d)[112], uint32_t descA, uint32_t descB) {
    asm volatile(
        "{\n.reg .pred p;\n.reg .b64 da, db;\nsetp.ne.b32 p, %114, 0;\n"
        "mov.b64 da, {%112, %116};\nmov.b64 db, {%113, %115};\n"
        "wgmma.mma_async.sync.aligned.m64n224k16.f32.bf16.bf16 "
        "{%0, %1, %2, %3, %4, %5, %6, %7, %8, %9, %10, %11, %12, %13, %14, %15, "
        "%16, %17, %18, %19, %20, %21, %22, %23, %24, %25, %26, %27, %28, %29, %30, %31, "
        "%32, %33, %34, %35, %36, %37, %38, %39, %40, %41, %42, %43, %44, %45, %46, %47, "
        "%48, %49, %50, %51, %52, %53, %54, %55, %56, %57, %58, %59, %60, %61, %62, %63, "
        "%64, %65, %66, %67, %68, %69, %70, %71, %72, %73, %74, %75, %76, %77, %78, %79, "
        "%80, %81, %82, %83, %84, %85, %86, %87, %88, %89, %90, %91, %92, %93, %94, %95, "
        "%96, %97, %98, %99, %100, %101, %102, %103, %104, %105, %106, %107, %108, %109, %110, %111}, "
        "da, db, p, 1, 1, 0, 1;\n}\n"
        : "+f"(d[0]), "+f"(d[1]), "+f"(d[2]), "+f"(d[3]), "+f"(d[4]), "+f"(d[5]), "+f"(d[6]), "+f"(d[7]),
          "+f"(d[8]), "+f"(d[9]), "+f"(d[10]), "+f"(d[11]), "+f"(d[12]), "+f"(d[13]), "+f"(d[14]), "+f"(d[15]),
          "+f"(d[16]), "+f"(d[17]), "+f"(d[18]), "+f"(d[19]), "+f"(d[20]), "+f"(d[21]), "+f"(d[22]), "+f"(d[23]),
          "+f"(d[24]), "+f"(d[25]), "+f"(d[26]), "+f"(d[27]), "+f"(d[28]), "+f"(d[29]), "+f"(d[30]), "+f"(d[31]),
          "+f"(d[32]), "+f"(d[33]), "+f"(d[34]), "+f"(d[35]), "+f"(d[36]), "+f"(d[37]), "+f"(d[38]), "+f"(d[39]),
          "+f"(d[40]), "+f"(d[41]), "+f"(d[42]), "+f"(d[43]), "+f"(d[44]), "+f"(d[45]), "+f"(d[46]), "+f"(d[47]),
          "+f"(d[48]), "+f"(d[49]), "+f"(d[50]), "+f"(d[51]), "+f"(d[52]), "+f"(d[53]), "+f"(d[54]), "+f"(d[55]),
          "+f"(d[56]), "+f"(d[57]), "+f"(d[58]), "+f"(d[59]), "+f"(d[60]), "+f"(d[61]), "+f"(d[62]), "+f"(d[63]),
          "+f"(d[64]), "+f"(d[65]), "+f"(d[66]), "+f"(d[67]), "+f"(d[68]), "+f"(d[69]), "+f"(d[70]), "+f"(d[71]),
          "+f"(d[72]), "+f"(d[73]), "+f"(d[74]), "+f"(d[75]), "+f"(d[76]), "+f"(d[77]), "+f"(d[78]), "+f"(d[79]),
          "+f"(d[80]), "+f"(d[81]), "+f"(d[82]), "+f"(d[83]), "+f"(d[84]), "+f"(d[85]), "+f"(d[86]), "+f"(d[87]),
          "+f"(d[88]), "+f"(d[89]), "+f"(d[90]), "+f"(d[91]), "+f"(d[92]), "+f"(d[93]), "+f"(d[94]), "+f"(d[95]),
          "+f"(d[96]), "+f"(d[97]), "+f"(d[98]), "+f"(d[99]), "+f"(d[100]), "+f"(d[101]), "+f"(d[102]), "+f"(d[103]),
          "+f"(d[104]), "+f"(d[105]), "+f"(d[106]), "+f"(d[107]), "+f"(d[108]), "+f"(d[109]), "+f"(d[110]), "+f"(d[111])
        : "r"(descA), "r"(descB), "n"(SCALE_D), "n"(BHI), "n"(AHI));
}

template <int SCALE_D, int BHI, uint32_t AHI = 0x40000040u>
__device__ __forceinline__ void wgmma128(float (&d)[64], uint32_t descA, uint32_t descB) {
    asm volatile(
        "{\n.reg .pred p;\n.reg .b64 da, db;\nsetp.ne.b32 p, %66, 0;\n"
        "mov.b64 da, {%64, %68};\nmov.b64 db, {%65, %67};\n"
        "wgmma.mma_async.sync.aligned.m64n128k16.f32.bf16.bf16 "
        "{%0, %1, %2, %3, %4, %5, %6, %7, %8, %9, %10, %11, %12, %13, %14, %15, "
        "%16, %17, %18, %19, %20, %21, %22, %23, %24, %25, %26, %27, %28, %29, %30, %31, "
        "%32, %33, %34, %35, %36, %37, %38, %39, %40, %41, %42, %43, %44, %45, %46, %47, "
        "%48, %49, %50, %51, %52, %53, %54, %55, %56, %57, %58, %59, %60, %61, %62, %63}, "
        "da, db, p, 1, 1, 0, 1;\n}\n"
        : "+f"(d[0]), "+f"(d[1]), "+f"(d[2]), "+f"(d[3]), "+f"(d[4]), "+f"(d[5]), "+f"(d[6]), "+f"(d[7]),
          "+f"(d[8]), "+f"(d[9]), "+f"(d[10]), "+f"(d[11]), "+f"(d[12]), "+f"(d[13]), "+f"(d[14]), "+f"(d[15]),
          "+f"(d[16]), "+f"(d[17]), "+f"(d[18]), "+f"(d[19]), "+f"(d[20]), "+f"(d[21]), "+f"(d[22]), "+f"(d[23]),
          "+f"(d[24]), "+f"(d[25]), "+f"(d[26]), "+f"(d[27]), "+f"(d[28]), "+f"(d[29]), "+f"(d[30]), "+f"(d[31]),
          "+f"(d[32]), "+f"(d[33]), "+f"(d[34]), "+f"(d[35]), "+f"(d[36]), "+f"(d[37]), "+f"(d[38]), "+f"(d[39]),
          "+f"(d[40]), "+f"(d[41]), "+f"(d[42]), "+f"(d[43]), "+f"(d[44]), "+f"(d[45]), "+f"(d[46]), "+f"(d[47]),
          "+f"(d[48]), "+f"(d[49]), "+f"(d[50]), "+f"(d[51]), "+f"(d[52]), "+f"(d[53]), "+f"(d[54]), "+f"(d[55]),
          "+f"(d[56]), "+f"(d[57]), "+f"(d[58]), "+f"(d[59]), "+f"(d[60]), "+f"(d[61]), "+f"(d[62]), "+f"(d[63])
        : "r"(descA), "r"(descB), "n"(SCALE_D), "n"(BHI), "n"(AHI));
}

template <int SCALE_D, int BHI, uint32_t AHI = 0x40000040u>
__device__ __forceinline__ void wgmma96(float (&d)[48], uint32_t descA, uint32_t descB) {
    asm volatile(
        "{\n.reg .pred p;\n.reg .b64 da, db;\nsetp.ne.b32 p, %50, 0;\n"
        "mov.b64 da, {%48, %52};\nmov.b64 db, {%49, %51};\n"
        "wgmma.mma_async.sync.aligned.m64n96k16.f32.bf16.bf16 "
        "{%0, %1, %2, %3, %4, %5, %6, %7, %8, %9, %10, %11, %12, %13, %14, %15, "
        "%16, %17, %18, %19, %20, %21, %22, %23, %24, %25, %26, %27, %28, %29, %30, %31, "
        "%32, %33, %34, %35, %36, %37, %38, %39, %40, %41, %42, %43, %44, %45, %46, %47}, "
        "da, db, p, 1, 1, 0, 1;\n}\n"
        : "+f"(d[0]), "+f"(d[1]), "+f"(d[2]), "+f"(d[3]), "+f"(d[4]), "+f"(d[5]), "+f"(d[6]), "+f"(d[7]),
          "+f"(d[8]), "+f"(d[9]), "+f"(d[10]), "+f"(d[11]), "+f"(d[12]), "+f"(d[13]), "+f"(d[14]), "+f"(d[15]),
          "+f"(d[16]), "+f"(d[17]), "+f"(d[18]), "+f"(d[19]), "+f"(d[20]), "+f"(d[21]), "+f"(d[22]), "+f"(d[23]),
          "+f"(d[24]), "+f"(d[25]), "+f"(d[26]), "+f"(d[27]), "+f"(d[28]), "+f"(d[29]), "+f"(d[30]), "+f"(d[31]),
          "+f"(d[32]), "+f"(d[33]), "+f"(d[34]), "+f"(d[35]), "+f"(d[36]), "+f"(d[37]), "+f"(d[38]), "+f"(d[39]),
          "+f"(d[40]), "+f"(d[41]), "+f"(d[42]), "+f"(d[43]), "+f"(d[44]), "+f"(d[45]), "+f"(d[46]), "+f"(d[47])
        : "r"(descA), "r"(descB), "n"(SCALE_D), "n"(BHI), "n"(AHI));
}

template <int BHI>
__device__ __forceinline__ void wgmma128r(float (&d)[64], const uint4& a, uint32_t descB) {
    asm volatile(
        "{\n.reg .pred p;\n.reg .b64 db;\nsetp.eq.b32 p, 0, 0;\n"
        "mov.b64 db, {%68, %69};\n"
        "wgmma.mma_async.sync.aligned.m64n128k16.f32.bf16.bf16 "
        "{%0, %1, %2, %3, %4, %5, %6, %7, %8, %9, %10, %11, %12, %13, %14, %15, "
        "%16, %17, %18, %19, %20, %21, %22, %23, %24, %25, %26, %27, %28, %29, %30, %31, "
        "%32, %33, %34, %35, %36, %37, %38, %39, %40, %41, %42, %43, %44, %45, %46, %47, "
        "%48, %49, %50, %51, %52, %53, %54, %55, %56, %57, %58, %59, %60, %61, %62, %63}, "
        "{%64, %65, %66, %67}, db, p, 1, 1, 1;\n}\n"
        : "+f"(d[0]), "+f"(d[1]), "+f"(d[2]), "+f"(d[3]), "+f"(d[4]), "+f"(d[5]), "+f"(d[6]), "+f"(d[7]),
          "+f"(d[8]), "+f"(d[9]), "+f"(d[10]), "+f"(d[11]), "+f"(d[12]), "+f"(d[13]), "+f"(d[14]), "+f"(d[15]),
          "+f"(d[16]), "+f"(d[17]), "+f"(d[18]), "+f"(d[19]), "+f"(d[20]), "+f"(d[21]), "+f"(d[22]), "+f"(d[23]),
          "+f"(d[24]), "+f"(d[25]), "+f"(d[26]), "+f"(d[27]), "+f"(d[28]), "+f"(d[29]), "+f"(d[30]), "+f"(d[31]),
          "+f"(d[32]), "+f"(d[33]), "+f"(d[34]), "+f"(d[35]), "+f"(d[36]), "+f"(d[37]), "+f"(d[38]), "+f"(d[39]),
          "+f"(d[40]), "+f"(d[41]), "+f"(d[42]), "+f"(d[43]), "+f"(d[44]), "+f"(d[45]), "+f"(d[46]), "+f"(d[47]),
          "+f"(d[48]), "+f"(d[49]), "+f"(d[50]), "+f"(d[51]), "+f"(d[52]), "+f"(d[53]), "+f"(d[54]), "+f"(d[55]),
          "+f"(d[56]), "+f"(d[57]), "+f"(d[58]), "+f"(d[59]), "+f"(d[60]), "+f"(d[61]), "+f"(d[62]), "+f"(d[63])
        : "r"(a.x), "r"(a.y), "r"(a.z), "r"(a.w), "r"(descB), "n"(BHI));
}

template <int BHI>
__device__ __forceinline__ void wgmma96r(float (&d)[48], const uint4& a, uint32_t descB) {
    asm volatile(
        "{\n.reg .pred p;\n.reg .b64 db;\nsetp.eq.b32 p, 0, 0;\n"
        "mov.b64 db, {%52, %53};\n"
        "wgmma.mma_async.sync.aligned.m64n96k16.f32.bf16.bf16 "
        "{%0, %1, %2, %3, %4, %5, %6, %7, %8, %9, %10, %11, %12, %13, %14, %15, "
        "%16, %17, %18, %19, %20, %21, %22, %23, %24, %25, %26, %27, %28, %29, %30, %31, "
        "%32, %33, %34, %35, %36, %37, %38, %39, %40, %41, %42, %43, %44, %45, %46, %47}, "
        "{%48, %49, %50, %51}, db, p, 1, 1, 1;\n}\n"
        : "+f"(d[0]), "+f"(d[1]), "+f"(d[2]), "+f"(d[3]), "+f"(d[4]), "+f"(d[5]), "+f"(d[6]), "+f"(d[7]),
          "+f"(d[8]), "+f"(d[9]), "+f"(d[10]), "+f"(d[11]), "+f"(d[12]), "+f"(d[13]), "+f"(d[14]), "+f"(d[15]),
          "+f"(d[16]), "+f"(d[17]), "+f"(d[18]), "+f"(d[19]), "+f"(d[20]), "+f"(d[21]), "+f"(d[22]), "+f"(d[23]),
          "+f"(d[24]), "+f"(d[25]), "+f"(d[26]), "+f"(d[27]), "+f"(d[28]), "+f"(d[29]), "+f"(d[30]), "+f"(d[31]),
          "+f"(d[32]), "+f"(d[33]), "+f"(d[34]), "+f"(d[35]), "+f"(d[36]), "+f"(d[37]), "+f"(d[38]), "+f"(d[39]),
          "+f"(d[40]), "+f"(d[41]), "+f"(d[42]), "+f"(d[43]), "+f"(d[44]), "+f"(d[45]), "+f"(d[46]), "+f"(d[47])
        : "r"(a.x), "r"(a.y), "r"(a.z), "r"(a.w), "r"(descB), "n"(BHI));
}

__device__ __forceinline__ uint32_t opq(uint32_t v) { asm volatile("" : "+r"(v)); return v; }
template <int I> struct IC { static constexpr int value = I; };
template <int B, int E, class F> __device__ __forceinline__ void static_for(F&& f) {
    if constexpr (B < E) { f(IC<B>{}); static_for<B + 1, E>(f); }
}

__device__ __forceinline__ void tma_store_2d(const CUtensorMap* tm, uint32_t src, int c0, int c1) {
    asm volatile("cp.async.bulk.tensor.2d.global.shared::cta.bulk_group [%0, {%2, %3}], [%1];" ::"l"(tm), "r"(src), "r"(c0), "r"(c1) : "memory");
}
__device__ __forceinline__ void bulk_store(void* dst, uint32_t src, uint32_t bytes) {
    asm volatile("cp.async.bulk.global.shared::cta.bulk_group [%0], [%1], %2;" ::"l"(dst), "r"(src), "r"(bytes) : "memory");
}
__device__ __forceinline__ void bulk_commit() { asm volatile("cp.async.bulk.commit_group;" ::: "memory"); }
template <int N> __device__ __forceinline__ void bulk_wait_read() { asm volatile("cp.async.bulk.wait_group.read %0;" ::"n"(N) : "memory"); }
__device__ __forceinline__ void bar_arrive(int id) { asm volatile("bar.arrive %0, 256;" ::"r"(id) : "memory"); }
__device__ __forceinline__ void bar_sync(int id) { asm volatile("bar.sync %0, 256;" ::"r"(id) : "memory"); }
template <int NC, int OFF, int N>
__device__ __forceinline__ void stage_cols(const float (&acc)[N], uint32_t stg) {
    int lane; asm volatile("mov.u32 %0, %%laneid;" : "=r"(lane));
    const int r = lane & 15;
    const uint32_t a0 = NC == 64 ? stg + r * 128 + (((lane >> 4) ^ (r & 7)) << 4) : stg + r * 64 + (((lane >> 4) ^ ((r >> 1) & 3)) << 4);
#pragma unroll
    for (int j = 0; j < NC / 16; j++) {
        const int i = OFF + 8 * j;
        stmatrix_x4(a0 ^ (j * 32), pack_bf16(acc[i], acc[i + 1]), pack_bf16(acc[i + 2], acc[i + 3]), pack_bf16(acc[i + 4], acc[i + 5]), pack_bf16(acc[i + 6], acc[i + 7]));
    }
}
__device__ __forceinline__ void send(uint32_t stg, const CUtensorMap* tmo, int col, int row) {
    fence_async_smem();
    __syncwarp();
    if (elect()) { tma_store_2d(tmo, stg, col, row); bulk_commit(); }
    __syncwarp();
}

__host__ __device__ constexpr int rslot(int u) { return (2 * u) % 3; }
__host__ __device__ constexpr int roff(int slot) { return slot < 2 ? slot * UNIT : RAW2_OFF - RAW_OFF; }
__host__ __device__ constexpr int rpar(int u) { return (u / 3 - (u % 3 == 0)) & 1; }
__host__ __device__ constexpr int sslot(int c) { return c < 3 ? c + 3 : c % 3; }
__host__ __device__ constexpr int vturn(int v) {
    return v < 20 ? v : v == 20 ? -21 : v == 21 ? -22 : v == 22 ? 21 : v == 23 ? -20 : v == 24 ? 20 : v < 29 ? v - 3 : v == 29 ? -24 : v == 30 ? -25 : 27;
}
__host__ __device__ constexpr int uoff(int v) { return vturn(v) < 0 ? RAW_OFF + roff(rslot(-vturn(v))) : W_OFF + (vturn(v) % NW) * UNIT; }
__host__ __device__ constexpr int ubar(int v) { return vturn(v) < 0 ? 96 + 8 * rslot(-vturn(v)) : 16 * (vturn(v) % NW); }
__host__ __device__ constexpr int upar(int v) { return vturn(v) < 0 ? rpar(-vturn(v)) : (vturn(v) / NW) & 1; }
__host__ __device__ constexpr int utime(int v) {
    return v == 20 ? CK0 : v == 21 ? (CK0 > 36 ? CK0 : 36) : v == 22 || v == 25 ? 38 : v < 25 ? 40 : v < 28 ? 42 : v == 28 ? 44 : 2 * v - 14;
}
__host__ __device__ constexpr uint32_t bdesc(int s) { return (uint32_t)(((0x400 + uoff(s >> 1)) >> 4) | ((7168u >> 4) << 16)) + (s & 1) * 224; }

__global__ void __cluster_dims__(2, 1, 1) __launch_bounds__(256, 1)
nf4_gemm_kernel(const int* __restrict__ qw, const __nv_bfloat16* __restrict__ cb, const __nv_bfloat16* __restrict__ absmax,
                uint8_t* __restrict__ wimg, unsigned* __restrict__ gflag,
                const __grid_constant__ CUtensorMap tmx, const __grid_constant__ CUtensorMap tmq, const __grid_constant__ CUtensorMap tmo64,
                const __grid_constant__ CUtensorMap tmo32, const __grid_constant__ CUtensorMap tmqp, const __grid_constant__ CUtensorMap tmx16,
                const __grid_constant__ CUtensorMap tmx64, const __grid_constant__ CUtensorMap tmq1) {
    extern __shared__ __align__(1024) uint8_t smem[];
    const uint32_t sbase = smem_u32(smem);
    const int rank = blockIdx.x, nt = blockIdx.y, pair = blockIdx.z;
    uint4 q[4], c0, c1;
    uint2 sf;
    if (threadIdx.x < 224) {
        const uint32_t t = threadIdx.x;
        const int* p = qw + (uint32_t)((t & 3) * (N_ - 1) + t + blockIdx.x * (8 * N_) + blockIdx.y * BN);
        q[0] = ldg128(p); q[1] = ldg128(p + 4 * N_);
        q[2] = ldg128(p + 16 * N_); q[3] = ldg128(p + 20 * N_);
        const void* ps = absmax + (uint32_t)(opq(t & ~3u) + blockIdx.y * BN);
        asm volatile("ld.global.nc.v2.b32 {%0, %1}, [%2];" : "=r"(sf.x), "=r"(sf.y) : "l"(ps) : "memory");
        c0 = ldg128(cb); c1 = ldg128(cb + 8);
    }
    const unsigned tstart = clk();
    const int mt = pair * 2 + rank;
    const int lane = threadIdx.x & 31;
    const int warp = __reduce_max_sync(~0u, threadIdx.x >> 5);
    const int wg = warp >> 2;
    const uint32_t bars = sbase + BAR_OFF;
    const uint32_t full = bars, rawfull = bars + 96, written = bars + 120, xbar = bars + 144, gbar = bars + 160 + wg * 16;
    const uint32_t rawh = bars + 192 - 8, ebar = bars + 216, ones = bars + 256;
    const uint32_t wbase = sbase + W_OFF;
    TS_INIT();
    __syncwarp();
    TSW(0, 0);

    auto insert = [](uint64_t m, int pos, int v) { const uint64_t low = (1ull << (4 * pos)) - 1; return (m & low) | ((m & ~low) << 4) | ((uint64_t)v << (4 * pos)); };
    const uint64_t others = (0xedcfedu >> (4 * pair)) & 0xfff;
    const uint64_t cmap = NG == 1 ? insert(0xba9876543210ull, G1, 12 + pair) | (others << 52)
                                  : insert(insert(0x76543210ull, G1, 8 + pair), G2, 12 + pair) | ((others - 0x444) << 40) | (others << 52);
    auto chunk = [&](int i) { return (int)(cmap >> (4 * i)) & 15; };
    unsigned* flag = gflag + nt * 32;
    uint8_t* wpan = wimg + nt * (8 * NG * UNIT);
    auto load_x = [&](int i, int slot, uint32_t bar) {
        tma_load_2d(sbase + slot * 32768, &tmx, chunk(i) * 64, mt * BM, bar);
        tma_load_2d(sbase + slot * 32768 + 16384, &tmx, chunk(i) * 64, mt * BM + 128, bar);
    };
    auto load_l = [&](int i, int slot, int g, uint32_t bar) {
        tma_load_2d(sbase + slot * 32768 + g * 16384, &tmx64, chunk(i) * 64, mt * BM + g * 128, bar);
        tma_load_2d(sbase + slot * 32768 + g * 16384 + 8192, &tmx64, chunk(i + 1) * 64, mt * BM + g * 128, bar);
    };
    auto snap = [&](int ss, uint32_t bar) { bulk_load(sbase + SC_OFF + ss * SC_STRIDE + 448, flag, 16, bar); };
    auto load_sc = [&](int i, int ss, uint32_t bar) {
        bulk_load(sbase + SC_OFF + ss * SC_STRIDE, absmax + chunk(i) * N_ + nt * BN, 448, bar);
    };
    auto load_raw = [&](int u, int slot) {
        mbar_expect_tx(rawfull + 8 * slot, UNIT);
        tma_load_5d(sbase + RAW_OFF + roff(slot), &tmq, 0, 0, nt * 7, rank, 4 * chunk(u >> 1) + 2 * (u & 1), rawfull + 8 * slot);
    };
    auto load_half = [&](int b, uint32_t more) {
        const uint32_t bar = (b & 1) ? rawfull + 8 * rslot(b >> 1) : rawh + 8 * (b >> 1);
        mbar_expect_tx(bar, 7168 + more);
        tma_load_5d(sbase + RAW_OFF + roff(rslot(b >> 1)) + (b & 1) * 7168, &tmq1, 0, 0, nt * 7, rank, b, bar);
    };
    auto load_w = [&](int v) {
        mbar_expect_tx(bars + ubar(v), UNIT + (!(v & 1) && v <= 24 ? 32768 : 0) + (v == 21 ? 16 : 0));
        bulk_load(sbase + uoff(v), wpan + (2 * (chunk(v >> 1) - NC) + (v & 1)) * UNIT, UNIT, bars + ubar(v));
    };
    auto prefetch_q = [&](int c) { if (c + PFQ < NC) tma_prefetch_2d(&tmqp, nt * BN, (c + PFQ) * 64 + pair * 16 + rank * 8); };
    auto prefetch_g = [&](int c) {
        if ((unsigned)(c - PFG) < 6) {
            const int k = c - PFG, k0 = k + (k >= 3);
            tma_prefetch_2d(&tmqp, nt * BN, (8 + (k0 & 4) + pair) * 64 + (k0 & 3) * 16 + rank * 8);
            if (k == 1 || k == 4) tma_prefetch_2d(&tmqp, nt * BN, (8 + (k0 & 4) + pair) * 64 + 48 + rank * 8);
        }
    };
    auto prefetch_x = [&](int i) { tma_prefetch_2d(&tmx16, chunk(i) * 64, mt * BM + nt * 16); };
    if (warp == 7) {
        if (elect()) {
            mbar_init(xbar, 1); mbar_init(rawh + 8, 1); mbar_init(rawfull + 8 * rslot(1), 1); mbar_init(xbar + 8, 1);
            fence_async_smem();
            load_half(2, 448);
            bulk_load(sbase + SC_OFF + sslot(0) * SC_STRIDE, absmax + nt * BN, 448, rawh + 8);
            if (!OR1) load_half(3, 0);
            mbar_expect_tx(xbar, 16384);
            tma_load_2d(sbase, &tmx, 0, mt * BM, xbar);
            if (OR1) load_half(3, 0);
            mbar_expect_tx(xbar + 8, 16384);
            if (!XB) tma_load_2d(sbase + 16384, &tmx, 0, mt * BM + 128, xbar + 8);
            mbar_init(rawfull + 8 * rslot(2), 1); mbar_init(rawfull + 8 * rslot(3), 1); mbar_init(rawh + 16, 1); mbar_init(rawh + 24, 1);
            mbar_init(ebar, 7); mbar_init(ebar + 8, 7);
            sts128(ones, make_uint4(1, 0, 0, 0)); sts128(ones + 16, make_uint4(0, 1, 0, 0));
#pragma unroll
            for (int s = 0; s < 12; s++) { mbar_init(full + 8 * s, 1); if (s < 4) mbar_arrive(full + 8 * s); }
#pragma unroll
            for (int s = 0; s < 3; s++) mbar_init(written + 8 * s, 7);
#pragma unroll
            for (int s = 0; s < 4; s++) mbar_init(bars + 160 + 8 * s, 4);
            asm volatile("fence.mbarrier_init.release.cluster;" ::: "memory");
            fence_async_smem();
            if ((sbase & 0xffffff) != 0x400) __trap();
        }
        __syncwarp();
        cluster_arrive();
        if (elect()) {
            asm volatile("prefetch.tensormap [%0];" ::"l"(&tmq) : "memory");
            asm volatile("prefetch.tensormap [%0];" ::"l"(&tmqp) : "memory");
            asm volatile("prefetch.tensormap [%0];" ::"l"(&tmx16) : "memory");
            asm volatile("prefetch.tensormap [%0];" ::"l"(&tmx64) : "memory");
            while (clk() - tstart < T2) { }
            if (XB) tma_load_2d(sbase + 16384, &tmx, 0, mt * BM + 128, xbar + 8);
            load_half(4, 2 * 448 + 16);
            load_sc(1, sslot(1), rawh + 16); load_sc(2, sslot(2), rawh + 16); snap(sslot(1), rawh + 16);
            load_half(5, 0);
            while (clk() - tstart < T2B) { }
            tma_load_2d(sbase + 32768, &tmx, 64, mt * BM, full + 32);
            load_half(6, 0); load_half(7, 0);
            tma_load_2d(sbase + 32768 + 16384, &tmx, 64, mt * BM + 128, full + 32);
            load_sc(3, sslot(3), full + 48);
            while (clk() - tstart < T3) { }
            if (PFQ == 4) prefetch_q(-2);
            prefetch_q(-1);
            if (PFS) {
                asm volatile("cp.async.bulk.prefetch.L2.global [%0], 448;" ::"l"(absmax + (2 * mt) * N_ + nt * BN) : "memory");
                asm volatile("cp.async.bulk.prefetch.L2.global [%0], 448;" ::"l"(absmax + (2 * mt + 1) * N_ + nt * BN) : "memory");
            }
        }
        __syncwarp();
        TSL(33);
        cluster_wait();
    } else {
        cluster_arrive();
    }
    const uint32_t rsrc = __shfl_sync(~0u, sbase + RAW_OFF + warp * 1024 + (lane & 7) * 128 + ((((lane >> 3) * 2) ^ (lane & 7)) << 4), lane);
    const uint32_t ssrc = sbase + SC_OFF + warp * 64;
    const int wpos = (nt & 1) ? (0x73210546 >> (4 * warp)) & 7 : warp;
    const uint32_t wown = wbase + rank * 7168 + wpos * 512;
    const uint32_t wdst = __shfl_sync(~0u, wown + lane * 16, lane);
    auto get_sc = [&](int ss) { return lds128(((opq(wdst) >> 3) & 0x30) + ssrc + ss * SC_STRIDE); };
    const uint32_t whalf = wbase + rank * 7168;
    const uint32_t pwhalf = mapa(whalf, rank ^ 1), pbars = mapa(bars, rank ^ 1);
    Lut lut;
    uint4 sc;
    uint4 q0, q1;
    auto fetch = [&](int slot, int h) {
        q0 = lds128(rsrc + roff(slot) + h * 7168);
        q1 = lds128((opq(rsrc) ^ 16) + roff(slot) + h * 7168);
    };
    auto signal = [&](uint32_t bar) { __syncwarp(); if (elect()) mbar_arrive(bar); __syncwarp(); };
    auto convert = [&](int ws, int h, bool w1, uint32_t bar1, uint32_t par1, bool w2, uint32_t bar2, uint32_t par2, bool next, int rsn,
                       bool sig, uint32_t sbar, bool scales, int cs) {
        bool ok1 = true, ok2 = true;
        if (w2) ok2 = mbar_try(bar2, par2);
        if (w1) ok1 = mbar_try(bar1, par1);
        uint4 w = dequant8(pack4(q0), pack4(q1), sc, lut);
        asm volatile("" : "+r"(w.x), "+r"(w.y), "+r"(w.z), "+r"(w.w));
        if (w1 && w2) mbar_wait2(bar2, par2, bar1, par1, ok1 && ok2);
        else if (w2) mbar_wait1(bar2, par2, ok2);
        else if (w1) mbar_wait1(bar1, par1, ok1);
        if (next) fetch(rsn, h ^ 1);
        sts128(wdst + ws * UNIT + h * 3584, w);
        if (sig) signal(sbar);
        if (scales) sc = get_sc(cs);
    };
    auto hand_over = [&](uint32_t sbar, uint32_t par, int ws, int h, uint32_t more, bool raw, int un, int rs, auto extra) {
        mbar_wait(sbar, par);
        fence_async_smem();
        if (elect()) {
            if (raw && RAWFIRST) load_raw(un, rs);
            copy_to_peer(pwhalf + ws * UNIT + h * 3584, whalf + ws * UNIT + h * 3584, 3584, pbars + 8 * (2 * ws + h));
            mbar_expect_tx(full + 8 * (2 * ws + h), 3584 + more);
            if (raw && !RAWFIRST) load_raw(un, rs);
            extra();
        }
        __syncwarp();
    };
    auto share = [&](int g, uint32_t o, uint32_t n) {
        bulk_store(wpan + 2 * (chunk(g) - NC) * UNIT + rank * 7168 + o, whalf + 2 * (g % 3) * UNIT + o, n);
        bulk_commit();
    };
    auto publish = [&](int k) {
        asm volatile("cp.async.bulk.wait_group 0;" ::: "memory");
        asm volatile("cp.reduce.async.bulk.global.shared::cta.bulk_group.add.u32 [%0], [%1], 16;" ::"l"(flag), "r"(ones + 16 * k) : "memory");
    };
    auto check = [&](int k, int ss) {
        unsigned f0, f1;
        asm volatile("ld.shared.u32 %0, [%1];" : "=r"(f0) : "r"(sbase + SC_OFF + sslot(1) * SC_STRIDE + 448 + 4 * k) : "memory");
        asm volatile("ld.shared.u32 %0, [%1];" : "=r"(f1) : "r"(sbase + SC_OFF + ss * SC_STRIDE + 448 + 4 * k) : "memory");
        asm volatile("{\n.reg .pred p;\n.reg .u32 n, d;\nmov.u32 n, 0;\nLAB_POLL:\nsub.u32 d, %0, %1;\nsetp.ge.u32 p, d, 8;\n@p bra.uni LAB_DONE;\n"
                     "ld.relaxed.gpu.global.u32 %0, [%2];\nadd.u32 n, n, 1;\nsetp.lt.u32 p, n, 0x10000;\n@p bra.uni LAB_POLL;\nLAB_DONE:\n}\n"
                     : "+r"(f1) : "r"(f0 & ~7u), "l"(flag + k) : "memory");
    };
    auto sig_bar = [&](int b) { return written + 8 * (b % 3); };
    auto sig_par = [](int b) { return (b / 3 - 1) & 1; };
    auto see = [&](int s) { if (s < 2 * NU) mbar_wait(full + 8 * (s % 12), (s / 12) & 1); else mbar_wait(bars + ubar(s >> 1), upar(s >> 1)); };
    auto block = [&](int b, int sn) {
        const int u = b >> 1, h = b & 1;
        const bool next = b + 1 < 2 * NU;
        convert(u % NW, h, sn == 2 || sn >= 4, sn == 2 ? ebar + 8 : full + 8 * (sn % 12), (sn / 12) & 1,
                next && (h || b < 8), b == 5 ? rawh + 24 : rawfull + 8 * rslot((b + 1) >> 1), b == 5 ? 0 : rpar((b + 1) >> 1),
                next, rslot((b + 1) >> 1), true, sig_bar(b), (b & 3) == 3 && next, sslot((b + 1) >> 2));
    };
    auto hand = [&](int b, auto extra) {
        const int u = b >> 1;
        hand_over(sig_bar(b), sig_par(b), u % NW, b & 1, ((b & 3) == 0 ? 32768 : (b & 3) == 2 && b < 36 ? 448 : 0) + (b == SN0 + 3 ? 16 : 0), (b & 1) && u + NR < NU, u + NR, rslot(u), extra);
    };
    auto pass_on = [&](int u) {
        fence_async_smem();
        __syncwarp();
        if (elect()) {
            const uint32_t o = wpos * 512 + u * UNIT;
            copy_to_peer(pwhalf + o, whalf + o, 512, pbars + 216 + 8 * u);
            copy_to_peer(pwhalf + o + 3584, whalf + o + 3584, 512, pbars + 216 + 8 * u);
            if (u == 1) mbar_arrive(sig_bar(3));
            mbar_expect_tx(ebar + 8 * u, 1024);
        }
        __syncwarp();
    };
    bool ok0 = false;
    if (warp < 7) {
        lut.lo[0] = __byte_perm(c0.x, c0.y, 0x6420); lut.hi[0] = __byte_perm(c0.x, c0.y, 0x7531);
        lut.lo[1] = __byte_perm(c0.z, c0.w, 0x6420); lut.hi[1] = __byte_perm(c0.z, c0.w, 0x7531);
        lut.lo[2] = __byte_perm(c1.x, c1.y, 0x6420); lut.hi[2] = __byte_perm(c1.x, c1.y, 0x7531);
        lut.lo[3] = __byte_perm(c1.z, c1.w, 0x6420); lut.hi[3] = __byte_perm(c1.z, c1.w, 0x7531);
        const uint32_t d = wown + (lane >> 3) * 128 + (lane & 3) * 16 + (lane & 4) * 2;
#pragma unroll
        for (int j = 0; j < 4; j++) {
            uint32_t a, b;
            lookup4(pack4(q[j]), lut, a, b);
            asm volatile("st.shared.v2.b32 [%0], {%1, %2};" ::"r"(d + (j >> 1) * 3584 + (j & 1) * 64), "r"(mul_bf16x2(a, sf.x)), "r"(mul_bf16x2(b, sf.y)) : "memory");
        }
        TSL(33);
        cluster_wait();
        pass_on(0);
        TSL(34);
        mbar_wait(rawh + 8, 0);
        const uint4 a0 = lds128(rsrc + roff(rslot(1))), a1 = lds128((rsrc ^ 16) + roff(rslot(1))), s0 = get_sc(sslot(0));
        mbar_wait(rawfull + 8 * rslot(1), 0);
        const uint4 a2 = lds128(rsrc + roff(rslot(1)) + 7168), a3 = lds128((rsrc ^ 16) + roff(rslot(1)) + 7168);
        sts128(wdst + UNIT, dequant8(pack4(a0), pack4(a1), s0, lut));
        sts128(wdst + UNIT + 3584, dequant8(pack4(a2), pack4(a3), s0, lut));
        ok0 = mbar_try(xbar + 8 * wg, 0) & mbar_try(ebar, 0);
        if (!DP) pass_on(1);
    }
    TSL(31);
    mbar_wait2(xbar + 8 * wg, 0, ebar, 0, ok0);
    TSL(32);
    if (TLPRO == -3) TSW(0, 1);

    float acc0[112], acc1[112];
    const uint32_t descA = ((0x400 + wg * 16384) >> 4) | (1u << 16);
    auto mma = [&](int s, int sid = -1) {
        const uint32_t da = opq(descA) + ((s >> 2) % 3) * (32768 >> 4) + (s & 3) * 2;
        wgmma_fence();
        wgmma224<1, 8>(acc0, da, bdesc(s)); wgmma224<1, 8>(acc1, da + 512, bdesc(s));
        wgmma_commit();
        TSB(sid < 0 ? s : sid);
        wgmma_wait<2>();
    };
    wgmma_fence();
    wgmma224<0, 8>(acc0, descA, bdesc(0)); wgmma224<0, 8>(acc1, descA + 512, bdesc(0));
    wgmma_commit();
    TSL(0); TSB(0);
    mma(1); TSL(1);
    if (warp < 7) {
        if (DP) pass_on(1);
        mbar_wait(rawh + 16, 0); fetch(rslot(2), 0); sc = get_sc(sslot(1));
        if (FD == 1) { block(4, -1); block(5, 2); } else block(4, 2);
    } else {
        mbar_wait(sig_bar(3), sig_par(3));
        if (elect()) { load_raw(4, rslot(4)); load_x(2, 2, full + 64); prefetch_q(0); prefetch_x(3); prefetch_g(0); }
        __syncwarp();
        if (FD == 1) hand(4, [] {});
        mbar_wait(ebar + 8, 0);
    }
    static_for<2, 8>([&](auto S) {
        constexpr int s = S.value;
        mma(s); TSL(s);
        if (warp < 7) { if (s <= FD) block(s + 3, s < FD ? s + 1 : -1); if (s >= FD) block(s + 4, s + 1); }
        else {
            if (s <= FD) hand(s + 2, [] {});
            if (s >= FD) hand(s + 3, [&] {
                if (s == 4) prefetch_q(1);
                if (s == 5) { load_sc(4, sslot(4), full + 80); prefetch_g(1); }
                if (s == 6) prefetch_x(4);
                if (s == 7) load_x(3, 0, full);
            });
            if (s >= 3) see(s + 1);
        }
    });
    {
        uint32_t ph = 0;
#pragma unroll 1
        for (int cb = 2; cb < 8; cb += 3)
          static_for<2, 5>([&](auto I) {
            constexpr int cc = I.value;
            constexpr int j0 = cc % 3, j1 = (cc + 1) % 3, j2 = (cc + 2) % 3;
            const int c = cb + cc - 2;
            auto sh = [&](int h) {
                if (SHE) {
                    if ((cc - G1 + 1) % 3 == 0 && c == G1 - 1) share(G1, h * 3584, 3584);
                    if ((cc - G1) % 3 == 0 && c == G1) share(G1, UNIT + h * 3584, 3584);
                    if ((cc - G1 - 1) % 3 == 0 && h == 0 && c == G1 + 1) publish(0);
                }
                if (!SHE && (cc - G1 + 1) % 3 == 0 && h == 1 && c == G1 - 1) share(G1, 0, 3584);
                if (!SHE && (cc - G1) % 3 == 0 && c == G1) share(G1, h ? UNIT : 3584, 3584);
                if (!SHE && (cc - G1 - 1) % 3 == 0 && c == G1 + 1) {
                    if (h == 0) { share(G1, UNIT + 3584, 3584); bulk_wait_read<1>(); }
                    else publish(0);
                }
                if ((cc - G2 + 1) % 3 == 0 && h == 1 && c == G2 - 1) share(G2, 0, 3584);
            };
            if (cc == 2) TSL(c < 8 ? 36 : 37);
            mma(4 * j0, 4 * c); TSL(cb == TLIT ? 4 * cc : 30);
            if (warp < 7) convert(2 * j1, 0, true, full + 32 * j0 + 8, ph, false, 0, 0, true, j1, true, sig_bar(4 * cc + 4), false, 0);
            else {
                const bool ok = mbar_try(full + 32 * j0 + 8, ph);
                hand_over(sig_bar(4 * cc + 3), sig_par(4 * cc + 3), 2 * j0 + 1, 1, 0, true, 2 * c + 4, j2, [&] { prefetch_q(c); if (PF12 && cc == PF12 - 3 && c == PF12) prefetch_x(12); });
                mbar_wait1(full + 32 * j0 + 8, ph, ok);
            }
            mma(4 * j0 + 1, 4 * c + 1); TSL(cb == TLIT ? 4 * cc + 1 : 30);
            if (warp < 7) convert(2 * j1, 1, true, full + 32 * j0 + 16, ph, true, rawfull + 8 * j0, rpar(2 * cc + 3), true, j0, true, sig_bar(4 * cc + 5), false, 0);
            else {
                const bool ok = mbar_try(full + 32 * j0 + 16, ph);
                hand_over(sig_bar(4 * cc + 4), sig_par(4 * cc + 4), 2 * j1, 0, 32768, false, 0, 0, [&] { load_sc(c + 3, j0, full + 32 * j1 + 16); prefetch_g(c); sh(0); });
                mbar_wait1(full + 32 * j0 + 16, ph, ok);
            }
            mma(4 * j0 + 2, 4 * c + 2); TSL(cb == TLIT ? 4 * cc + 2 : 30);
            if (warp < 7) convert(2 * j1 + 1, 0, true, full + 32 * j0 + 24, ph, false, 0, 0, true, j0, true, sig_bar(4 * cc + 6), false, 0);
            else {
                const bool ok = mbar_try(full + 32 * j0 + 24, ph);
                hand_over(sig_bar(4 * cc + 5), sig_par(4 * cc + 5), 2 * j1, 1, 0, true, 2 * c + 5, j1, [&] { prefetch_x(c + PFX); });
                mbar_wait1(full + 32 * j0 + 24, ph, ok);
            }
            if (j1 == 0) asm volatile("xor.b32 %0, %0, 1;" : "+r"(ph));
            mma(4 * j0 + 3, 4 * c + 3); TSL(cb == TLIT ? 4 * cc + 3 : 30);
            if (warp < 7) convert(2 * j1 + 1, 1, true, full + 32 * j1, ph, true, rawfull + 8 * j2, rpar(2 * cc + 4), true, j2, true, sig_bar(4 * cc + 7), true, j2);
            else {
                const bool ok = mbar_try(full + 32 * j1, ph);
                hand_over(sig_bar(4 * cc + 6), sig_par(4 * cc + 6), 2 * j1 + 1, 0, 448, false, 0, 0, [&] { load_x(c + 2, j2, full + 32 * j2); sh(1); });
                mbar_wait1(full + 32 * j1, ph, ok);
            }
          });
    }
    uint4 fa[8];
    auto get_frag = [&](int f, uint32_t rows, int j0 = 0, int j1 = 4) {
        int ln; asm volatile("mov.u32 %0, %%laneid;" : "=r"(ln));
        const uint32_t a = rows + (ln & 15) * 128 + (((ln >> 4) ^ (ln & 7)) << 4);
#pragma unroll
        for (int j = j0; j < j1; j++) fa[4 * f + j] = ldmatrix_x4(a ^ (j * 32));
    };
    static_assert(NG == 2 && G2 == 8 && G1 <= 6, "");
    static_for<32, 46>([&](auto S) {
        constexpr int s = S.value;
        constexpr int vb = 40 + (s - 37) / 2;
        mma(s);
        if (TLIT == 99) TSL(s - 26);
        if (s == 39) cluster_arrive();
        if (s == 41) cluster_wait();
        if (s == FS) mbar_wait(rawh + 8, 1);
        if (s >= FS && s < 40) get_frag(0, sbase + uoff(24) + wg * (uoff(23) - uoff(24)) + (warp & 3) * 2048, s == FS ? 0 : s - 36, s - 35);
        if (warp < 7) {
            if (s < 36) block(s + 4, s + 1);
            else {
                if (s & 1) signal(sig_bar(vb));
                if (s < 39 || (s & 1)) see(s + 1);
            }
        } else {
            auto loads = [&] {
                if (s < 45) static_for<NU, 31>([&](auto V) { if constexpr (utime(V.value) == s) load_w(V.value); });
                if (s == 32) { share(G2, 3584, 3584); prefetch_x(11); }
                if (s == 33) {
                    mbar_expect_tx(rawh + 8, 16384);
                    tma_load_2d(sbase + uoff(24), &tmx64, chunk(12) * 64, mt * BM + 64, rawh + 8);
                    tma_load_2d(sbase + uoff(23), &tmx64, chunk(12) * 64, mt * BM + 192, rawh + 8);
                    share(G2, UNIT, 3584);
                }
                if (s == 34) share(G2, UNIT + 3584, 3584);
                if (s == 37) { if (!PF12) prefetch_x(12); prefetch_x(13); }
                if (s == 39) snap(1, bars + ubar(21));
                if (s == 41) { prefetch_x(14); prefetch_x(15); }
                if (s == 43) { load_l(12, 0, 0, bars + ubar(24)); load_l(12, 0, 1, bars + ubar(24)); }
                else if ((s & 3) == 3) load_x((s >> 2) + 2, ((s >> 2) + 2) % 3, bars + ubar(2 * (s >> 2) + 4));
                if (s == 44) {
                    asm volatile("prefetch.tensormap [%0];" ::"l"(&tmo64) : "memory");
                    asm volatile("prefetch.tensormap [%0];" ::"l"(&tmo32) : "memory");
                }
                if (s == 45) { mbar_expect_tx(xbar, 16384); load_l(14, 1, 0, xbar); }
                if (s == 45) load_w(30);
                if (s == PB1) publish(1);
            };
            if (s == SN0) { if (elect()) snap(0, full + 8 * ((SN0 + 3) % 12)); __syncwarp(); }
            if (s == CK0) check(0, 0);
            if (s == 42) check(1, 1);
            if (s <= 36) hand(s + 3, loads);
            else {
                if (!(s & 1)) mbar_wait(sig_bar(40 + (s - 38) / 2), sig_par(40 + (s - 38) / 2));
                if (s == 45) mbar_wait(sig_bar(vb), sig_par(vb));
                if (elect()) loads();
                __syncwarp();
            }
            if (s < 39 || (s & 1)) see(s + 1);
        }
    });
    if (wg == 1) bar_sync(8);
    mma(46);
    if (warp == 7) {
        wgmma_wait<1>();
        see(48);
        if (elect()) { load_w(31); mbar_expect_tx(xbar + 8, 16384); load_l(14, 1, 1, xbar + 8); }
        __syncwarp();
    }
    mma(47);
    if (wg == 0) bar_arrive(8);
    const uint32_t slice0 = sbase + wg * 16384 + (warp & 3) * 2048;
    auto slc = [&](int p) { return slice0 + (p >> 1) * 32768 + (p & 1) * 8192; };
    const int row0 = mt * BM + wg * 128 + (warp & 3) * 16, odd = nt & 1;
    const int colL = nt * BN + odd * 96, colA = nt * BN + (odd ? 32 : 128), colB = nt * BN + (odd ? 0 : 192);
    auto load_s = [&](int i, int p, uint32_t bar) { tma_load_2d(slc(p), &tmx16, chunk(i) * 64, row0 + 64, bar); };
    const uint32_t tA = opq(descA);
    see(48);
    wgmma_wait<0>();
    RT(0); TSB(48);
    if (TLPRO == -3) TSW(4, 2);
    float lo0[64], hi0[48], lo1[64], hi1[48];
#pragma unroll
    for (int i = 0; i < 64; i++) { asm volatile("mov.b32 %0, %1;" : "=f"(lo0[i]) : "f"(acc0[i])); asm volatile("mov.b32 %0, %1;" : "=f"(lo1[i]) : "f"(acc1[i])); }
#pragma unroll
    for (int i = 0; i < 48; i++) { asm volatile("mov.b32 %0, %1;" : "=f"(hi0[i]) : "f"(acc0[64 + i])); asm volatile("mov.b32 %0, %1;" : "=f"(hi1[i]) : "f"(acc1[64 + i])); }
    auto tdesc = [&](int p, int s) { return tA + (p >> 1) * (32768 >> 4) + (p & 1) * 512 + (s & 3) * 2; };
    auto ldesc = [&](int s) { return tdesc(s >> 2, s); };
    auto gdesc = [&](int s) { return tdesc(((s >> 2) + 3) % 6, s); };
    if (wg == 1) { mbar_wait(xbar + 8, 1); bar_sync(1); }
    static_for<0, 8>([&](auto V) {
        constexpr int v = 24 + (V.value == 0 || V.value > 3 ? V.value : V.value == 3 ? 1 : V.value + 1), s = 2 * (v - 24);
        if (v == 26) mbar_wait2(bars + ubar(26), upar(26), bars + ubar(27), upar(27), wg);
        else if (v == 28) mbar_wait2(bars + ubar(28), upar(28), xbar, 1, wg);
        else if (v != 24 && v != 27) mbar_wait1(bars + ubar(v), upar(v), wg);
        wgmma_fence();
        wgmma96<1, 8>(hi0, ldesc(s), bdesc(48 + s) + 128);
        wgmma96<1, 8>(hi0, ldesc(s + 1), bdesc(49 + s) + 128);
    });
    wgmma_commit();
    bar_arrive(1 + wg);
    wgmma_wait<0>();
    RT(1);
    stage_cols<64, 0>(hi0, slc(4)); send(slc(4), &tmo64, colA, row0);
    stage_cols<32, 32>(hi0, slc(5));
    RT(2);
    bar_sync(2 + wg);
    RT(3);
    wgmma_fence();
    static_for<0, 7>([&](auto S) { wgmma128<1, 8>(lo0, ldesc(S.value), bdesc(48 + S.value)); });
    wgmma_commit();
    send(slc(5), &tmo32, colB, row0);
    wgmma_fence();
    static_for<7, 16>([&](auto S) { wgmma128<1, 8>(lo0, ldesc(S.value), bdesc(48 + S.value)); });
    wgmma_commit();
    bar_arrive(3 + wg);
    RT(4);
    {
        const uint32_t zero = opq(gridDim.x - 2);
#pragma unroll
        for (int j = 0; j < 4; j++) { fa[j].x ^= zero; fa[j].y ^= zero; fa[j].z ^= zero; fa[j].w ^= zero; asm volatile("" : "+r"(fa[j].x), "+r"(fa[j].y), "+r"(fa[j].z), "+r"(fa[j].w)); }
    }
    if (elect()) { mbar_expect_tx(gbar, 4096); bulk_wait_read<0>(); load_s(13, 4, gbar); load_s(14, 5, gbar); }
    __syncwarp();
    wgmma_wait<0>();
    RT(5);
    stage_cols<64, 0>(lo0, slc(2));
    if (elect()) { mbar_expect_tx(gbar + 8, 2048); load_s(15, 0, gbar + 8); }
    __syncwarp();
    const bool okg = mbar_try(gbar, 0);
    send(slc(2), &tmo64, colL, row0);
    stage_cols<64, 32>(lo0, slc(3));
    mbar_wait1(gbar, 0, okg);
    RT(6);
    auto mma2 = [&](auto I) { constexpr int s = I.value; if constexpr (s < 4) wgmma128r<8>(lo1, fa[s], bdesc(48 + s)); else wgmma128<1, 8>(lo1, gdesc(s), bdesc(48 + s)); };
    auto mma3 = [&](auto I) { constexpr int s = I.value; if constexpr (s < 8) wgmma96r<8>(hi1, fa[s], bdesc(48 + s) + 128); else wgmma96<1, 8>(hi1, gdesc(s), bdesc(48 + s) + 128); };
    bar_sync(4 + wg);
    RT(7);
    wgmma_fence();
    static_for<0, 8>(mma2);
    wgmma_commit();
    const bool okg2 = mbar_try(gbar + 8, 0);
    send(slc(3), &tmo64, colL + 64, row0);
    mbar_wait1(gbar + 8, 0, okg2);
    wgmma_fence();
    static_for<8, 16>(mma2);
    wgmma_commit();
    bar_arrive(5 + wg);
    RT(8);
    get_frag(1, slc(4));
    if (elect()) bulk_wait_read<1>();
    __syncwarp();
    wgmma_wait<0>();
    RT(9);
    stage_cols<64, 0>(lo1, slc(1)); send(slc(1), &tmo64, colL, row0 + 64);
    stage_cols<64, 32>(lo1, slc(2));
    RT(10);
    bar_sync(6 + wg);
    RT(11);
    wgmma_fence();
    static_for<0, GG3>(mma3);
    wgmma_commit();
    send(slc(2), &tmo64, colL + 64, row0 + 64);
    wgmma_fence();
    static_for<GG3, 16>(mma3);
    wgmma_commit();
    if (wg == 0) bar_arrive(7);
    RT(12);
    wgmma_wait<0>();
    RT(13);
    if (TLPRO == -3) TSW(4, 3);
    stage_cols<64, 0>(hi1, slc(4)); send(slc(4), &tmo64, colA, row0 + 64);
    stage_cols<32, 32>(hi1, slc(5)); send(slc(5), &tmo32, colB, row0 + 64);
    RT(14);
    if (elect()) bulk_wait_read<0>();
    __syncwarp();
    RT(15);
    TSW(wg * 4, 38 + wg);
    TS_DUMP();
    TL_DUMP();
}

typedef CUresult (*EncodeFn)(CUtensorMap*, CUtensorMapDataType, cuuint32_t, void*, const cuuint64_t*, const cuuint64_t*,
                             const cuuint32_t*, const cuuint32_t*, CUtensorMapInterleave, CUtensorMapSwizzle,
                             CUtensorMapL2promotion, CUtensorMapFloatOOBfill);

extern "C" void kernel_launch(void* const* d_in, const int* in_sizes, int n_in, void* d_out, int out_size) {
    const __nv_bfloat16* x = (const __nv_bfloat16*)d_in[0];
    const int* qw = (const int*)d_in[1];
    const __nv_bfloat16* cb = (const __nv_bfloat16*)d_in[2];
    const __nv_bfloat16* absmax = (const __nv_bfloat16*)d_in[3];
    static EncodeFn encode = nullptr;
    static void *wimg = nullptr, *gflag = nullptr;
    if (!encode) {
        cudaGetSymbolAddress(&wimg, g_wimg);
        cudaGetSymbolAddress(&gflag, g_flag);
        void* fn = nullptr;
        cudaDriverEntryPointQueryResult qr;
        cudaGetDriverEntryPoint("cuTensorMapEncodeTiled", &fn, cudaEnableDefault, &qr);
        encode = (EncodeFn)fn;
        cudaFuncSetAttribute(nf4_gemm_kernel, cudaFuncAttributeMaxDynamicSharedMemorySize, SMEM_BYTES);
    }
    CUtensorMap tmx, tmq, tmo64, tmo32, tmqp, tmx16, tmx64, tmq1;
    {
        cuuint64_t dims[2] = {(cuuint64_t)K_, (cuuint64_t)M_};
        cuuint64_t strides[1] = {(cuuint64_t)K_ * 2};
        cuuint32_t box[2] = {64, 128};
        cuuint32_t es[2] = {1, 1};
        encode(&tmx, CU_TENSOR_MAP_DATA_TYPE_BFLOAT16, 2, (void*)x, dims, strides, box, es, CU_TENSOR_MAP_INTERLEAVE_NONE,
               CU_TENSOR_MAP_SWIZZLE_128B, CU_TENSOR_MAP_L2_PROMOTION_L2_128B, CU_TENSOR_MAP_FLOAT_OOB_FILL_NONE);
        box[1] = 64;
        encode(&tmx64, CU_TENSOR_MAP_DATA_TYPE_BFLOAT16, 2, (void*)x, dims, strides, box, es, CU_TENSOR_MAP_INTERLEAVE_NONE,
               CU_TENSOR_MAP_SWIZZLE_128B, CU_TENSOR_MAP_L2_PROMOTION_L2_128B, CU_TENSOR_MAP_FLOAT_OOB_FILL_NONE);
        box[1] = 16;
        encode(&tmx16, CU_TENSOR_MAP_DATA_TYPE_BFLOAT16, 2, (void*)x, dims, strides, box, es, CU_TENSOR_MAP_INTERLEAVE_NONE,
               CU_TENSOR_MAP_SWIZZLE_128B, CU_TENSOR_MAP_L2_PROMOTION_L2_128B, CU_TENSOR_MAP_FLOAT_OOB_FILL_NONE);
    }
    {
        cuuint64_t dims[5] = {32, 8, (cuuint64_t)(N_ / 32), 2, (cuuint64_t)(K_ / 16)};
        cuuint64_t strides[4] = {(cuuint64_t)N_ * 4, 128, (cuuint64_t)N_ * 4 * 8, (cuuint64_t)N_ * 4 * 16};
        cuuint32_t box[5] = {32, 8, 7, 1, 2};
        cuuint32_t es[5] = {1, 1, 1, 1, 1};
        encode(&tmq, CU_TENSOR_MAP_DATA_TYPE_INT32, 5, (void*)qw, dims, strides, box, es, CU_TENSOR_MAP_INTERLEAVE_NONE,
               CU_TENSOR_MAP_SWIZZLE_128B, CU_TENSOR_MAP_L2_PROMOTION_L2_128B, CU_TENSOR_MAP_FLOAT_OOB_FILL_NONE);
        box[4] = 1;
        encode(&tmq1, CU_TENSOR_MAP_DATA_TYPE_INT32, 5, (void*)qw, dims, strides, box, es, CU_TENSOR_MAP_INTERLEAVE_NONE,
               CU_TENSOR_MAP_SWIZZLE_128B, CU_TENSOR_MAP_L2_PROMOTION_L2_128B, CU_TENSOR_MAP_FLOAT_OOB_FILL_NONE);
        cuuint64_t dims2[2] = {(cuuint64_t)N_, (cuuint64_t)K_};
        cuuint32_t box2[2] = {224, 8};
        encode(&tmqp, CU_TENSOR_MAP_DATA_TYPE_INT32, 2, (void*)qw, dims2, strides, box2, es, CU_TENSOR_MAP_INTERLEAVE_NONE,
               CU_TENSOR_MAP_SWIZZLE_NONE, CU_TENSOR_MAP_L2_PROMOTION_L2_128B, CU_TENSOR_MAP_FLOAT_OOB_FILL_NONE);
    }
    {
        cuuint64_t dims[2] = {(cuuint64_t)N_, (cuuint64_t)M_};
        cuuint64_t strides[1] = {(cuuint64_t)N_ * 2};
        cuuint32_t box[2] = {64, 16};
        cuuint32_t es[2] = {1, 1};
        encode(&tmo64, CU_TENSOR_MAP_DATA_TYPE_BFLOAT16, 2, d_out, dims, strides, box, es, CU_TENSOR_MAP_INTERLEAVE_NONE,
               CU_TENSOR_MAP_SWIZZLE_128B, CU_TENSOR_MAP_L2_PROMOTION_NONE, CU_TENSOR_MAP_FLOAT_OOB_FILL_NONE);
        box[0] = 32;
        encode(&tmo32, CU_TENSOR_MAP_DATA_TYPE_BFLOAT16, 2, d_out, dims, strides, box, es, CU_TENSOR_MAP_INTERLEAVE_NONE,
               CU_TENSOR_MAP_SWIZZLE_64B, CU_TENSOR_MAP_L2_PROMOTION_NONE, CU_TENSOR_MAP_FLOAT_OOB_FILL_NONE);
    }
    nf4_gemm_kernel<<<dim3(2, 16, 4), 256, SMEM_BYTES>>>(qw, cb, absmax, (uint8_t*)wimg, (unsigned*)gflag, tmx, tmq, tmo64, tmo32, tmqp, tmx16, tmx64, tmq1);
}
```

```cpp
#include <cuda_runtime.h>
#include <cuda_bf16.h>
#include <cuda.h>
#include <stdint.h>

constexpr int M_ = 2048, K_ = 1024, N_ = 3584;
constexpr int BM = 256, BN = 224;
constexpr int UNIT = 14336;
constexpr int NW = 6, NR = 3;
constexpr int NU = 20;
constexpr int G1 = 5, G2 = 8;
constexpr int PFQ = 4, PFX = 3;
constexpr unsigned T2 = 900, T2B = 1300, T3 = 1700;
constexpr int RAW_OFF = 3 * 32768;
constexpr int SC_OFF = RAW_OFF + 2 * UNIT;
constexpr int SC_STRIDE = 464;
constexpr int W_OFF = 127 * 1024;
constexpr int RAW2_OFF = W_OFF + NW * UNIT;
constexpr int BAR_OFF = RAW2_OFF + UNIT;
constexpr int SMEM_BYTES = BAR_OFF + 320;
__device__ __align__(1024) uint8_t g_wimg[16 * 16 * UNIT];
__device__ __align__(128) unsigned g_flag[16 * 32];

__device__ __forceinline__ uint32_t smem_u32(const void* p) { return (uint32_t)__cvta_generic_to_shared(p); }
__device__ __forceinline__ bool elect() {
    uint32_t ok;
    asm volatile("{\n.reg .pred p;\nelect.sync _|p, 0xffffffff;\nselp.u32 %0, 1, 0, p;\n}\n" : "=r"(ok));
    return ok != 0;
}
__device__ __forceinline__ void mbar_init(uint32_t bar, uint32_t cnt) { asm volatile("mbarrier.init.shared::cta.b64 [%0], %1;" ::"r"(bar), "r"(cnt) : "memory"); }
__device__ __forceinline__ void mbar_expect_tx(uint32_t bar, uint32_t bytes) { asm volatile("mbarrier.arrive.expect_tx.shared::cta.b64 _, [%0], %1;" ::"r"(bar), "r"(bytes) : "memory"); }
__device__ __forceinline__ void mbar_arrive(uint32_t bar) { asm volatile("mbarrier.arrive.shared::cta.b64 _, [%0];" ::"r"(bar) : "memory"); }
#define BOUNDED
#define WAIT_INIT "mov.u32 n, 0;\n"
#define WAIT_NEXT "@p bra.uni LAB_DONE;\nadd.u32 n, n, 1;\nsetp.lt.u32 p, n, 0x4000;\n@p bra.uni LAB_WAIT;\n"
__device__ __forceinline__ void mbar_wait(uint32_t bar, uint32_t parity) {
    asm volatile(
        "{\n.reg .pred p;\n.reg .u32 n;\n"
        WAIT_INIT
        "LAB_WAIT:\n"
        "mbarrier.try_wait.parity.shared::cta.b64 p, [%0], %1;\n"
        WAIT_NEXT
        "LAB_DONE:\n}\n" ::"r"(bar), "r"(parity) : "memory");
}
__device__ __forceinline__ bool mbar_try(uint32_t bar, uint32_t parity) {
    uint32_t ok;
    asm volatile("{\n.reg .pred p;\nmbarrier.test_wait.parity.shared::cta.b64 p, [%1], %2;\nselp.u32 %0, 1, 0, p;\n}\n" : "=r"(ok) : "r"(bar), "r"(parity) : "memory");
    return ok != 0;
}
__device__ __forceinline__ void mbar_wait1(uint32_t b0, uint32_t p0, bool skip) {
    asm volatile(
        "{\n.reg .pred p;\n.reg .u32 n;\n"
        "setp.ne.u32 p, %2, 0;\n@p bra.uni LAB_DONE;\n"
        WAIT_INIT
        "LAB_WAIT:\n"
        "mbarrier.try_wait.parity.shared::cta.b64 p, [%0], %1;\n"
        WAIT_NEXT
        "LAB_DONE:\n}\n" ::"r"(b0), "r"(p0), "r"((uint32_t)skip) : "memory");
}
__device__ __forceinline__ void mbar_wait2(uint32_t b0, uint32_t p0, uint32_t b1, uint32_t p1, bool skip = false) {
    asm volatile(
        "{\n.reg .pred p, q;\n.reg .u32 n;\n"
        "setp.ne.u32 p, %4, 0;\n@p bra.uni LAB_DONE;\n"
        WAIT_INIT
        "LAB_WAIT:\n"
        "mbarrier.try_wait.parity.shared::cta.b64 p, [%0], %1;\n"
        "mbarrier.try_wait.parity.shared::cta.b64 q, [%2], %3;\n"
        "and.pred p, p, q;\n"
        WAIT_NEXT
        "LAB_DONE:\n}\n" ::"r"(b0), "r"(p0), "r"(b1), "r"(p1), "r"((uint32_t)skip) : "memory");
}
__device__ __forceinline__ void tma_load_2d(uint32_t dst, const CUtensorMap* tm, int c0, int c1, uint32_t bar) {
    asm volatile("cp.async.bulk.tensor.2d.shared::cluster.global.mbarrier::complete_tx::bytes [%0], [%1, {%2, %3}], [%4];"
                 ::"r"(dst), "l"(tm), "r"(c0), "r"(c1), "r"(bar) : "memory");
}
__device__ __forceinline__ void tma_load_5d(uint32_t dst, const CUtensorMap* tm, int c0, int c1, int c2, int c3, int c4, uint32_t bar) {
    asm volatile("cp.async.bulk.tensor.5d.shared::cluster.global.mbarrier::complete_tx::bytes [%0], [%1, {%2, %3, %4, %5, %6}], [%7];"
                 ::"r"(dst), "l"(tm), "r"(c0), "r"(c1), "r"(c2), "r"(c3), "r"(c4), "r"(bar) : "memory");
}
__device__ __forceinline__ void tma_prefetch_2d(const CUtensorMap* tm, int c0, int c1) {
    asm volatile("cp.async.bulk.prefetch.tensor.2d.L2.global [%0, {%1, %2}];" ::"l"(tm), "r"(c0), "r"(c1) : "memory");
}
__device__ __forceinline__ void bulk_load(uint32_t dst, const void* src, uint32_t bytes, uint32_t bar) {
    asm volatile("cp.async.bulk.shared::cluster.global.mbarrier::complete_tx::bytes [%0], [%1], %2, [%3];"
                 ::"r"(dst), "l"(src), "r"(bytes), "r"(bar) : "memory");
}
__device__ __forceinline__ void cluster_arrive() { asm volatile("barrier.cluster.arrive.relaxed.aligned;" ::: "memory"); }
__device__ __forceinline__ void cluster_wait() { asm volatile("barrier.cluster.wait.acquire.aligned;" ::: "memory"); }
__device__ __forceinline__ uint32_t mapa(uint32_t addr, uint32_t cta) {
    uint32_t r; asm("mapa.shared::cluster.u32 %0, %1, %2;" : "=r"(r) : "r"(addr), "r"(cta)); return r;
}
__device__ __forceinline__ void copy_to_peer(uint32_t cdst, uint32_t src, uint32_t bytes, uint32_t cbar) {
    asm volatile("cp.async.bulk.shared::cluster.shared::cta.mbarrier::complete_tx::bytes [%0], [%1], %2, [%3];"
                 ::"r"(cdst), "r"(src), "r"(bytes), "r"(cbar) : "memory");
}
__device__ __forceinline__ void wgmma_fence() { asm volatile("wgmma.fence.sync.aligned;" ::: "memory"); }
__device__ __forceinline__ void wgmma_commit() { asm volatile("wgmma.commit_group.sync.aligned;" ::: "memory"); }
template <int N> __device__ __forceinline__ void wgmma_wait() { asm volatile("wgmma.wait_group.sync.aligned %0;" ::"n"(N) : "memory"); }
__device__ __forceinline__ uint32_t pack_bf16(float lo, float hi) {
    uint32_t r; asm("cvt.rn.bf16x2.f32 %0, %1, %2;" : "=r"(r) : "f"(hi), "f"(lo)); return r;
}
__device__ __forceinline__ void stmatrix_x4(uint32_t addr, uint32_t a, uint32_t b, uint32_t c, uint32_t d) {
    asm volatile("stmatrix.sync.aligned.m8n8.x4.shared.b16 [%0], {%1, %2, %3, %4};" ::"r"(addr), "r"(a), "r"(b), "r"(c), "r"(d) : "memory");
}
__device__ __forceinline__ uint4 ldmatrix_x4(uint32_t a) {
    uint4 v; asm volatile("ldmatrix.sync.aligned.m8n8.x4.shared.b16 {%0, %1, %2, %3}, [%4];" : "=r"(v.x), "=r"(v.y), "=r"(v.z), "=r"(v.w) : "r"(a) : "memory"); return v;
}
__device__ __forceinline__ uint4 lds128(uint32_t a) {
    uint4 v; asm volatile("ld.shared.v4.b32 {%0, %1, %2, %3}, [%4];" : "=r"(v.x), "=r"(v.y), "=r"(v.z), "=r"(v.w) : "r"(a) : "memory"); return v;
}
__device__ __forceinline__ void sts128(uint32_t a, uint4 v) {
    asm volatile("st.shared.v4.b32 [%0], {%1, %2, %3, %4};" ::"r"(a), "r"(v.x), "r"(v.y), "r"(v.z), "r"(v.w) : "memory");
}
__device__ __forceinline__ uint4 ldg128(const void* p) {
    uint4 v; asm volatile("ld.global.nc.v4.b32 {%0, %1, %2, %3}, [%4];" : "=r"(v.x), "=r"(v.y), "=r"(v.z), "=r"(v.w) : "l"(p) : "memory"); return v;
}
__device__ __forceinline__ unsigned clk() { unsigned c; asm volatile("mov.u32 %0, %%clock;" : "=r"(c) :: "memory"); return c; }
__device__ __forceinline__ uint32_t mul_bf16x2(uint32_t a, uint32_t b) { uint32_t r; asm("mul.rn.bf16x2 %0, %1, %2;" : "=r"(r) : "r"(a), "r"(b)); return r; }
struct Lut { uint32_t lo[4], hi[4]; };
__device__ __forceinline__ uint32_t prmt(uint32_t a, uint32_t b, uint32_t s) { uint32_t r; asm("prmt.b32 %0, %1, %2, %3;" : "=r"(r) : "r"(a), "r"(b), "r"(s)); return r; }
__device__ __forceinline__ uint32_t pack4(const uint4& q) {
    uint32_t ab, cd, p;
    asm volatile("mad.lo.u32 %0, %1, 16, %2;" : "=r"(ab) : "r"(q.y), "r"(q.x));
    asm volatile("mad.lo.u32 %0, %1, 16, %2;" : "=r"(cd) : "r"(q.w), "r"(q.z));
    asm volatile("mad.lo.u32 %0, %1, 256, %2;" : "=r"(p) : "r"(cd), "r"(ab));
    return p;
}
__device__ __forceinline__ void lookup4(uint32_t p, const Lut& t, uint32_t& w01, uint32_t& w23) {
    const uint32_t t8 = p & 0x8888u, s7 = p & 0x7777u;
    const uint32_t sel = (t8 >> 1) + 0x3210u;
    const uint32_t lo = prmt(prmt(t.lo[0], t.lo[1], p), prmt(t.lo[2], t.lo[3], s7), sel);
    const uint32_t hi = prmt(prmt(t.hi[0], t.hi[1], p), prmt(t.hi[2], t.hi[3], s7), sel);
    w01 = prmt(lo, hi, 0x5140);
    w23 = prmt(lo, hi, 0x7362);
}
__device__ __forceinline__ uint4 dequant8(uint32_t p0, uint32_t p1, const uint4& sc, const Lut& t) {
    uint4 r;
    lookup4(p0, t, r.x, r.y);
    lookup4(p1, t, r.z, r.w);
    r.x = mul_bf16x2(r.x, sc.x); r.y = mul_bf16x2(r.y, sc.y); r.z = mul_bf16x2(r.z, sc.z); r.w = mul_bf16x2(r.w, sc.w);
    return r;
}
__device__ __forceinline__ void fence_async_smem() { asm volatile("fence.proxy.async.shared::cta;" ::: "memory"); }

template <int SCALE_D, int BHI, uint32_t AHI = 0x40000040u>
__device__ __forceinline__ void wgmma224(float (&d)[112], uint32_t descA, uint32_t descB) {
    asm volatile(
        "{\n.reg .pred p;\n.reg .b64 da, db;\nsetp.ne.b32 p, %114, 0;\n"
        "mov.b64 da, {%112, %116};\nmov.b64 db, {%113, %115};\n"
        "wgmma.mma_async.sync.aligned.m64n224k16.f32.bf16.bf16 "
        "{%0, %1, %2, %3, %4, %5, %6, %7, %8, %9, %10, %11, %12, %13, %14, %15, "
        "%16, %17, %18, %19, %20, %21, %22, %23, %24, %25, %26, %27, %28, %29, %30, %31, "
        "%32, %33, %34, %35, %36, %37, %38, %39, %40, %41, %42, %43, %44, %45, %46, %47, "
        "%48, %49, %50, %51, %52, %53, %54, %55, %56, %57, %58, %59, %60, %61, %62, %63, "
        "%64, %65, %66, %67, %68, %69, %70, %71, %72, %73, %74, %75, %76, %77, %78, %79, "
        "%80, %81, %82, %83, %84, %85, %86, %87, %88, %89, %90, %91, %92, %93, %94, %95, "
        "%96, %97, %98, %99, %100, %101, %102, %103, %104, %105, %106, %107, %108, %109, %110, %111}, "
        "da, db, p, 1, 1, 0, 1;\n}\n"
        : "+f"(d[0]), "+f"(d[1]), "+f"(d[2]), "+f"(d[3]), "+f"(d[4]), "+f"(d[5]), "+f"(d[6]), "+f"(d[7]),
          "+f"(d[8]), "+f"(d[9]), "+f"(d[10]), "+f"(d[11]), "+f"(d[12]), "+f"(d[13]), "+f"(d[14]), "+f"(d[15]),
          "+f"(d[16]), "+f"(d[17]), "+f"(d[18]), "+f"(d[19]), "+f"(d[20]), "+f"(d[21]), "+f"(d[22]), "+f"(d[23]),
          "+f"(d[24]), "+f"(d[25]), "+f"(d[26]), "+f"(d[27]), "+f"(d[28]), "+f"(d[29]), "+f"(d[30]), "+f"(d[31]),
          "+f"(d[32]), "+f"(d[33]), "+f"(d[34]), "+f"(d[35]), "+f"(d[36]), "+f"(d[37]), "+f"(d[38]), "+f"(d[39]),
          "+f"(d[40]), "+f"(d[41]), "+f"(d[42]), "+f"(d[43]), "+f"(d[44]), "+f"(d[45]), "+f"(d[46]), "+f"(d[47]),
          "+f"(d[48]), "+f"(d[49]), "+f"(d[50]), "+f"(d[51]), "+f"(d[52]), "+f"(d[53]), "+f"(d[54]), "+f"(d[55]),
          "+f"(d[56]), "+f"(d[57]), "+f"(d[58]), "+f"(d[59]), "+f"(d[60]), "+f"(d[61]), "+f"(d[62]), "+f"(d[63]),
          "+f"(d[64]), "+f"(d[65]), "+f"(d[66]), "+f"(d[67]), "+f"(d[68]), "+f"(d[69]), "+f"(d[70]), "+f"(d[71]),
          "+f"(d[72]), "+f"(d[73]), "+f"(d[74]), "+f"(d[75]), "+f"(d[76]), "+f"(d[77]), "+f"(d[78]), "+f"(d[79]),
          "+f"(d[80]), "+f"(d[81]), "+f"(d[82]), "+f"(d[83]), "+f"(d[84]), "+f"(d[85]), "+f"(d[86]), "+f"(d[87]),
          "+f"(d[88]), "+f"(d[89]), "+f"(d[90]), "+f"(d[91]), "+f"(d[92]), "+f"(d[93]), "+f"(d[94]), "+f"(d[95]),
          "+f"(d[96]), "+f"(d[97]), "+f"(d[98]), "+f"(d[99]), "+f"(d[100]), "+f"(d[101]), "+f"(d[102]), "+f"(d[103]),
          "+f"(d[104]), "+f"(d[105]), "+f"(d[106]), "+f"(d[107]), "+f"(d[108]), "+f"(d[109]), "+f"(d[110]), "+f"(d[111])
        : "r"(descA), "r"(descB), "n"(SCALE_D), "n"(BHI), "n"(AHI));
}

template <int SCALE_D, int BHI, uint32_t AHI = 0x40000040u>
__device__ __forceinline__ void wgmma128(float (&d)[64], uint32_t descA, uint32_t descB) {
    asm volatile(
        "{\n.reg .pred p;\n.reg .b64 da, db;\nsetp.ne.b32 p, %66, 0;\n"
        "mov.b64 da, {%64, %68};\nmov.b64 db, {%65, %67};\n"
        "wgmma.mma_async.sync.aligned.m64n128k16.f32.bf16.bf16 "
        "{%0, %1, %2, %3, %4, %5, %6, %7, %8, %9, %10, %11, %12, %13, %14, %15, "
        "%16, %17, %18, %19, %20, %21, %22, %23, %24, %25, %26, %27, %28, %29, %30, %31, "
        "%32, %33, %34, %35, %36, %37, %38, %39, %40, %41, %42, %43, %44, %45, %46, %47, "
        "%48, %49, %50, %51, %52, %53, %54, %55, %56, %57, %58, %59, %60, %61, %62, %63}, "
        "da, db, p, 1, 1, 0, 1;\n}\n"
        : "+f"(d[0]), "+f"(d[1]), "+f"(d[2]), "+f"(d[3]), "+f"(d[4]), "+f"(d[5]), "+f"(d[6]), "+f"(d[7]),
          "+f"(d[8]), "+f"(d[9]), "+f"(d[10]), "+f"(d[11]), "+f"(d[12]), "+f"(d[13]), "+f"(d[14]), "+f"(d[15]),
          "+f"(d[16]), "+f"(d[17]), "+f"(d[18]), "+f"(d[19]), "+f"(d[20]), "+f"(d[21]), "+f"(d[22]), "+f"(d[23]),
          "+f"(d[24]), "+f"(d[25]), "+f"(d[26]), "+f"(d[27]), "+f"(d[28]), "+f"(d[29]), "+f"(d[30]), "+f"(d[31]),
          "+f"(d[32]), "+f"(d[33]), "+f"(d[34]), "+f"(d[35]), "+f"(d[36]), "+f"(d[37]), "+f"(d[38]), "+f"(d[39]),
          "+f"(d[40]), "+f"(d[41]), "+f"(d[42]), "+f"(d[43]), "+f"(d[44]), "+f"(d[45]), "+f"(d[46]), "+f"(d[47]),
          "+f"(d[48]), "+f"(d[49]), "+f"(d[50]), "+f"(d[51]), "+f"(d[52]), "+f"(d[53]), "+f"(d[54]), "+f"(d[55]),
          "+f"(d[56]), "+f"(d[57]), "+f"(d[58]), "+f"(d[59]), "+f"(d[60]), "+f"(d[61]), "+f"(d[62]), "+f"(d[63])
        : "r"(descA), "r"(descB), "n"(SCALE_D), "n"(BHI), "n"(AHI));
}

template <int SCALE_D, int BHI, uint32_t AHI = 0x40000040u>
__device__ __forceinline__ void wgmma96(float (&d)[48], uint32_t descA, uint32_t descB) {
    asm volatile(
        "{\n.reg .pred p;\n.reg .b64 da, db;\nsetp.ne.b32 p, %50, 0;\n"
        "mov.b64 da, {%48, %52};\nmov.b64 db, {%49, %51};\n"
        "wgmma.mma_async.sync.aligned.m64n96k16.f32.bf16.bf16 "
        "{%0, %1, %2, %3, %4, %5, %6, %7, %8, %9, %10, %11, %12, %13, %14, %15, "
        "%16, %17, %18, %19, %20, %21, %22, %23, %24, %25, %26, %27, %28, %29, %30, %31, "
        "%32, %33, %34, %35, %36, %37, %38, %39, %40, %41, %42, %43, %44, %45, %46, %47}, "
        "da, db, p, 1, 1, 0, 1;\n}\n"
        : "+f"(d[0]), "+f"(d[1]), "+f"(d[2]), "+f"(d[3]), "+f"(d[4]), "+f"(d[5]), "+f"(d[6]), "+f"(d[7]),
          "+f"(d[8]), "+f"(d[9]), "+f"(d[10]), "+f"(d[11]), "+f"(d[12]), "+f"(d[13]), "+f"(d[14]), "+f"(d[15]),
          "+f"(d[16]), "+f"(d[17]), "+f"(d[18]), "+f"(d[19]), "+f"(d[20]), "+f"(d[21]), "+f"(d[22]), "+f"(d[23]),
          "+f"(d[24]), "+f"(d[25]), "+f"(d[26]), "+f"(d[27]), "+f"(d[28]), "+f"(d[29]), "+f"(d[30]), "+f"(d[31]),
          "+f"(d[32]), "+f"(d[33]), "+f"(d[34]), "+f"(d[35]), "+f"(d[36]), "+f"(d[37]), "+f"(d[38]), "+f"(d[39]),
          "+f"(d[40]), "+f"(d[41]), "+f"(d[42]), "+f"(d[43]), "+f"(d[44]), "+f"(d[45]), "+f"(d[46]), "+f"(d[47])
        : "r"(descA), "r"(descB), "n"(SCALE_D), "n"(BHI), "n"(AHI));
}

template <int BHI>
__device__ __forceinline__ void wgmma128r(float (&d)[64], const uint4& a, uint32_t descB) {
    asm volatile(
        "{\n.reg .pred p;\n.reg .b64 db;\nsetp.eq.b32 p, 0, 0;\n"
        "mov.b64 db, {%68, %69};\n"
        "wgmma.mma_async.sync.aligned.m64n128k16.f32.bf16.bf16 "
        "{%0, %1, %2, %3, %4, %5, %6, %7, %8, %9, %10, %11, %12, %13, %14, %15, "
        "%16, %17, %18, %19, %20, %21, %22, %23, %24, %25, %26, %27, %28, %29, %30, %31, "
        "%32, %33, %34, %35, %36, %37, %38, %39, %40, %41, %42, %43, %44, %45, %46, %47, "
        "%48, %49, %50, %51, %52, %53, %54, %55, %56, %57, %58, %59, %60, %61, %62, %63}, "
        "{%64, %65, %66, %67}, db, p, 1, 1, 1;\n}\n"
        : "+f"(d[0]), "+f"(d[1]), "+f"(d[2]), "+f"(d[3]), "+f"(d[4]), "+f"(d[5]), "+f"(d[6]), "+f"(d[7]),
          "+f"(d[8]), "+f"(d[9]), "+f"(d[10]), "+f"(d[11]), "+f"(d[12]), "+f"(d[13]), "+f"(d[14]), "+f"(d[15]),
          "+f"(d[16]), "+f"(d[17]), "+f"(d[18]), "+f"(d[19]), "+f"(d[20]), "+f"(d[21]), "+f"(d[22]), "+f"(d[23]),
          "+f"(d[24]), "+f"(d[25]), "+f"(d[26]), "+f"(d[27]), "+f"(d[28]), "+f"(d[29]), "+f"(d[30]), "+f"(d[31]),
          "+f"(d[32]), "+f"(d[33]), "+f"(d[34]), "+f"(d[35]), "+f"(d[36]), "+f"(d[37]), "+f"(d[38]), "+f"(d[39]),
          "+f"(d[40]), "+f"(d[41]), "+f"(d[42]), "+f"(d[43]), "+f"(d[44]), "+f"(d[45]), "+f"(d[46]), "+f"(d[47]),
          "+f"(d[48]), "+f"(d[49]), "+f"(d[50]), "+f"(d[51]), "+f"(d[52]), "+f"(d[53]), "+f"(d[54]), "+f"(d[55]),
          "+f"(d[56]), "+f"(d[57]), "+f"(d[58]), "+f"(d[59]), "+f"(d[60]), "+f"(d[61]), "+f"(d[62]), "+f"(d[63])
        : "r"(a.x), "r"(a.y), "r"(a.z), "r"(a.w), "r"(descB), "n"(BHI));
}

template <int BHI>
__device__ __forceinline__ void wgmma96r(float (&d)[48], const uint4& a, uint32_t descB) {
    asm volatile(
        "{\n.reg .pred p;\n.reg .b64 db;\nsetp.eq.b32 p, 0, 0;\n"
        "mov.b64 db, {%52, %53};\n"
        "wgmma.mma_async.sync.aligned.m64n96k16.f32.bf16.bf16 "
        "{%0, %1, %2, %3, %4, %5, %6, %7, %8, %9, %10, %11, %12, %13, %14, %15, "
        "%16, %17, %18, %19, %20, %21, %22, %23, %24, %25, %26, %27, %28, %29, %30, %31, "
        "%32, %33, %34, %35, %36, %37, %38, %39, %40, %41, %42, %43, %44, %45, %46, %47}, "
        "{%48, %49, %50, %51}, db, p, 1, 1, 1;\n}\n"
        : "+f"(d[0]), "+f"(d[1]), "+f"(d[2]), "+f"(d[3]), "+f"(d[4]), "+f"(d[5]), "+f"(d[6]), "+f"(d[7]),
          "+f"(d[8]), "+f"(d[9]), "+f"(d[10]), "+f"(d[11]), "+f"(d[12]), "+f"(d[13]), "+f"(d[14]), "+f"(d[15]),
          "+f"(d[16]), "+f"(d[17]), "+f"(d[18]), "+f"(d[19]), "+f"(d[20]), "+f"(d[21]), "+f"(d[22]), "+f"(d[23]),
          "+f"(d[24]), "+f"(d[25]), "+f"(d[26]), "+f"(d[27]), "+f"(d[28]), "+f"(d[29]), "+f"(d[30]), "+f"(d[31]),
          "+f"(d[32]), "+f"(d[33]), "+f"(d[34]), "+f"(d[35]), "+f"(d[36]), "+f"(d[37]), "+f"(d[38]), "+f"(d[39]),
          "+f"(d[40]), "+f"(d[41]), "+f"(d[42]), "+f"(d[43]), "+f"(d[44]), "+f"(d[45]), "+f"(d[46]), "+f"(d[47])
        : "r"(a.x), "r"(a.y), "r"(a.z), "r"(a.w), "r"(descB), "n"(BHI));
}

__device__ __forceinline__ uint32_t opq(uint32_t v) { asm volatile("" : "+r"(v)); return v; }
template <int I> struct IC { static constexpr int value = I; };
template <int B, int E, class F> __device__ __forceinline__ void static_for(F&& f) {
    if constexpr (B < E) { f(IC<B>{}); static_for<B + 1, E>(f); }
}

__device__ __forceinline__ void tma_store_2d(const CUtensorMap* tm, uint32_t src, int c0, int c1) {
    asm volatile("cp.async.bulk.tensor.2d.global.shared::cta.bulk_group [%0, {%2, %3}], [%1];" ::"l"(tm), "r"(src), "r"(c0), "r"(c1) : "memory");
}
__device__ __forceinline__ void bulk_store(void* dst, uint32_t src, uint32_t bytes) {
    asm volatile("cp.async.bulk.global.shared::cta.bulk_group [%0], [%1], %2;" ::"l"(dst), "r"(src), "r"(bytes) : "memory");
}
__device__ __forceinline__ void bulk_commit() { asm volatile("cp.async.bulk.commit_group;" ::: "memory"); }
template <int N> __device__ __forceinline__ void bulk_wait_read() { asm volatile("cp.async.bulk.wait_group.read %0;" ::"n"(N) : "memory"); }
__device__ __forceinline__ void bar_arrive(int id) { asm volatile("bar.arrive %0, 256;" ::"r"(id) : "memory"); }
__device__ __forceinline__ void bar_sync(int id) { asm volatile("bar.sync %0, 256;" ::"r"(id) : "memory"); }
template <int NC, int OFF, int N>
__device__ __forceinline__ void stage_cols(const float (&acc)[N], uint32_t stg) {
    int lane; asm volatile("mov.u32 %0, %%laneid;" : "=r"(lane));
    const int r = lane & 15;
    const uint32_t a0 = NC == 64 ? stg + r * 128 + (((lane >> 4) ^ (r & 7)) << 4) : stg + r * 64 + (((lane >> 4) ^ ((r >> 1) & 3)) << 4);
#pragma unroll
    for (int j = 0; j < NC / 16; j++) {
        const int i = OFF + 8 * j;
        stmatrix_x4(a0 ^ (j * 32), pack_bf16(acc[i], acc[i + 1]), pack_bf16(acc[i + 2], acc[i + 3]), pack_bf16(acc[i + 4], acc[i + 5]), pack_bf16(acc[i + 6], acc[i + 7]));
    }
}
__device__ __forceinline__ void send(uint32_t stg, const CUtensorMap* tmo, int col, int row) {
    fence_async_smem();
    __syncwarp();
    if (elect()) { tma_store_2d(tmo, stg, col, row); bulk_commit(); }
    __syncwarp();
}

__host__ __device__ constexpr int rslot(int u) { return (2 * u) % 3; }
__host__ __device__ constexpr int roff(int slot) { return slot < 2 ? slot * UNIT : RAW2_OFF - RAW_OFF; }
__host__ __device__ constexpr int rpar(int u) { return (u / 3 - (u % 3 == 0)) & 1; }
__host__ __device__ constexpr int sslot(int c) { return c < 3 ? c + 3 : c % 3; }
__host__ __device__ constexpr int vturn(int v) {
    return v < 20 ? v : v == 20 ? -21 : v == 21 ? -22 : v == 22 ? 21 : v == 23 ? -20 : v == 24 ? 20 : v < 29 ? v - 3 : v == 29 ? -24 : v == 30 ? -25 : 27;
}
__host__ __device__ constexpr int uoff(int v) { return vturn(v) < 0 ? RAW_OFF + roff(rslot(-vturn(v))) : W_OFF + (vturn(v) % NW) * UNIT; }
__host__ __device__ constexpr int ubar(int v) { return vturn(v) < 0 ? 96 + 8 * rslot(-vturn(v)) : 16 * (vturn(v) % NW); }
__host__ __device__ constexpr int upar(int v) { return vturn(v) < 0 ? rpar(-vturn(v)) : (vturn(v) / NW) & 1; }
__host__ __device__ constexpr int utime(int v) {
    return v < 22 ? v + 15 : v == 22 || v == 25 ? 38 : v < 25 ? 40 : v < 28 ? 42 : 44;
}
__host__ __device__ constexpr uint32_t bdesc(int s) { return (uint32_t)(((0x400 + uoff(s >> 1)) >> 4) | ((7168u >> 4) << 16)) + (s & 1) * 224; }

__global__ void __cluster_dims__(2, 1, 1) __launch_bounds__(256, 1)
nf4_gemm_kernel(const int* __restrict__ qw, const __nv_bfloat16* __restrict__ cb, const __nv_bfloat16* __restrict__ absmax,
                uint8_t* __restrict__ wimg, unsigned* __restrict__ gflag,
                const __grid_constant__ CUtensorMap tmx, const __grid_constant__ CUtensorMap tmq, const __grid_constant__ CUtensorMap tmo64,
                const __grid_constant__ CUtensorMap tmo32, const __grid_constant__ CUtensorMap tmqp, const __grid_constant__ CUtensorMap tmx16,
                const __grid_constant__ CUtensorMap tmx64, const __grid_constant__ CUtensorMap tmq1) {
    extern __shared__ __align__(1024) uint8_t smem[];
    const uint32_t sbase = smem_u32(smem);
    const int rank = blockIdx.x, nt = blockIdx.y, pair = blockIdx.z;
    uint4 q[4], c0, c1;
    uint2 sf;
    if (threadIdx.x < 224) {
        const uint32_t t = threadIdx.x;
        const int* p = qw + (uint32_t)((t & 3) * (N_ - 1) + t + blockIdx.x * (8 * N_) + blockIdx.y * BN);
        q[0] = ldg128(p); q[1] = ldg128(p + 4 * N_);
        q[2] = ldg128(p + 16 * N_); q[3] = ldg128(p + 20 * N_);
        const void* ps = absmax + (uint32_t)(opq(t & ~3u) + blockIdx.y * BN);
        asm volatile("ld.global.nc.v2.b32 {%0, %1}, [%2];" : "=r"(sf.x), "=r"(sf.y) : "l"(ps) : "memory");
        c0 = ldg128(cb); c1 = ldg128(cb + 8);
    }
    const unsigned tstart = clk();
    const int mt = pair * 2 + rank;
    const int lane = threadIdx.x & 31;
    const int warp = __reduce_max_sync(~0u, threadIdx.x >> 5);
    const int wg = warp >> 2;
    const uint32_t bars = sbase + BAR_OFF;
    const uint32_t full = bars, rawfull = bars + 96, written = bars + 120, xbar = bars + 144, gbar = bars + 160 + wg * 16;
    const uint32_t rawh = bars + 192 - 8, ebar = bars + 216, ones = bars + 256;
    const uint32_t wbase = sbase + W_OFF;
    __syncwarp();

    auto insert = [](uint64_t m, int pos, int v) { const uint64_t low = (1ull << (4 * pos)) - 1; return (m & low) | ((m & ~low) << 4) | ((uint64_t)v << (4 * pos)); };
    const uint64_t others = (0xedcfedu >> (4 * pair)) & 0xfff;
    const uint64_t cmap = insert(insert(0x76543210ull, G1, 8 + pair), G2, 12 + pair) | ((others - 0x444) << 40) | (others << 52);
    auto chunk = [&](int i) { return (int)(cmap >> (4 * i)) & 15; };
    unsigned* flag = gflag + nt * 32;
    uint8_t* wpan = wimg + nt * (16 * UNIT);
    auto load_x = [&](int i, int slot, uint32_t bar) {
        tma_load_2d(sbase + slot * 32768, &tmx, chunk(i) * 64, mt * BM, bar);
        tma_load_2d(sbase + slot * 32768 + 16384, &tmx, chunk(i) * 64, mt * BM + 128, bar);
    };
    auto load_l = [&](int i, int slot, int g, uint32_t bar) {
        tma_load_2d(sbase + slot * 32768 + g * 16384, &tmx64, chunk(i) * 64, mt * BM + g * 128, bar);
        tma_load_2d(sbase + slot * 32768 + g * 16384 + 8192, &tmx64, chunk(i + 1) * 64, mt * BM + g * 128, bar);
    };
    auto snap = [&](int ss, uint32_t bar) { bulk_load(sbase + SC_OFF + ss * SC_STRIDE + 448, flag, 16, bar); };
    auto load_sc = [&](int i, int ss, uint32_t bar) {
        bulk_load(sbase + SC_OFF + ss * SC_STRIDE, absmax + chunk(i) * N_ + nt * BN, 448, bar);
    };
    auto load_raw = [&](int u, int slot) {
        mbar_expect_tx(rawfull + 8 * slot, UNIT);
        tma_load_5d(sbase + RAW_OFF + roff(slot), &tmq, 0, 0, nt * 7, rank, 4 * chunk(u >> 1) + 2 * (u & 1), rawfull + 8 * slot);
    };
    auto load_half = [&](int b, uint32_t more) {
        const uint32_t bar = (b & 1) ? rawfull + 8 * rslot(b >> 1) : rawh + 8 * (b >> 1);
        mbar_expect_tx(bar, 7168 + more);
        tma_load_5d(sbase + RAW_OFF + roff(rslot(b >> 1)) + (b & 1) * 7168, &tmq1, 0, 0, nt * 7, rank, b, bar);
    };
    auto load_w = [&](int v) {
        mbar_expect_tx(bars + ubar(v), UNIT + (!(v & 1) && v <= 24 ? 32768 : 0) + (v == 21 ? 16 : 0));
        bulk_load(sbase + uoff(v), wpan + (2 * (chunk(v >> 1) - 8) + (v & 1)) * UNIT, UNIT, bars + ubar(v));
    };
    auto prefetch_q = [&](int c) { if (c + PFQ < 8) tma_prefetch_2d(&tmqp, nt * BN, (c + PFQ) * 64 + pair * 16 + rank * 8); };
    auto prefetch_g = [&](int c) {
        if (c < 6) {
            const int k = c, k0 = k + (k >= 3);
            tma_prefetch_2d(&tmqp, nt * BN, (8 + (k0 & 4) + pair) * 64 + (k0 & 3) * 16 + rank * 8);
            if (k == 1 || k == 4) tma_prefetch_2d(&tmqp, nt * BN, (8 + (k0 & 4) + pair) * 64 + 48 + rank * 8);
        }
    };
    auto prefetch_x = [&](int i) { tma_prefetch_2d(&tmx16, chunk(i) * 64, mt * BM + nt * 16); };
    if (warp == 7) {
        if (elect()) {
            mbar_init(xbar, 1); mbar_init(rawh + 8, 1); mbar_init(rawfull + 8 * rslot(1), 1); mbar_init(xbar + 8, 1);
            fence_async_smem();
            load_half(2, 448);
            bulk_load(sbase + SC_OFF + sslot(0) * SC_STRIDE, absmax + nt * BN, 448, rawh + 8);
            load_half(3, 0);
            mbar_expect_tx(xbar, 16384);
            tma_load_2d(sbase, &tmx, 0, mt * BM, xbar);
            mbar_expect_tx(xbar + 8, 16384);
            tma_load_2d(sbase + 16384, &tmx, 0, mt * BM + 128, xbar + 8);
            mbar_init(rawfull + 8 * rslot(2), 1); mbar_init(rawfull + 8 * rslot(3), 1); mbar_init(rawh + 16, 1); mbar_init(rawh + 24, 1);
            mbar_init(ebar, 7); mbar_init(ebar + 8, 7);
            sts128(ones, make_uint4(1, 0, 0, 0)); sts128(ones + 16, make_uint4(0, 1, 0, 0));
#pragma unroll
            for (int s = 0; s < 12; s++) { mbar_init(full + 8 * s, 1); if (s < 4) mbar_arrive(full + 8 * s); }
#pragma unroll
            for (int s = 0; s < 3; s++) mbar_init(written + 8 * s, 7);
#pragma unroll
            for (int s = 0; s < 4; s++) mbar_init(bars + 160 + 8 * s, 4);
            asm volatile("fence.mbarrier_init.release.cluster;" ::: "memory");
            fence_async_smem();
            if ((sbase & 0xffffff) != 0x400) __trap();
        }
        __syncwarp();
        cluster_arrive();
        if (elect()) {
            asm volatile("prefetch.tensormap [%0];" ::"l"(&tmq) : "memory");
            asm volatile("prefetch.tensormap [%0];" ::"l"(&tmqp) : "memory");
            asm volatile("prefetch.tensormap [%0];" ::"l"(&tmx16) : "memory");
            asm volatile("prefetch.tensormap [%0];" ::"l"(&tmx64) : "memory");
            while (clk() - tstart < T2) { }
            load_half(4, 2 * 448 + 16);
            load_sc(1, sslot(1), rawh + 16); load_sc(2, sslot(2), rawh + 16); snap(sslot(1), rawh + 16);
            load_half(5, 0);
            while (clk() - tstart < T2B) { }
            tma_load_2d(sbase + 32768, &tmx, 64, mt * BM, full + 32);
            load_half(6, 0); load_half(7, 0);
            tma_load_2d(sbase + 32768 + 16384, &tmx, 64, mt * BM + 128, full + 32);
            load_sc(3, sslot(3), full + 48);
            while (clk() - tstart < T3) { }
            prefetch_q(-2); prefetch_q(-1);
            asm volatile("cp.async.bulk.prefetch.L2.global [%0], 448;" ::"l"(absmax + (2 * mt) * N_ + nt * BN) : "memory");
            asm volatile("cp.async.bulk.prefetch.L2.global [%0], 448;" ::"l"(absmax + (2 * mt + 1) * N_ + nt * BN) : "memory");
        }
        __syncwarp();
        cluster_wait();
    } else {
        cluster_arrive();
    }
    const uint32_t rsrc = __shfl_sync(~0u, sbase + RAW_OFF + warp * 1024 + (lane & 7) * 128 + ((((lane >> 3) * 2) ^ (lane & 7)) << 4), lane);
    const uint32_t ssrc = sbase + SC_OFF + warp * 64;
    const int wpos = (nt & 1) ? (0x73210546 >> (4 * warp)) & 7 : warp;
    const uint32_t wown = wbase + rank * 7168 + wpos * 512;
    const uint32_t wdst = __shfl_sync(~0u, wown + lane * 16, lane);
    auto get_sc = [&](int ss) { return lds128(((opq(wdst) >> 3) & 0x30) + ssrc + ss * SC_STRIDE); };
    const uint32_t whalf = wbase + rank * 7168;
    const uint32_t pwhalf = mapa(whalf, rank ^ 1), pbars = mapa(bars, rank ^ 1);
    Lut lut;
    uint4 sc;
    uint4 q0, q1;
    auto fetch = [&](int slot, int h) {
        q0 = lds128(rsrc + roff(slot) + h * 7168);
        q1 = lds128((opq(rsrc) ^ 16) + roff(slot) + h * 7168);
    };
    auto signal = [&](uint32_t bar) { __syncwarp(); if (elect()) mbar_arrive(bar); __syncwarp(); };
    auto convert = [&](int ws, int h, bool w1, uint32_t bar1, uint32_t par1, bool w2, uint32_t bar2, uint32_t par2, bool next, int rsn,
                       bool sig, uint32_t sbar, bool scales, int cs) {
        bool ok1 = true, ok2 = true;
        if (w2) ok2 = mbar_try(bar2, par2);
        if (w1) ok1 = mbar_try(bar1, par1);
        uint4 w = dequant8(pack4(q0), pack4(q1), sc, lut);
        asm volatile("" : "+r"(w.x), "+r"(w.y), "+r"(w.z), "+r"(w.w));
        if (w1 && w2) mbar_wait2(bar2, par2, bar1, par1, ok1 && ok2);
        else if (w2) mbar_wait1(bar2, par2, ok2);
        else if (w1) mbar_wait1(bar1, par1, ok1);
        if (next) fetch(rsn, h ^ 1);
        sts128(wdst + ws * UNIT + h * 3584, w);
        if (sig) signal(sbar);
        if (scales) sc = get_sc(cs);
    };
    auto hand_over = [&](uint32_t sbar, uint32_t par, int ws, int h, uint32_t more, bool raw, int un, int rs, auto extra) {
        mbar_wait(sbar, par);
        fence_async_smem();
        if (elect()) {
            if (raw) load_raw(un, rs);
            copy_to_peer(pwhalf + ws * UNIT + h * 3584, whalf + ws * UNIT + h * 3584, 3584, pbars + 8 * (2 * ws + h));
            mbar_expect_tx(full + 8 * (2 * ws + h), 3584 + more);
            extra();
        }
        __syncwarp();
    };
    auto share = [&](int g, uint32_t o, uint32_t n) {
        bulk_store(wpan + 2 * (chunk(g) - 8) * UNIT + rank * 7168 + o, whalf + 2 * (g % 3) * UNIT + o, n);
        bulk_commit();
    };
    auto publish = [&](int k) {
        asm volatile("cp.async.bulk.wait_group 0;" ::: "memory");
        asm volatile("cp.reduce.async.bulk.global.shared::cta.bulk_group.add.u32 [%0], [%1], 16;" ::"l"(flag), "r"(ones + 16 * k) : "memory");
    };
    auto check = [&](int k, int ss) {
        unsigned f0, f1;
        asm volatile("ld.shared.u32 %0, [%1];" : "=r"(f0) : "r"(sbase + SC_OFF + sslot(1) * SC_STRIDE + 448 + 4 * k) : "memory");
        asm volatile("ld.shared.u32 %0, [%1];" : "=r"(f1) : "r"(sbase + SC_OFF + ss * SC_STRIDE + 448 + 4 * k) : "memory");
        asm volatile("{\n.reg .pred p;\n.reg .u32 n, d;\nmov.u32 n, 0;\nLAB_POLL:\nsub.u32 d, %0, %1;\nsetp.ge.u32 p, d, 8;\n@p bra.uni LAB_DONE;\n"
                     "ld.relaxed.gpu.global.u32 %0, [%2];\nadd.u32 n, n, 1;\nsetp.lt.u32 p, n, 0x10000;\n@p bra.uni LAB_POLL;\nLAB_DONE:\n}\n"
                     : "+r"(f1) : "r"(f0 & ~7u), "l"(flag + k) : "memory");
    };
    auto sig_bar = [&](int b) { return written + 8 * (b % 3); };
    auto sig_par = [](int b) { return (b / 3 - 1) & 1; };
    auto see = [&](int s) { if (s < 2 * NU) mbar_wait(full + 8 * (s % 12), (s / 12) & 1); else mbar_wait(bars + ubar(s >> 1), upar(s >> 1)); };
    auto block = [&](int b, int sn) {
        const int u = b >> 1, h = b & 1;
        const bool next = b + 1 < 2 * NU;
        convert(u % NW, h, sn == 2 || sn >= 4, sn == 2 ? ebar + 8 : full + 8 * (sn % 12), (sn / 12) & 1,
                next && (h || b < 8), b == 5 ? rawh + 24 : rawfull + 8 * rslot((b + 1) >> 1), b == 5 ? 0 : rpar((b + 1) >> 1),
                next, rslot((b + 1) >> 1), true, sig_bar(b), (b & 3) == 3 && next, sslot((b + 1) >> 2));
    };
    auto hand = [&](int b, auto extra) {
        const int u = b >> 1;
        hand_over(sig_bar(b), sig_par(b), u % NW, b & 1, (b & 3) == 0 ? 32768 : (b & 3) == 2 && b < 36 ? 448 : b == 35 ? 16 : 0, (b & 1) && u + NR < NU, u + NR, rslot(u), extra);
    };
    auto pass_on = [&](int u) {
        fence_async_smem();
        __syncwarp();
        if (elect()) {
            const uint32_t o = wpos * 512 + u * UNIT;
            copy_to_peer(pwhalf + o, whalf + o, 512, pbars + 216 + 8 * u);
            copy_to_peer(pwhalf + o + 3584, whalf + o + 3584, 512, pbars + 216 + 8 * u);
            if (u == 1) mbar_arrive(sig_bar(3));
            mbar_expect_tx(ebar + 8 * u, 1024);
        }
        __syncwarp();
    };
    bool ok0 = false;
    if (warp < 7) {
        lut.lo[0] = __byte_perm(c0.x, c0.y, 0x6420); lut.hi[0] = __byte_perm(c0.x, c0.y, 0x7531);
        lut.lo[1] = __byte_perm(c0.z, c0.w, 0x6420); lut.hi[1] = __byte_perm(c0.z, c0.w, 0x7531);
        lut.lo[2] = __byte_perm(c1.x, c1.y, 0x6420); lut.hi[2] = __byte_perm(c1.x, c1.y, 0x7531);
        lut.lo[3] = __byte_perm(c1.z, c1.w, 0x6420); lut.hi[3] = __byte_perm(c1.z, c1.w, 0x7531);
        const uint32_t d = wown + (lane >> 3) * 128 + (lane & 3) * 16 + (lane & 4) * 2;
#pragma unroll
        for (int j = 0; j < 4; j++) {
            uint32_t a, b;
            lookup4(pack4(q[j]), lut, a, b);
            asm volatile("st.shared.v2.b32 [%0], {%1, %2};" ::"r"(d + (j >> 1) * 3584 + (j & 1) * 64), "r"(mul_bf16x2(a, sf.x)), "r"(mul_bf16x2(b, sf.y)) : "memory");
        }
        cluster_wait();
        pass_on(0);
        mbar_wait(rawh + 8, 0);
        const uint4 a0 = lds128(rsrc + roff(rslot(1))), a1 = lds128((rsrc ^ 16) + roff(rslot(1))), s0 = get_sc(sslot(0));
        mbar_wait(rawfull + 8 * rslot(1), 0);
        const uint4 a2 = lds128(rsrc + roff(rslot(1)) + 7168), a3 = lds128((rsrc ^ 16) + roff(rslot(1)) + 7168);
        sts128(wdst + UNIT, dequant8(pack4(a0), pack4(a1), s0, lut));
        sts128(wdst + UNIT + 3584, dequant8(pack4(a2), pack4(a3), s0, lut));
        ok0 = mbar_try(xbar + 8 * wg, 0) & mbar_try(ebar, 0);
        pass_on(1);
    }
    mbar_wait2(xbar + 8 * wg, 0, ebar, 0, ok0);

    float acc0[112], acc1[112];
    const uint32_t descA = ((0x400 + wg * 16384) >> 4) | (1u << 16);
    auto mma = [&](int s) {
        const uint32_t da = opq(descA) + ((s >> 2) % 3) * (32768 >> 4) + (s & 3) * 2;
        wgmma_fence();
        wgmma224<1, 8>(acc0, da, bdesc(s)); wgmma224<1, 8>(acc1, da + 512, bdesc(s));
        wgmma_commit();
        wgmma_wait<2>();
    };
    wgmma_fence();
    wgmma224<0, 8>(acc0, descA, bdesc(0)); wgmma224<0, 8>(acc1, descA + 512, bdesc(0));
    wgmma_commit();
    mma(1);
    if (warp < 7) {
        mbar_wait(rawh + 16, 0); fetch(rslot(2), 0); sc = get_sc(sslot(1));
        block(4, 2);
    } else {
        mbar_wait(sig_bar(3), sig_par(3));
        if (elect()) { load_raw(4, rslot(4)); load_x(2, 2, full + 64); prefetch_q(0); prefetch_x(3); prefetch_g(0); }
        __syncwarp();
        mbar_wait(ebar + 8, 0);
    }
    static_for<2, 8>([&](auto S) {
        constexpr int s = S.value;
        mma(s);
        if (warp < 7) { if (s <= 3) block(s + 3, s < 3 ? s + 1 : -1); if (s >= 3) block(s + 4, s + 1); }
        else {
            if (s <= 3) hand(s + 2, [] {});
            if (s >= 3) hand(s + 3, [&] {
                if (s == 4) prefetch_q(1);
                if (s == 5) { load_sc(4, sslot(4), full + 80); prefetch_g(1); }
                if (s == 6) prefetch_x(4);
                if (s == 7) load_x(3, 0, full);
            });
            if (s >= 3) see(s + 1);
        }
    });
    {
        uint32_t ph = 0;
#pragma unroll 1
        for (int cb = 2; cb < 8; cb += 3)
          static_for<2, 5>([&](auto I) {
            constexpr int cc = I.value;
            constexpr int j0 = cc % 3, j1 = (cc + 1) % 3, j2 = (cc + 2) % 3;
            const int c = cb + cc - 2;
            auto sh = [&](int h) {
                if ((cc - G1 + 1) % 3 == 0 && h == 1 && c == G1 - 1) share(G1, 0, 3584);
                if ((cc - G1) % 3 == 0 && c == G1) share(G1, h ? UNIT : 3584, 3584);
                if ((cc - G1 - 1) % 3 == 0 && c == G1 + 1) {
                    if (h == 0) { share(G1, UNIT + 3584, 3584); bulk_wait_read<1>(); }
                    else publish(0);
                }
                if ((cc - G2 + 1) % 3 == 0 && h == 1 && c == G2 - 1) share(G2, 0, 3584);
            };
            mma(4 * j0);
            if (warp < 7) convert(2 * j1, 0, true, full + 32 * j0 + 8, ph, false, 0, 0, true, j1, true, sig_bar(4 * cc + 4), false, 0);
            else {
                const bool ok = mbar_try(full + 32 * j0 + 8, ph);
                hand_over(sig_bar(4 * cc + 3), sig_par(4 * cc + 3), 2 * j0 + 1, 1, 0, true, 2 * c + 4, j2, [&] { prefetch_q(c); if (cc == 4 && c == 7) prefetch_x(12); });
                mbar_wait1(full + 32 * j0 + 8, ph, ok);
            }
            mma(4 * j0 + 1);
            if (warp < 7) convert(2 * j1, 1, true, full + 32 * j0 + 16, ph, true, rawfull + 8 * j0, rpar(2 * cc + 3), true, j0, true, sig_bar(4 * cc + 5), false, 0);
            else {
                const bool ok = mbar_try(full + 32 * j0 + 16, ph);
                hand_over(sig_bar(4 * cc + 4), sig_par(4 * cc + 4), 2 * j1, 0, 32768, false, 0, 0, [&] { load_sc(c + 3, j0, full + 32 * j1 + 16); prefetch_g(c); sh(0); });
                mbar_wait1(full + 32 * j0 + 16, ph, ok);
            }
            mma(4 * j0 + 2);
            if (warp < 7) convert(2 * j1 + 1, 0, true, full + 32 * j0 + 24, ph, false, 0, 0, true, j0, true, sig_bar(4 * cc + 6), false, 0);
            else {
                const bool ok = mbar_try(full + 32 * j0 + 24, ph);
                hand_over(sig_bar(4 * cc + 5), sig_par(4 * cc + 5), 2 * j1, 1, 0, true, 2 * c + 5, j1, [&] { prefetch_x(c + PFX); });
                mbar_wait1(full + 32 * j0 + 24, ph, ok);
            }
            if (j1 == 0) asm volatile("xor.b32 %0, %0, 1;" : "+r"(ph));
            mma(4 * j0 + 3);
            if (warp < 7) convert(2 * j1 + 1, 1, true, full + 32 * j1, ph, true, rawfull + 8 * j2, rpar(2 * cc + 4), true, j2, true, sig_bar(4 * cc + 7), true, j2);
            else {
                const bool ok = mbar_try(full + 32 * j1, ph);
                hand_over(sig_bar(4 * cc + 6), sig_par(4 * cc + 6), 2 * j1 + 1, 0, 448, false, 0, 0, [&] { load_x(c + 2, j2, full + 32 * j2); sh(1); });
                mbar_wait1(full + 32 * j1, ph, ok);
            }
          });
    }
    uint4 fa[8];
    auto get_frag = [&](int f, uint32_t rows, int j0 = 0, int j1 = 4) {
        int ln; asm volatile("mov.u32 %0, %%laneid;" : "=r"(ln));
        const uint32_t a = rows + (ln & 15) * 128 + (((ln >> 4) ^ (ln & 7)) << 4);
#pragma unroll
        for (int j = j0; j < j1; j++) fa[4 * f + j] = ldmatrix_x4(a ^ (j * 32));
    };
    static_for<32, 46>([&](auto S) {
        constexpr int s = S.value;
        constexpr int vb = 40 + (s - 37) / 2;
        mma(s);
        if (s == 39) cluster_arrive();
        if (s == 41) cluster_wait();
        if (s == 36) mbar_wait(rawh + 8, 1);
        if (s >= 36 && s < 40) get_frag(0, sbase + uoff(24) + wg * (uoff(23) - uoff(24)) + (warp & 3) * 2048, s - 36, s - 35);
        if (warp < 7) {
            if (s < 36) block(s + 4, s + 1);
            else {
                if (s & 1) signal(sig_bar(vb));
                if (s < 39 || (s & 1)) see(s + 1);
            }
        } else {
            auto loads = [&] {
                static_for<NU, 30>([&](auto V) { if constexpr (utime(V.value) == s) load_w(V.value); });
                if (s == 32) { share(G2, 3584, 3584); prefetch_x(11); }
                if (s == 33) {
                    mbar_expect_tx(rawh + 8, 16384);
                    tma_load_2d(sbase + uoff(24), &tmx64, chunk(12) * 64, mt * BM + 64, rawh + 8);
                    tma_load_2d(sbase + uoff(23), &tmx64, chunk(12) * 64, mt * BM + 192, rawh + 8);
                    share(G2, UNIT, 3584);
                }
                if (s == 34) share(G2, UNIT + 3584, 3584);
                if (s == 37) prefetch_x(13);
                if (s == 39) snap(1, bars + ubar(21));
                if (s == 41) { prefetch_x(14); prefetch_x(15); }
                if (s == 43) { load_l(12, 0, 0, bars + ubar(24)); load_l(12, 0, 1, bars + ubar(24)); }
                else if ((s & 3) == 3) load_x((s >> 2) + 2, ((s >> 2) + 2) % 3, bars + ubar(2 * (s >> 2) + 4));
                if (s == 44) {
                    asm volatile("prefetch.tensormap [%0];" ::"l"(&tmo64) : "memory");
                    asm volatile("prefetch.tensormap [%0];" ::"l"(&tmo32) : "memory");
                }
                if (s == 45) { mbar_expect_tx(xbar, 16384); load_l(14, 1, 0, xbar); }
                if (s == 45) load_w(30);
                if (s == 37) publish(1);
            };
            if (s == 32) { if (elect()) snap(0, full + 8 * (35 % 12)); __syncwarp(); }
            if (s == 35) check(0, 0);
            if (s == 42) check(1, 1);
            if (s <= 36) hand(s + 3, loads);
            else {
                if (!(s & 1)) mbar_wait(sig_bar(40 + (s - 38) / 2), sig_par(40 + (s - 38) / 2));
                if (s == 45) mbar_wait(sig_bar(vb), sig_par(vb));
                if (elect()) loads();
                __syncwarp();
            }
            if (s < 39 || (s & 1)) see(s + 1);
        }
    });
    if (wg == 1) bar_sync(8);
    mma(46);
    if (warp == 7) {
        wgmma_wait<1>();
        see(48);
        if (elect()) { load_w(31); mbar_expect_tx(xbar + 8, 16384); load_l(14, 1, 1, xbar + 8); }
        __syncwarp();
    }
    mma(47);
    if (wg == 0) bar_arrive(8);
    const uint32_t slice0 = sbase + wg * 16384 + (warp & 3) * 2048;
    auto slc = [&](int p) { return slice0 + (p >> 1) * 32768 + (p & 1) * 8192; };
    const int row0 = mt * BM + wg * 128 + (warp & 3) * 16, odd = nt & 1;
    const int colL = nt * BN + odd * 96, colA = nt * BN + (odd ? 32 : 128), colB = nt * BN + (odd ? 0 : 192);
    auto load_s = [&](int i, int p, uint32_t bar) { tma_load_2d(slc(p), &tmx16, chunk(i) * 64, row0 + 64, bar); };
    const uint32_t tA = opq(descA);
    see(48);
    wgmma_wait<0>();
    float lo0[64], hi0[48], lo1[64], hi1[48];
#pragma unroll
    for (int i = 0; i < 64; i++) { asm volatile("mov.b32 %0, %1;" : "=f"(lo0[i]) : "f"(acc0[i])); asm volatile("mov.b32 %0, %1;" : "=f"(lo1[i]) : "f"(acc1[i])); }
#pragma unroll
    for (int i = 0; i < 48; i++) { asm volatile("mov.b32 %0, %1;" : "=f"(hi0[i]) : "f"(acc0[64 + i])); asm volatile("mov.b32 %0, %1;" : "=f"(hi1[i]) : "f"(acc1[64 + i])); }
    auto tdesc = [&](int p, int s) { return tA + (p >> 1) * (32768 >> 4) + (p & 1) * 512 + (s & 3) * 2; };
    auto ldesc = [&](int s) { return tdesc(s >> 2, s); };
    auto gdesc = [&](int s) { return tdesc(((s >> 2) + 3) % 6, s); };
    if (wg == 1) { mbar_wait(xbar + 8, 1); bar_sync(1); }
    static_for<0, 8>([&](auto V) {
        constexpr int v = 24 + (V.value == 0 || V.value > 3 ? V.value : V.value == 3 ? 1 : V.value + 1), s = 2 * (v - 24);
        if (v == 26) mbar_wait2(bars + ubar(26), upar(26), bars + ubar(27), upar(27), wg);
        else if (v == 28) mbar_wait2(bars + ubar(28), upar(28), xbar, 1, wg);
        else if (v != 24 && v != 27) mbar_wait1(bars + ubar(v), upar(v), wg);
        wgmma_fence();
        wgmma96<1, 8>(hi0, ldesc(s), bdesc(48 + s) + 128);
        wgmma96<1, 8>(hi0, ldesc(s + 1), bdesc(49 + s) + 128);
    });
    wgmma_commit();
    bar_arrive(1 + wg);
    wgmma_wait<0>();
    stage_cols<64, 0>(hi0, slc(4)); send(slc(4), &tmo64, colA, row0);
    stage_cols<32, 32>(hi0, slc(5));
    bar_sync(2 + wg);
    wgmma_fence();
    static_for<0, 7>([&](auto S) { wgmma128<1, 8>(lo0, ldesc(S.value), bdesc(48 + S.value)); });
    wgmma_commit();
    send(slc(5), &tmo32, colB, row0);
    wgmma_fence();
    static_for<7, 16>([&](auto S) { wgmma128<1, 8>(lo0, ldesc(S.value), bdesc(48 + S.value)); });
    wgmma_commit();
    bar_arrive(3 + wg);
    {
        const uint32_t zero = opq(gridDim.x - 2);
#pragma unroll
        for (int j = 0; j < 4; j++) { fa[j].x ^= zero; fa[j].y ^= zero; fa[j].z ^= zero; fa[j].w ^= zero; asm volatile("" : "+r"(fa[j].x), "+r"(fa[j].y), "+r"(fa[j].z), "+r"(fa[j].w)); }
    }
    if (elect()) { mbar_expect_tx(gbar, 4096); bulk_wait_read<0>(); load_s(13, 4, gbar); load_s(14, 5, gbar); }
    __syncwarp();
    wgmma_wait<0>();
    stage_cols<64, 0>(lo0, slc(2));
    if (elect()) { mbar_expect_tx(gbar + 8, 2048); load_s(15, 0, gbar + 8); }
    __syncwarp();
    const bool okg = mbar_try(gbar, 0);
    send(slc(2), &tmo64, colL, row0);
    stage_cols<64, 32>(lo0, slc(3));
    mbar_wait1(gbar, 0, okg);
    auto mma2 = [&](auto I) { constexpr int s = I.value; if constexpr (s < 4) wgmma128r<8>(lo1, fa[s], bdesc(48 + s)); else wgmma128<1, 8>(lo1, gdesc(s), bdesc(48 + s)); };
    auto mma3 = [&](auto I) { constexpr int s = I.value; if constexpr (s < 8) wgmma96r<8>(hi1, fa[s], bdesc(48 + s) + 128); else wgmma96<1, 8>(hi1, gdesc(s), bdesc(48 + s) + 128); };
    bar_sync(4 + wg);
    wgmma_fence();
    static_for<0, 8>(mma2);
    wgmma_commit();
    const bool okg2 = mbar_try(gbar + 8, 0);
    send(slc(3), &tmo64, colL + 64, row0);
    mbar_wait1(gbar + 8, 0, okg2);
    wgmma_fence();
    static_for<8, 16>(mma2);
    wgmma_commit();
    bar_arrive(5 + wg);
    get_frag(1, slc(4));
    if (elect()) bulk_wait_read<1>();
    __syncwarp();
    wgmma_wait<0>();
    stage_cols<64, 0>(lo1, slc(1)); send(slc(1), &tmo64, colL, row0 + 64);
    stage_cols<64, 32>(lo1, slc(2));
    bar_sync(6 + wg);
    wgmma_fence();
    static_for<0, 6>(mma3);
    wgmma_commit();
    send(slc(2), &tmo64, colL + 64, row0 + 64);
    wgmma_fence();
    static_for<6, 16>(mma3);
    wgmma_commit();
    if (wg == 0) bar_arrive(7);
    wgmma_wait<0>();
    stage_cols<64, 0>(hi1, slc(4)); send(slc(4), &tmo64, colA, row0 + 64);
    stage_cols<32, 32>(hi1, slc(5)); send(slc(5), &tmo32, colB, row0 + 64);
    if (elect()) bulk_wait_read<0>();
    __syncwarp();
}

typedef CUresult (*EncodeFn)(CUtensorMap*, CUtensorMapDataType, cuuint32_t, void*, const cuuint64_t*, const cuuint64_t*,
                             const cuuint32_t*, const cuuint32_t*, CUtensorMapInterleave, CUtensorMapSwizzle,
                             CUtensorMapL2promotion, CUtensorMapFloatOOBfill);

extern "C" void kernel_launch(void* const* d_in, const int* in_sizes, int n_in, void* d_out, int out_size) {
    const __nv_bfloat16* x = (const __nv_bfloat16*)d_in[0];
    const int* qw = (const int*)d_in[1];
    const __nv_bfloat16* cb = (const __nv_bfloat16*)d_in[2];
    const __nv_bfloat16* absmax = (const __nv_bfloat16*)d_in[3];
    static EncodeFn encode = nullptr;
    static void *wimg = nullptr, *gflag = nullptr;
    if (!encode) {
        cudaGetSymbolAddress(&wimg, g_wimg);
        cudaGetSymbolAddress(&gflag, g_flag);
        void* fn = nullptr;
        cudaDriverEntryPointQueryResult qr;
        cudaGetDriverEntryPoint("cuTensorMapEncodeTiled", &fn, cudaEnableDefault, &qr);
        encode = (EncodeFn)fn;
        cudaFuncSetAttribute(nf4_gemm_kernel, cudaFuncAttributeMaxDynamicSharedMemorySize, SMEM_BYTES);
    }
    CUtensorMap tmx, tmq, tmo64, tmo32, tmqp, tmx16, tmx64, tmq1;
    {
        cuuint64_t dims[2] = {(cuuint64_t)K_, (cuuint64_t)M_};
        cuuint64_t strides[1] = {(cuuint64_t)K_ * 2};
        cuuint32_t box[2] = {64, 128};
        cuuint32_t es[2] = {1, 1};
        encode(&tmx, CU_TENSOR_MAP_DATA_TYPE_BFLOAT16, 2, (void*)x, dims, strides, box, es, CU_TENSOR_MAP_INTERLEAVE_NONE,
               CU_TENSOR_MAP_SWIZZLE_128B, CU_TENSOR_MAP_L2_PROMOTION_L2_128B, CU_TENSOR_MAP_FLOAT_OOB_FILL_NONE);
        box[1] = 64;
        encode(&tmx64, CU_TENSOR_MAP_DATA_TYPE_BFLOAT16, 2, (void*)x, dims, strides, box, es, CU_TENSOR_MAP_INTERLEAVE_NONE,
               CU_TENSOR_MAP_SWIZZLE_128B, CU_TENSOR_MAP_L2_PROMOTION_L2_128B, CU_TENSOR_MAP_FLOAT_OOB_FILL_NONE);
        box[1] = 16;
        encode(&tmx16, CU_TENSOR_MAP_DATA_TYPE_BFLOAT16, 2, (void*)x, dims, strides, box, es, CU_TENSOR_MAP_INTERLEAVE_NONE,
               CU_TENSOR_MAP_SWIZZLE_128B, CU_TENSOR_MAP_L2_PROMOTION_L2_128B, CU_TENSOR_MAP_FLOAT_OOB_FILL_NONE);
    }
    {
        cuuint64_t dims[5] = {32, 8, (cuuint64_t)(N_ / 32), 2, (cuuint64_t)(K_ / 16)};
        cuuint64_t strides[4] = {(cuuint64_t)N_ * 4, 128, (cuuint64_t)N_ * 4 * 8, (cuuint64_t)N_ * 4 * 16};
        cuuint32_t box[5] = {32, 8, 7, 1, 2};
        cuuint32_t es[5] = {1, 1, 1, 1, 1};
        encode(&tmq, CU_TENSOR_MAP_DATA_TYPE_INT32, 5, (void*)qw, dims, strides, box, es, CU_TENSOR_MAP_INTERLEAVE_NONE,
               CU_TENSOR_MAP_SWIZZLE_128B, CU_TENSOR_MAP_L2_PROMOTION_L2_128B, CU_TENSOR_MAP_FLOAT_OOB_FILL_NONE);
        box[4] = 1;
        encode(&tmq1, CU_TENSOR_MAP_DATA_TYPE_INT32, 5, (void*)qw, dims, strides, box, es, CU_TENSOR_MAP_INTERLEAVE_NONE,
               CU_TENSOR_MAP_SWIZZLE_128B, CU_TENSOR_MAP_L2_PROMOTION_L2_128B, CU_TENSOR_MAP_FLOAT_OOB_FILL_NONE);
        cuuint64_t dims2[2] = {(cuuint64_t)N_, (cuuint64_t)K_};
        cuuint32_t box2[2] = {224, 8};
        encode(&tmqp, CU_TENSOR_MAP_DATA_TYPE_INT32, 2, (void*)qw, dims2, strides, box2, es, CU_TENSOR_MAP_INTERLEAVE_NONE,
               CU_TENSOR_MAP_SWIZZLE_NONE, CU_TENSOR_MAP_L2_PROMOTION_L2_128B, CU_TENSOR_MAP_FLOAT_OOB_FILL_NONE);
    }
    {
        cuuint64_t dims[2] = {(cuuint64_t)N_, (cuuint64_t)M_};
        cuuint64_t strides[1] = {(cuuint64_t)N_ * 2};
        cuuint32_t box[2] = {64, 16};
        cuuint32_t es[2] = {1, 1};
        encode(&tmo64, CU_TENSOR_MAP_DATA_TYPE_BFLOAT16, 2, d_out, dims, strides, box, es, CU_TENSOR_MAP_INTERLEAVE_NONE,
               CU_TENSOR_MAP_SWIZZLE_128B, CU_TENSOR_MAP_L2_PROMOTION_NONE, CU_TENSOR_MAP_FLOAT_OOB_FILL_NONE);
        box[0] = 32;
        encode(&tmo32, CU_TENSOR_MAP_DATA_TYPE_BFLOAT16, 2, d_out, dims, strides, box, es, CU_TENSOR_MAP_INTERLEAVE_NONE,
               CU_TENSOR_MAP_SWIZZLE_64B, CU_TENSOR_MAP_L2_PROMOTION_NONE, CU_TENSOR_MAP_FLOAT_OOB_FILL_NONE);
    }
    nf4_gemm_kernel<<<dim3(2, 16, 4), 256, SMEM_BYTES>>>(qw, cb, absmax, (uint8_t*)wimg, (unsigned*)gflag, tmx, tmq, tmo64, tmo32, tmqp, tmx16, tmx64, tmq1);
}
```

```cpp
#include <cuda_runtime.h>
#include <cuda_bf16.h>
#include <cuda.h>
#include <stdint.h>

constexpr int M_ = 2048, K_ = 1024, N_ = 3584;
constexpr int BM = 256, BN = 224;
constexpr int UNIT = 14336;
constexpr int NW = 6, NR = 3;
constexpr int NU = 20;
constexpr int G1 = 5, G2 = 8;
constexpr int PFQ = 4, PFX = 3;
constexpr unsigned T2 = 900, T2B = 1300, T3 = 1700;
constexpr int RAW_OFF = 3 * 32768;
constexpr int SC_OFF = RAW_OFF + 2 * UNIT;
constexpr int SC_STRIDE = 464;
constexpr int W_OFF = 127 * 1024;
constexpr int RAW2_OFF = W_OFF + NW * UNIT;
constexpr int BAR_OFF = RAW2_OFF + UNIT;
constexpr int SMEM_BYTES = BAR_OFF + 320;
__device__ __align__(1024) uint8_t g_wimg[16 * 16 * UNIT];
__device__ __align__(128) unsigned g_flag[16 * 32];

__device__ __forceinline__ uint32_t smem_u32(const void* p) { return (uint32_t)__cvta_generic_to_shared(p); }
__device__ __forceinline__ bool elect() {
    uint32_t ok;
    asm volatile("{\n.reg .pred p;\nelect.sync _|p, 0xffffffff;\nselp.u32 %0, 1, 0, p;\n}\n" : "=r"(ok));
    return ok != 0;
}
__device__ __forceinline__ void mbar_init(uint32_t bar, uint32_t cnt) { asm volatile("mbarrier.init.shared::cta.b64 [%0], %1;" ::"r"(bar), "r"(cnt) : "memory"); }
__device__ __forceinline__ void mbar_expect_tx(uint32_t bar, uint32_t bytes) { asm volatile("mbarrier.arrive.expect_tx.shared::cta.b64 _, [%0], %1;" ::"r"(bar), "r"(bytes) : "memory"); }
__device__ __forceinline__ void mbar_arrive(uint32_t bar) { asm volatile("mbarrier.arrive.shared::cta.b64 _, [%0];" ::"r"(bar) : "memory"); }
#define BOUNDED
#define WAIT_INIT "mov.u32 n, 0;\n"
#define WAIT_NEXT "@p bra.uni LAB_DONE;\nadd.u32 n, n, 1;\nsetp.lt.u32 p, n, 0x4000;\n@p bra.uni LAB_WAIT;\n"
__device__ __forceinline__ void mbar_wait(uint32_t bar, uint32_t parity) {
    asm volatile(
        "{\n.reg .pred p;\n.reg .u32 n;\n"
        WAIT_INIT
        "LAB_WAIT:\n"
        "mbarrier.try_wait.parity.shared::cta.b64 p, [%0], %1;\n"
        WAIT_NEXT
        "LAB_DONE:\n}\n" ::"r"(bar), "r"(parity) : "memory");
}
__device__ __forceinline__ bool mbar_try(uint32_t bar, uint32_t parity) {
    uint32_t ok;
    asm volatile("{\n.reg .pred p;\nmbarrier.test_wait.parity.shared::cta.b64 p, [%1], %2;\nselp.u32 %0, 1, 0, p;\n}\n" : "=r"(ok) : "r"(bar), "r"(parity) : "memory");
    return ok != 0;
}
__device__ __forceinline__ void mbar_wait1(uint32_t b0, uint32_t p0, bool skip) {
    asm volatile(
        "{\n.reg .pred p;\n.reg .u32 n;\n"
        "setp.ne.u32 p, %2, 0;\n@p bra.uni LAB_DONE;\n"
        WAIT_INIT
        "LAB_WAIT:\n"
        "mbarrier.try_wait.parity.shared::cta.b64 p, [%0], %1;\n"
        WAIT_NEXT
        "LAB_DONE:\n}\n" ::"r"(b0), "r"(p0), "r"((uint32_t)skip) : "memory");
}
__device__ __forceinline__ void mbar_wait2(uint32_t b0, uint32_t p0, uint32_t b1, uint32_t p1, bool skip = false) {
    asm volatile(
        "{\n.reg .pred p, q;\n.reg .u32 n;\n"
        "setp.ne.u32 p, %4, 0;\n@p bra.uni LAB_DONE;\n"
        WAIT_INIT
        "LAB_WAIT:\n"
        "mbarrier.try_wait.parity.shared::cta.b64 p, [%0], %1;\n"
        "mbarrier.try_wait.parity.shared::cta.b64 q, [%2], %3;\n"
        "and.pred p, p, q;\n"
        WAIT_NEXT
        "LAB_DONE:\n}\n" ::"r"(b0), "r"(p0), "r"(b1), "r"(p1), "r"((uint32_t)skip) : "memory");
}
__device__ __forceinline__ void tma_load_2d(uint32_t dst, const CUtensorMap* tm, int c0, int c1, uint32_t bar) {
    asm volatile("cp.async.bulk.tensor.2d.shared::cluster.global.mbarrier::complete_tx::bytes [%0], [%1, {%2, %3}], [%4];"
                 ::"r"(dst), "l"(tm), "r"(c0), "r"(c1), "r"(bar) : "memory");
}
__device__ __forceinline__ void tma_load_5d(uint32_t dst, const CUtensorMap* tm, int c0, int c1, int c2, int c3, int c4, uint32_t bar) {
    asm volatile("cp.async.bulk.tensor.5d.shared::cluster.global.mbarrier::complete_tx::bytes [%0], [%1, {%2, %3, %4, %5, %6}], [%7];"
                 ::"r"(dst), "l"(tm), "r"(c0), "r"(c1), "r"(c2), "r"(c3), "r"(c4), "r"(bar) : "memory");
}
__device__ __forceinline__ void tma_prefetch_2d(const CUtensorMap* tm, int c0, int c1) {
    asm volatile("cp.async.bulk.prefetch.tensor.2d.L2.global [%0, {%1, %2}];" ::"l"(tm), "r"(c0), "r"(c1) : "memory");
}
__device__ __forceinline__ void bulk_load(uint32_t dst, const void* src, uint32_t bytes, uint32_t bar) {
    asm volatile("cp.async.bulk.shared::cluster.global.mbarrier::complete_tx::bytes [%0], [%1], %2, [%3];"
                 ::"r"(dst), "l"(src), "r"(bytes), "r"(bar) : "memory");
}
__device__ __forceinline__ void cluster_arrive() { asm volatile("barrier.cluster.arrive.relaxed.aligned;" ::: "memory"); }
__device__ __forceinline__ void cluster_wait() { asm volatile("barrier.cluster.wait.acquire.aligned;" ::: "memory"); }
__device__ __forceinline__ uint32_t mapa(uint32_t addr, uint32_t cta) {
    uint32_t r; asm("mapa.shared::cluster.u32 %0, %1, %2;" : "=r"(r) : "r"(addr), "r"(cta)); return r;
}
__device__ __forceinline__ void copy_to_peer(uint32_t cdst, uint32_t src, uint32_t bytes, uint32_t cbar) {
    asm volatile("cp.async.bulk.shared::cluster.shared::cta.mbarrier::complete_tx::bytes [%0], [%1], %2, [%3];"
                 ::"r"(cdst), "r"(src), "r"(bytes), "r"(cbar) : "memory");
}
__device__ __forceinline__ void wgmma_fence() { asm volatile("wgmma.fence.sync.aligned;" ::: "memory"); }
__device__ __forceinline__ void wgmma_commit() { asm volatile("wgmma.commit_group.sync.aligned;" ::: "memory"); }
template <int N> __device__ __forceinline__ void wgmma_wait() { asm volatile("wgmma.wait_group.sync.aligned %0;" ::"n"(N) : "memory"); }
__device__ __forceinline__ uint32_t pack_bf16(float lo, float hi) {
    uint32_t r; asm("cvt.rn.bf16x2.f32 %0, %1, %2;" : "=r"(r) : "f"(hi), "f"(lo)); return r;
}
__device__ __forceinline__ void stmatrix_x4(uint32_t addr, uint32_t a, uint32_t b, uint32_t c, uint32_t d) {
    asm volatile("stmatrix.sync.aligned.m8n8.x4.shared.b16 [%0], {%1, %2, %3, %4};" ::"r"(addr), "r"(a), "r"(b), "r"(c), "r"(d) : "memory");
}
__device__ __forceinline__ uint4 ldmatrix_x4(uint32_t a) {
    uint4 v; asm volatile("ldmatrix.sync.aligned.m8n8.x4.shared.b16 {%0, %1, %2, %3}, [%4];" : "=r"(v.x), "=r"(v.y), "=r"(v.z), "=r"(v.w) : "r"(a) : "memory"); return v;
}
__device__ __forceinline__ uint4 lds128(uint32_t a) {
    uint4 v; asm volatile("ld.shared.v4.b32 {%0, %1, %2, %3}, [%4];" : "=r"(v.x), "=r"(v.y), "=r"(v.z), "=r"(v.w) : "r"(a) : "memory"); return v;
}
__device__ __forceinline__ void sts128(uint32_t a, uint4 v) {
    asm volatile("st.shared.v4.b32 [%0], {%1, %2, %3, %4};" ::"r"(a), "r"(v.x), "r"(v.y), "r"(v.z), "r"(v.w) : "memory");
}
__device__ __forceinline__ uint4 ldg128(const void* p) {
    uint4 v; asm volatile("ld.global.nc.v4.b32 {%0, %1, %2, %3}, [%4];" : "=r"(v.x), "=r"(v.y), "=r"(v.z), "=r"(v.w) : "l"(p) : "memory"); return v;
}
__device__ __forceinline__ unsigned clk() { unsigned c; asm volatile("mov.u32 %0, %%clock;" : "=r"(c) :: "memory"); return c; }
__device__ __forceinline__ uint32_t mul_bf16x2(uint32_t a, uint32_t b) { uint32_t r; asm("mul.rn.bf16x2 %0, %1, %2;" : "=r"(r) : "r"(a), "r"(b)); return r; }
struct Lut { uint32_t lo[4], hi[4]; };
__device__ __forceinline__ uint32_t prmt(uint32_t a, uint32_t b, uint32_t s) { uint32_t r; asm("prmt.b32 %0, %1, %2, %3;" : "=r"(r) : "r"(a), "r"(b), "r"(s)); return r; }
__device__ __forceinline__ uint32_t pack4(const uint4& q) {
    uint32_t ab, cd, p;
    asm volatile("mad.lo.u32 %0, %1, 16, %2;" : "=r"(ab) : "r"(q.y), "r"(q.x));
    asm volatile("mad.lo.u32 %0, %1, 16, %2;" : "=r"(cd) : "r"(q.w), "r"(q.z));
    asm volatile("mad.lo.u32 %0, %1, 256, %2;" : "=r"(p) : "r"(cd), "r"(ab));
    return p;
}
__device__ __forceinline__ void lookup4(uint32_t p, const Lut& t, uint32_t& w01, uint32_t& w23) {
    const uint32_t t8 = p & 0x8888u, s7 = p & 0x7777u;
    const uint32_t sel = (t8 >> 1) + 0x3210u;
    const uint32_t lo = prmt(prmt(t.lo[0], t.lo[1], p), prmt(t.lo[2], t.lo[3], s7), sel);
    const uint32_t hi = prmt(prmt(t.hi[0], t.hi[1], p), prmt(t.hi[2], t.hi[3], s7), sel);
    w01 = prmt(lo, hi, 0x5140);
    w23 = prmt(lo, hi, 0x7362);
}
__device__ __forceinline__ uint4 dequant8(uint32_t p0, uint32_t p1, const uint4& sc, const Lut& t) {
    uint4 r;
    lookup4(p0, t, r.x, r.y);
    lookup4(p1, t, r.z, r.w);
    r.x = mul_bf16x2(r.x, sc.x); r.y = mul_bf16x2(r.y, sc.y); r.z = mul_bf16x2(r.z, sc.z); r.w = mul_bf16x2(r.w, sc.w);
    return r;
}
__device__ __forceinline__ void fence_async_smem() { asm volatile("fence.proxy.async.shared::cta;" ::: "memory"); }

template <int SCALE_D, int BHI, uint32_t AHI = 0x40000040u>
__device__ __forceinline__ void wgmma224(float (&d)[112], uint32_t descA, uint32_t descB) {
    asm volatile(
        "{\n.reg .pred p;\n.reg .b64 da, db;\nsetp.ne.b32 p, %114, 0;\n"
        "mov.b64 da, {%112, %116};\nmov.b64 db, {%113, %115};\n"
        "wgmma.mma_async.sync.aligned.m64n224k16.f32.bf16.bf16 "
        "{%0, %1, %2, %3, %4, %5, %6, %7, %8, %9, %10, %11, %12, %13, %14, %15, "
        "%16, %17, %18, %19, %20, %21, %22, %23, %24, %25, %26, %27, %28, %29, %30, %31, "
        "%32, %33, %34, %35, %36, %37, %38, %39, %40, %41, %42, %43, %44, %45, %46, %47, "
        "%48, %49, %50, %51, %52, %53, %54, %55, %56, %57, %58, %59, %60, %61, %62, %63, "
        "%64, %65, %66, %67, %68, %69, %70, %71, %72, %73, %74, %75, %76, %77, %78, %79, "
        "%80, %81, %82, %83, %84, %85, %86, %87, %88, %89, %90, %91, %92, %93, %94, %95, "
        "%96, %97, %98, %99, %100, %101, %102, %103, %104, %105, %106, %107, %108, %109, %110, %111}, "
        "da, db, p, 1, 1, 0, 1;\n}\n"
        : "+f"(d[0]), "+f"(d[1]), "+f"(d[2]), "+f"(d[3]), "+f"(d[4]), "+f"(d[5]), "+f"(d[6]), "+f"(d[7]),
          "+f"(d[8]), "+f"(d[9]), "+f"(d[10]), "+f"(d[11]), "+f"(d[12]), "+f"(d[13]), "+f"(d[14]), "+f"(d[15]),
          "+f"(d[16]), "+f"(d[17]), "+f"(d[18]), "+f"(d[19]), "+f"(d[20]), "+f"(d[21]), "+f"(d[22]), "+f"(d[23]),
          "+f"(d[24]), "+f"(d[25]), "+f"(d[26]), "+f"(d[27]), "+f"(d[28]), "+f"(d[29]), "+f"(d[30]), "+f"(d[31]),
          "+f"(d[32]), "+f"(d[33]), "+f"(d[34]), "+f"(d[35]), "+f"(d[36]), "+f"(d[37]), "+f"(d[38]), "+f"(d[39]),
          "+f"(d[40]), "+f"(d[41]), "+f"(d[42]), "+f"(d[43]), "+f"(d[44]), "+f"(d[45]), "+f"(d[46]), "+f"(d[47]),
          "+f"(d[48]), "+f"(d[49]), "+f"(d[50]), "+f"(d[51]), "+f"(d[52]), "+f"(d[53]), "+f"(d[54]), "+f"(d[55]),
          "+f"(d[56]), "+f"(d[57]), "+f"(d[58]), "+f"(d[59]), "+f"(d[60]), "+f"(d[61]), "+f"(d[62]), "+f"(d[63]),
          "+f"(d[64]), "+f"(d[65]), "+f"(d[66]), "+f"(d[67]), "+f"(d[68]), "+f"(d[69]), "+f"(d[70]), "+f"(d[71]),
          "+f"(d[72]), "+f"(d[73]), "+f"(d[74]), "+f"(d[75]), "+f"(d[76]), "+f"(d[77]), "+f"(d[78]), "+f"(d[79]),
          "+f"(d[80]), "+f"(d[81]), "+f"(d[82]), "+f"(d[83]), "+f"(d[84]), "+f"(d[85]), "+f"(d[86]), "+f"(d[87]),
          "+f"(d[88]), "+f"(d[89]), "+f"(d[90]), "+f"(d[91]), "+f"(d[92]), "+f"(d[93]), "+f"(d[94]), "+f"(d[95]),
          "+f"(d[96]), "+f"(d[97]), "+f"(d[98]), "+f"(d[99]), "+f"(d[100]), "+f"(d[101]), "+f"(d[102]), "+f"(d[103]),
          "+f"(d[104]), "+f"(d[105]), "+f"(d[106]), "+f"(d[107]), "+f"(d[108]), "+f"(d[109]), "+f"(d[110]), "+f"(d[111])
        : "r"(descA), "r"(descB), "n"(SCALE_D), "n"(BHI), "n"(AHI));
}

template <int SCALE_D, int BHI, uint32_t AHI = 0x40000040u>
__device__ __forceinline__ void wgmma128(float (&d)[64], uint32_t descA, uint32_t descB) {
    asm volatile(
        "{\n.reg .pred p;\n.reg .b64 da, db;\nsetp.ne.b32 p, %66, 0;\n"
        "mov.b64 da, {%64, %68};\nmov.b64 db, {%65, %67};\n"
        "wgmma.mma_async.sync.aligned.m64n128k16.f32.bf16.bf16 "
        "{%0, %1, %2, %3, %4, %5, %6, %7, %8, %9, %10, %11, %12, %13, %14, %15, "
        "%16, %17, %18, %19, %20, %21, %22, %23, %24, %25, %26, %27, %28, %29, %30, %31, "
        "%32, %33, %34, %35, %36, %37, %38, %39, %40, %41, %42, %43, %44, %45, %46, %47, "
        "%48, %49, %50, %51, %52, %53, %54, %55, %56, %57, %58, %59, %60, %61, %62, %63}, "
        "da, db, p, 1, 1, 0, 1;\n}\n"
        : "+f"(d[0]), "+f"(d[1]), "+f"(d[2]), "+f"(d[3]), "+f"(d[4]), "+f"(d[5]), "+f"(d[6]), "+f"(d[7]),
          "+f"(d[8]), "+f"(d[9]), "+f"(d[10]), "+f"(d[11]), "+f"(d[12]), "+f"(d[13]), "+f"(d[14]), "+f"(d[15]),
          "+f"(d[16]), "+f"(d[17]), "+f"(d[18]), "+f"(d[19]), "+f"(d[20]), "+f"(d[21]), "+f"(d[22]), "+f"(d[23]),
          "+f"(d[24]), "+f"(d[25]), "+f"(d[26]), "+f"(d[27]), "+f"(d[28]), "+f"(d[29]), "+f"(d[30]), "+f"(d[31]),
          "+f"(d[32]), "+f"(d[33]), "+f"(d[34]), "+f"(d[35]), "+f"(d[36]), "+f"(d[37]), "+f"(d[38]), "+f"(d[39]),
          "+f"(d[40]), "+f"(d[41]), "+f"(d[42]), "+f"(d[43]), "+f"(d[44]), "+f"(d[45]), "+f"(d[46]), "+f"(d[47]),
          "+f"(d[48]), "+f"(d[49]), "+f"(d[50]), "+f"(d[51]), "+f"(d[52]), "+f"(d[53]), "+f"(d[54]), "+f"(d[55]),
          "+f"(d[56]), "+f"(d[57]), "+f"(d[58]), "+f"(d[59]), "+f"(d[60]), "+f"(d[61]), "+f"(d[62]), "+f"(d[63])
        : "r"(descA), "r"(descB), "n"(SCALE_D), "n"(BHI), "n"(AHI));
}

template <int SCALE_D, int BHI, uint32_t AHI = 0x40000040u>
__device__ __forceinline__ void wgmma96(float (&d)[48], uint32_t descA, uint32_t descB) {
    asm volatile(
        "{\n.reg .pred p;\n.reg .b64 da, db;\nsetp.ne.b32 p, %50, 0;\n"
        "mov.b64 da, {%48, %52};\nmov.b64 db, {%49, %51};\n"
        "wgmma.mma_async.sync.aligned.m64n96k16.f32.bf16.bf16 "
        "{%0, %1, %2, %3, %4, %5, %6, %7, %8, %9, %10, %11, %12, %13, %14, %15, "
        "%16, %17, %18, %19, %20, %21, %22, %23, %24, %25, %26, %27, %28, %29, %30, %31, "
        "%32, %33, %34, %35, %36, %37, %38, %39, %40, %41, %42, %43, %44, %45, %46, %47}, "
        "da, db, p, 1, 1, 0, 1;\n}\n"
        : "+f"(d[0]), "+f"(d[1]), "+f"(d[2]), "+f"(d[3]), "+f"(d[4]), "+f"(d[5]), "+f"(d[6]), "+f"(d[7]),
          "+f"(d[8]), "+f"(d[9]), "+f"(d[10]), "+f"(d[11]), "+f"(d[12]), "+f"(d[13]), "+f"(d[14]), "+f"(d[15]),
          "+f"(d[16]), "+f"(d[17]), "+f"(d[18]), "+f"(d[19]), "+f"(d[20]), "+f"(d[21]), "+f"(d[22]), "+f"(d[23]),
          "+f"(d[24]), "+f"(d[25]), "+f"(d[26]), "+f"(d[27]), "+f"(d[28]), "+f"(d[29]), "+f"(d[30]), "+f"(d[31]),
          "+f"(d[32]), "+f"(d[33]), "+f"(d[34]), "+f"(d[35]), "+f"(d[36]), "+f"(d[37]), "+f"(d[38]), "+f"(d[39]),
          "+f"(d[40]), "+f"(d[41]), "+f"(d[42]), "+f"(d[43]), "+f"(d[44]), "+f"(d[45]), "+f"(d[46]), "+f"(d[47])
        : "r"(descA), "r"(descB), "n"(SCALE_D), "n"(BHI), "n"(AHI));
}

template <int BHI>
__device__ __forceinline__ void wgmma128r(float (&d)[64], const uint4& a, uint32_t descB) {
    asm volatile(
        "{\n.reg .pred p;\n.reg .b64 db;\nsetp.eq.b32 p, 0, 0;\n"
        "mov.b64 db, {%68, %69};\n"
        "wgmma.mma_async.sync.aligned.m64n128k16.f32.bf16.bf16 "
        "{%0, %1, %2, %3, %4, %5, %6, %7, %8, %9, %10, %11, %12, %13, %14, %15, "
        "%16, %17, %18, %19, %20, %21, %22, %23, %24, %25, %26, %27, %28, %29, %30, %31, "
        "%32, %33, %34, %35, %36, %37, %38, %39, %40, %41, %42, %43, %44, %45, %46, %47, "
        "%48, %49, %50, %51, %52, %53, %54, %55, %56, %57, %58, %59, %60, %61, %62, %63}, "
        "{%64, %65, %66, %67}, db, p, 1, 1, 1;\n}\n"
        : "+f"(d[0]), "+f"(d[1]), "+f"(d[2]), "+f"(d[3]), "+f"(d[4]), "+f"(d[5]), "+f"(d[6]), "+f"(d[7]),
          "+f"(d[8]), "+f"(d[9]), "+f"(d[10]), "+f"(d[11]), "+f"(d[12]), "+f"(d[13]), "+f"(d[14]), "+f"(d[15]),
          "+f"(d[16]), "+f"(d[17]), "+f"(d[18]), "+f"(d[19]), "+f"(d[20]), "+f"(d[21]), "+f"(d[22]), "+f"(d[23]),
          "+f"(d[24]), "+f"(d[25]), "+f"(d[26]), "+f"(d[27]), "+f"(d[28]), "+f"(d[29]), "+f"(d[30]), "+f"(d[31]),
          "+f"(d[32]), "+f"(d[33]), "+f"(d[34]), "+f"(d[35]), "+f"(d[36]), "+f"(d[37]), "+f"(d[38]), "+f"(d[39]),
          "+f"(d[40]), "+f"(d[41]), "+f"(d[42]), "+f"(d[43]), "+f"(d[44]), "+f"(d[45]), "+f"(d[46]), "+f"(d[47]),
          "+f"(d[48]), "+f"(d[49]), "+f"(d[50]), "+f"(d[51]), "+f"(d[52]), "+f"(d[53]), "+f"(d[54]), "+f"(d[55]),
          "+f"(d[56]), "+f"(d[57]), "+f"(d[58]), "+f"(d[59]), "+f"(d[60]), "+f"(d[61]), "+f"(d[62]), "+f"(d[63])
        : "r"(a.x), "r"(a.y), "r"(a.z), "r"(a.w), "r"(descB), "n"(BHI));
}

template <int BHI>
__device__ __forceinline__ void wgmma96r(float (&d)[48], const uint4& a, uint32_t descB) {
    asm volatile(
        "{\n.reg .pred p;\n.reg .b64 db;\nsetp.eq.b32 p, 0, 0;\n"
        "mov.b64 db, {%52, %53};\n"
        "wgmma.mma_async.sync.aligned.m64n96k16.f32.bf16.bf16 "
        "{%0, %1, %2, %3, %4, %5, %6, %7, %8, %9, %10, %11, %12, %13, %14, %15, "
        "%16, %17, %18, %19, %20, %21, %22, %23, %24, %25, %26, %27, %28, %29, %30, %31, "
        "%32, %33, %34, %35, %36, %37, %38, %39, %40, %41, %42, %43, %44, %45, %46, %47}, "
        "{%48, %49, %50, %51}, db, p, 1, 1, 1;\n}\n"
        : "+f"(d[0]), "+f"(d[1]), "+f"(d[2]), "+f"(d[3]), "+f"(d[4]), "+f"(d[5]), "+f"(d[6]), "+f"(d[7]),
          "+f"(d[8]), "+f"(d[9]), "+f"(d[10]), "+f"(d[11]), "+f"(d[12]), "+f"(d[13]), "+f"(d[14]), "+f"(d[15]),
          "+f"(d[16]), "+f"(d[17]), "+f"(d[18]), "+f"(d[19]), "+f"(d[20]), "+f"(d[21]), "+f"(d[22]), "+f"(d[23]),
          "+f"(d[24]), "+f"(d[25]), "+f"(d[26]), "+f"(d[27]), "+f"(d[28]), "+f"(d[29]), "+f"(d[30]), "+f"(d[31]),
          "+f"(d[32]), "+f"(d[33]), "+f"(d[34]), "+f"(d[35]), "+f"(d[36]), "+f"(d[37]), "+f"(d[38]), "+f"(d[39]),
          "+f"(d[40]), "+f"(d[41]), "+f"(d[42]), "+f"(d[43]), "+f"(d[44]), "+f"(d[45]), "+f"(d[46]), "+f"(d[47])
        : "r"(a.x), "r"(a.y), "r"(a.z), "r"(a.w), "r"(descB), "n"(BHI));
}

__device__ __forceinline__ uint32_t opq(uint32_t v) { asm volatile("" : "+r"(v)); return v; }
template <int I> struct IC { static constexpr int value = I; };
template <int B, int E, class F> __device__ __forceinline__ void static_for(F&& f) {
    if constexpr (B < E) { f(IC<B>{}); static_for<B + 1, E>(f); }
}

__device__ __forceinline__ void tma_store_2d(const CUtensorMap* tm, uint32_t src, int c0, int c1) {
    asm volatile("cp.async.bulk.tensor.2d.global.shared::cta.bulk_group [%0, {%2, %3}], [%1];" ::"l"(tm), "r"(src), "r"(c0), "r"(c1) : "memory");
}
__device__ __forceinline__ void bulk_store(void* dst, uint32_t src, uint32_t bytes) {
    asm volatile("cp.async.bulk.global.shared::cta.bulk_group [%0], [%1], %2;" ::"l"(dst), "r"(src), "r"(bytes) : "memory");
}
__device__ __forceinline__ void bulk_commit() { asm volatile("cp.async.bulk.commit_group;" ::: "memory"); }
template <int N> __device__ __forceinline__ void bulk_wait_read() { asm volatile("cp.async.bulk.wait_group.read %0;" ::"n"(N) : "memory"); }
__device__ __forceinline__ void bar_arrive(int id) { asm volatile("bar.arrive %0, 256;" ::"r"(id) : "memory"); }
__device__ __forceinline__ void bar_sync(int id) { asm volatile("bar.sync %0, 256;" ::"r"(id) : "memory"); }
template <int NC, int OFF, int N>
__device__ __forceinline__ void stage_cols(const float (&acc)[N], uint32_t stg) {
    int lane; asm volatile("mov.u32 %0, %%laneid;" : "=r"(lane));
    const int r = lane & 15;
    const uint32_t a0 = NC == 64 ? stg + r * 128 + (((lane >> 4) ^ (r & 7)) << 4) : stg + r * 64 + (((lane >> 4) ^ ((r >> 1) & 3)) << 4);
#pragma unroll
    for (int j = 0; j < NC / 16; j++) {
        const int i = OFF + 8 * j;
        stmatrix_x4(a0 ^ (j * 32), pack_bf16(acc[i], acc[i + 1]), pack_bf16(acc[i + 2], acc[i + 3]), pack_bf16(acc[i + 4], acc[i + 5]), pack_bf16(acc[i + 6], acc[i + 7]));
    }
}
__device__ __forceinline__ void send(uint32_t stg, const CUtensorMap* tmo, int col, int row) {
    fence_async_smem();
    __syncwarp();
    if (elect()) { tma_store_2d(tmo, stg, col, row); bulk_commit(); }
    __syncwarp();
}

__host__ __device__ constexpr int rslot(int u) { return (2 * u) % 3; }
__host__ __device__ constexpr int roff(int slot) { return slot < 2 ? slot * UNIT : RAW2_OFF - RAW_OFF; }
__host__ __device__ constexpr int rpar(int u) { return (u / 3 - (u % 3 == 0)) & 1; }
__host__ __device__ constexpr int sslot(int c) { return c < 3 ? c + 3 : c % 3; }
__host__ __device__ constexpr int vturn(int v) {
    return v < 20 ? v : v == 20 ? -21 : v == 21 ? -22 : v == 22 ? 21 : v == 23 ? -20 : v == 24 ? 20 : v < 29 ? v - 3 : v == 29 ? -24 : v == 30 ? -25 : 27;
}
__host__ __device__ constexpr int uoff(int v) { return vturn(v) < 0 ? RAW_OFF + roff(rslot(-vturn(v))) : W_OFF + (vturn(v) % NW) * UNIT; }
__host__ __device__ constexpr int ubar(int v) { return vturn(v) < 0 ? 96 + 8 * rslot(-vturn(v)) : 16 * (vturn(v) % NW); }
__host__ __device__ constexpr int upar(int v) { return vturn(v) < 0 ? rpar(-vturn(v)) : (vturn(v) / NW) & 1; }
__host__ __device__ constexpr int utime(int v) {
    return v < 22 ? v + 15 : v == 22 || v == 25 ? 38 : v < 25 ? 40 : v < 28 ? 42 : 44;
}
__host__ __device__ constexpr int sh_at(int g, int k) { return (g ? 4 * G2 : 4 * G1) - 3 + (((g ? 0x01458 : 0x01479) >> (16 - 4 * k)) & 15); }
__host__ __device__ constexpr bool shares_at(int s) { for (int k = 0; k < 5; k++) if (sh_at(0, k) == s || sh_at(1, k) == s) return true; return false; }
__host__ __device__ constexpr uint32_t bdesc(int s) { return (uint32_t)(((0x400 + uoff(s >> 1)) >> 4) | ((7168u >> 4) << 16)) + (s & 1) * 224; }

__global__ void __cluster_dims__(2, 1, 1) __launch_bounds__(256, 1)
nf4_gemm_kernel(const int* __restrict__ qw, const __nv_bfloat16* __restrict__ cb, const __nv_bfloat16* __restrict__ absmax,
                uint8_t* __restrict__ wimg, unsigned* __restrict__ gflag,
                const __grid_constant__ CUtensorMap tmx, const __grid_constant__ CUtensorMap tmq, const __grid_constant__ CUtensorMap tmo64,
                const __grid_constant__ CUtensorMap tmo32, const __grid_constant__ CUtensorMap tmqp, const __grid_constant__ CUtensorMap tmx16,
                const __grid_constant__ CUtensorMap tmx64, const __grid_constant__ CUtensorMap tmq1) {
    extern __shared__ __align__(1024) uint8_t smem[];
    const uint32_t sbase = smem_u32(smem);
    const uint32_t cl = blockIdx.y;
    const uint32_t tile = cl < 36 ? (cl < 4 ? cl * 16 + 15 : ((cl - 4) & 7) + ((cl - 4) & 24) * 2) : cl - 28 + (((cl - 36) * 37) >> 8) * 9;
    const int rank = blockIdx.x, nt = tile & 15, pair = tile >> 4;
    uint4 q[4], c0, c1;
    uint2 sf;
    if (threadIdx.x < 224) {
        const uint32_t t = threadIdx.x;
        const int* p = qw + (uint32_t)((t & 3) * (N_ - 1) + t + blockIdx.x * (8 * N_) + nt * BN);
        q[0] = ldg128(p); q[1] = ldg128(p + 4 * N_);
        q[2] = ldg128(p + 16 * N_); q[3] = ldg128(p + 20 * N_);
        const void* ps = absmax + (uint32_t)(opq(t & ~3u) + nt * BN);
        asm volatile("ld.global.nc.v2.b32 {%0, %1}, [%2];" : "=r"(sf.x), "=r"(sf.y) : "l"(ps) : "memory");
        c0 = ldg128(cb); c1 = ldg128(cb + 8);
    }
    const unsigned tstart = clk();
    const int mt = pair * 2 + rank;
    const int lane = threadIdx.x & 31;
    const int warp = __reduce_max_sync(~0u, threadIdx.x >> 5);
    const int wg = warp >> 2;
    const uint32_t bars = sbase + BAR_OFF;
    const uint32_t full = bars, rawfull = bars + 96, written = bars + 120, xbar = bars + 144, gbar = bars + 160 + wg * 16;
    const uint32_t rawh = bars + 192 - 8, ebar = bars + 216, ones = bars + 256;
    const uint32_t wbase = sbase + W_OFF;
    __syncwarp();

    auto insert = [](uint64_t m, int pos, int v) { const uint64_t low = (1ull << (4 * pos)) - 1; return (m & low) | ((m & ~low) << 4) | ((uint64_t)v << (4 * pos)); };
    const uint64_t others = (0xedcfedu >> (4 * pair)) & 0xfff;
    const uint64_t cmap = insert(insert(0x76543210ull, G1, 8 + pair), G2, 12 + pair) | ((others - 0x444) << 40) | (others << 52);
    auto chunk = [&](int i) { return (int)(cmap >> (4 * i)) & 15; };
    unsigned* flag = gflag + nt * 32;
    uint8_t* wpan = wimg + nt * (16 * UNIT);
    auto load_x = [&](int i, int slot, uint32_t bar) {
        tma_load_2d(sbase + slot * 32768, &tmx, chunk(i) * 64, mt * BM, bar);
        tma_load_2d(sbase + slot * 32768 + 16384, &tmx, chunk(i) * 64, mt * BM + 128, bar);
    };
    auto load_l = [&](int i, int slot, int g, uint32_t bar) {
        tma_load_2d(sbase + slot * 32768 + g * 16384, &tmx64, chunk(i) * 64, mt * BM + g * 128, bar);
        tma_load_2d(sbase + slot * 32768 + g * 16384 + 8192, &tmx64, chunk(i + 1) * 64, mt * BM + g * 128, bar);
    };
    auto snap = [&](int ss, uint32_t bar) { bulk_load(sbase + SC_OFF + ss * SC_STRIDE + 448, flag, 16, bar); };
    auto load_sc = [&](int i, int ss, uint32_t bar) {
        bulk_load(sbase + SC_OFF + ss * SC_STRIDE, absmax + chunk(i) * N_ + nt * BN, 448, bar);
    };
    auto load_raw = [&](int u, int slot) {
        mbar_expect_tx(rawfull + 8 * slot, UNIT);
        tma_load_5d(sbase + RAW_OFF + roff(slot), &tmq, 0, 0, nt * 7, rank, 4 * chunk(u >> 1) + 2 * (u & 1), rawfull + 8 * slot);
    };
    auto load_half = [&](int b, uint32_t more) {
        const uint32_t bar = (b & 1) ? rawfull + 8 * rslot(b >> 1) : rawh + 8 * (b >> 1);
        mbar_expect_tx(bar, 7168 + more);
        tma_load_5d(sbase + RAW_OFF + roff(rslot(b >> 1)) + (b & 1) * 7168, &tmq1, 0, 0, nt * 7, rank, b, bar);
    };
    auto load_w = [&](int v) {
        mbar_expect_tx(bars + ubar(v), UNIT + (!(v & 1) && v <= 24 ? 32768 : 0) + (v == 21 ? 16 : 0));
        bulk_load(sbase + uoff(v), wpan + (2 * (chunk(v >> 1) - 8) + (v & 1)) * UNIT, UNIT, bars + ubar(v));
    };
    auto prefetch_q = [&](int c) { if (c + PFQ < 8) tma_prefetch_2d(&tmqp, nt * BN, (c + PFQ) * 64 + pair * 16 + rank * 8); };
    auto prefetch_g = [&](int c) {
        if (c < 6) {
            const int k = c, k0 = k + (k >= 3);
            tma_prefetch_2d(&tmqp, nt * BN, (8 + (k0 & 4) + pair) * 64 + (k0 & 3) * 16 + rank * 8);
            if (k == 1 || k == 4) tma_prefetch_2d(&tmqp, nt * BN, (8 + (k0 & 4) + pair) * 64 + 48 + rank * 8);
        }
    };
    auto prefetch_x = [&](int i) { tma_prefetch_2d(&tmx16, chunk(i) * 64, mt * BM + nt * 16); };
    if (warp == 7) {
        if (elect()) {
            mbar_init(xbar, 1); mbar_init(rawh + 8, 1); mbar_init(rawfull + 8 * rslot(1), 1); mbar_init(xbar + 8, 1);
            fence_async_smem();
            load_half(2, 448);
            bulk_load(sbase + SC_OFF + sslot(0) * SC_STRIDE, absmax + nt * BN, 448, rawh + 8);
            load_half(3, 0);
            mbar_expect_tx(xbar, 16384);
            tma_load_2d(sbase, &tmx, 0, mt * BM, xbar);
            mbar_expect_tx(xbar + 8, 16384);
            tma_load_2d(sbase + 16384, &tmx, 0, mt * BM + 128, xbar + 8);
            mbar_init(rawfull + 8 * rslot(2), 1); mbar_init(rawfull + 8 * rslot(3), 1); mbar_init(rawh + 16, 1); mbar_init(rawh + 24, 1);
            mbar_init(ebar, 7); mbar_init(ebar + 8, 7);
            sts128(ones, make_uint4(1, 0, 0, 0)); sts128(ones + 16, make_uint4(0, 1, 0, 0));
#pragma unroll
            for (int s = 0; s < 12; s++) { mbar_init(full + 8 * s, 1); if (s < 4) mbar_arrive(full + 8 * s); }
#pragma unroll
            for (int s = 0; s < 3; s++) mbar_init(written + 8 * s, 7);
#pragma unroll
            for (int s = 0; s < 4; s++) mbar_init(bars + 160 + 8 * s, 4);
            asm volatile("fence.mbarrier_init.release.cluster;" ::: "memory");
            fence_async_smem();
            if ((sbase & 0xffffff) != 0x400) __trap();
        }
        __syncwarp();
        cluster_arrive();
        if (elect()) {
            asm volatile("prefetch.tensormap [%0];" ::"l"(&tmq) : "memory");
            asm volatile("prefetch.tensormap [%0];" ::"l"(&tmqp) : "memory");
            asm volatile("prefetch.tensormap [%0];" ::"l"(&tmx16) : "memory");
            asm volatile("prefetch.tensormap [%0];" ::"l"(&tmx64) : "memory");
            while (clk() - tstart < T2) { }
            load_half(4, 2 * 448 + 16);
            load_sc(1, sslot(1), rawh + 16); load_sc(2, sslot(2), rawh + 16); snap(sslot(1), rawh + 16);
            load_half(5, 0);
            while (clk() - tstart < T2B) { }
            tma_load_2d(sbase + 32768, &tmx, 64, mt * BM, full + 32);
            load_half(6, 0); load_half(7, 0);
            tma_load_2d(sbase + 32768 + 16384, &tmx, 64, mt * BM + 128, full + 32);
            load_sc(3, sslot(3), full + 48);
            while (clk() - tstart < T3) { }
            prefetch_q(-2); prefetch_q(-1);
            asm volatile("cp.async.bulk.prefetch.L2.global [%0], 448;" ::"l"(absmax + (2 * mt) * N_ + nt * BN) : "memory");
            asm volatile("cp.async.bulk.prefetch.L2.global [%0], 448;" ::"l"(absmax + (2 * mt + 1) * N_ + nt * BN) : "memory");
        }
        __syncwarp();
        cluster_wait();
    } else {
        cluster_arrive();
    }
    const uint32_t rsrc = __shfl_sync(~0u, sbase + RAW_OFF + warp * 1024 + (lane & 7) * 128 + ((((lane >> 3) * 2) ^ (lane & 7)) << 4), lane);
    const uint32_t ssrc = sbase + SC_OFF + warp * 64;
    const int wpos = (nt & 1) ? (0x73210546 >> (4 * warp)) & 7 : warp;
    const uint32_t wown = wbase + rank * 7168 + wpos * 512;
    const uint32_t wdst = __shfl_sync(~0u, wown + lane * 16, lane);
    auto get_sc = [&](int ss) { return lds128(((opq(wdst) >> 3) & 0x30) + ssrc + ss * SC_STRIDE); };
    const uint32_t whalf = wbase + rank * 7168;
    const uint32_t pwhalf = mapa(whalf, rank ^ 1), pbars = mapa(bars, rank ^ 1);
    Lut lut;
    uint4 sc;
    uint4 q0, q1;
    auto fetch = [&](int slot, int h) {
        q0 = lds128(rsrc + roff(slot) + h * 7168);
        q1 = lds128((opq(rsrc) ^ 16) + roff(slot) + h * 7168);
    };
    auto signal = [&](uint32_t bar) { __syncwarp(); if (elect()) mbar_arrive(bar); __syncwarp(); };
    auto convert = [&](int ws, int h, bool w1, uint32_t bar1, uint32_t par1, bool w2, uint32_t bar2, uint32_t par2, bool next, int rsn,
                       bool sig, uint32_t sbar, bool scales, int cs) {
        bool ok1 = true, ok2 = true;
        if (w2) ok2 = mbar_try(bar2, par2);
        if (w1) ok1 = mbar_try(bar1, par1);
        uint4 w = dequant8(pack4(q0), pack4(q1), sc, lut);
        asm volatile("" : "+r"(w.x), "+r"(w.y), "+r"(w.z), "+r"(w.w));
        if (w1 && w2) mbar_wait2(bar2, par2, bar1, par1, ok1 && ok2);
        else if (w2) mbar_wait1(bar2, par2, ok2);
        else if (w1) mbar_wait1(bar1, par1, ok1);
        if (next) fetch(rsn, h ^ 1);
        sts128(wdst + ws * UNIT + h * 3584, w);
        if (sig) signal(sbar);
        if (scales) sc = get_sc(cs);
    };
    auto hand_over = [&](uint32_t sbar, uint32_t par, int ws, int h, uint32_t more, bool raw, int un, int rs, auto extra) {
        mbar_wait(sbar, par);
        fence_async_smem();
        if (elect()) {
            if (raw) load_raw(un, rs);
            copy_to_peer(pwhalf + ws * UNIT + h * 3584, whalf + ws * UNIT + h * 3584, 3584, pbars + 8 * (2 * ws + h));
            mbar_expect_tx(full + 8 * (2 * ws + h), 3584 + more);
            extra();
        }
        __syncwarp();
    };
    auto share = [&](int g, uint32_t o, uint32_t n) {
        bulk_store(wpan + 2 * (chunk(g) - 8) * UNIT + rank * 7168 + o, whalf + 2 * (g % 3) * UNIT + o, n);
        bulk_commit();
    };
    auto publish = [&](int k) {
        asm volatile("cp.async.bulk.wait_group 0;" ::: "memory");
        asm volatile("cp.reduce.async.bulk.global.shared::cta.bulk_group.add.u32 [%0], [%1], 16;" ::"l"(flag), "r"(ones + 16 * k) : "memory");
    };
    auto check = [&](int k, int ss) {
        unsigned f0, f1;
        asm volatile("ld.shared.u32 %0, [%1];" : "=r"(f0) : "r"(sbase + SC_OFF + sslot(1) * SC_STRIDE + 448 + 4 * k) : "memory");
        asm volatile("ld.shared.u32 %0, [%1];" : "=r"(f1) : "r"(sbase + SC_OFF + ss * SC_STRIDE + 448 + 4 * k) : "memory");
        asm volatile("{\n.reg .pred p;\n.reg .u32 n, d;\nmov.u32 n, 0;\nLAB_POLL:\nsub.u32 d, %0, %1;\nsetp.ge.u32 p, d, 8;\n@p bra.uni LAB_DONE;\n"
                     "ld.relaxed.gpu.global.u32 %0, [%2];\nadd.u32 n, n, 1;\nsetp.lt.u32 p, n, 0x10000;\n@p bra.uni LAB_POLL;\nLAB_DONE:\n}\n"
                     : "+r"(f1) : "r"(f0 & ~7u), "l"(flag + k) : "memory");
    };
    auto shares = [&](auto S) {
        constexpr int s = S.value;
        static_for<0, 4>([&](auto K) {
            constexpr int k = K.value;
            if constexpr (sh_at(0, k) == s) { share(G1, (k >> 1) * UNIT + (k & 1) * 3584, 3584); if (k == 3) bulk_wait_read<1>(); }
            if constexpr (sh_at(1, k) == s) share(G2, (k >> 1) * UNIT + (k & 1) * 3584, 3584);
        });
        if (s == sh_at(0, 4)) publish(0);
        if (s == sh_at(1, 4)) publish(1);
    };
    auto sig_bar = [&](int b) { return written + 8 * (b % 3); };
    auto sig_par = [](int b) { return (b / 3 - 1) & 1; };
    auto see = [&](int s) { if (s < 2 * NU) mbar_wait(full + 8 * (s % 12), (s / 12) & 1); else mbar_wait(bars + ubar(s >> 1), upar(s >> 1)); };
    auto block = [&](int b, int sn) {
        const int u = b >> 1, h = b & 1;
        const bool next = b + 1 < 2 * NU;
        convert(u % NW, h, sn == 2 || sn >= 4, sn == 2 ? ebar + 8 : full + 8 * (sn % 12), (sn / 12) & 1,
                next && (h || b < 8), b == 5 ? rawh + 24 : rawfull + 8 * rslot((b + 1) >> 1), b == 5 ? 0 : rpar((b + 1) >> 1),
                next, rslot((b + 1) >> 1), true, sig_bar(b), (b & 3) == 3 && next, sslot((b + 1) >> 2));
    };
    auto hand = [&](int b, auto extra) {
        const int u = b >> 1;
        hand_over(sig_bar(b), sig_par(b), u % NW, b & 1, (b & 3) == 0 ? 32768 : (b & 3) == 2 && b < 36 ? 448 : b == 35 ? 16 : 0, (b & 1) && u + NR < NU, u + NR, rslot(u), extra);
    };
    auto pass_on = [&](int u) {
        fence_async_smem();
        __syncwarp();
        if (elect()) {
            const uint32_t o = wpos * 512 + u * UNIT;
            copy_to_peer(pwhalf + o, whalf + o, 512, pbars + 216 + 8 * u);
            copy_to_peer(pwhalf + o + 3584, whalf + o + 3584, 512, pbars + 216 + 8 * u);
            if (u == 1) mbar_arrive(sig_bar(3));
            mbar_expect_tx(ebar + 8 * u, 1024);
        }
        __syncwarp();
    };
    bool ok0 = false;
    if (warp < 7) {
        lut.lo[0] = __byte_perm(c0.x, c0.y, 0x6420); lut.hi[0] = __byte_perm(c0.x, c0.y, 0x7531);
        lut.lo[1] = __byte_perm(c0.z, c0.w, 0x6420); lut.hi[1] = __byte_perm(c0.z, c0.w, 0x7531);
        lut.lo[2] = __byte_perm(c1.x, c1.y, 0x6420); lut.hi[2] = __byte_perm(c1.x, c1.y, 0x7531);
        lut.lo[3] = __byte_perm(c1.z, c1.w, 0x6420); lut.hi[3] = __byte_perm(c1.z, c1.w, 0x7531);
        const uint32_t d = wown + (lane >> 3) * 128 + (lane & 3) * 16 + (lane & 4) * 2;
#pragma unroll
        for (int j = 0; j < 4; j++) {
            uint32_t a, b;
            lookup4(pack4(q[j]), lut, a, b);
            asm volatile("st.shared.v2.b32 [%0], {%1, %2};" ::"r"(d + (j >> 1) * 3584 + (j & 1) * 64), "r"(mul_bf16x2(a, sf.x)), "r"(mul_bf16x2(b, sf.y)) : "memory");
        }
        cluster_wait();
        pass_on(0);
        mbar_wait(rawh + 8, 0);
        const uint4 a0 = lds128(rsrc + roff(rslot(1))), a1 = lds128((rsrc ^ 16) + roff(rslot(1))), s0 = get_sc(sslot(0));
        mbar_wait(rawfull + 8 * rslot(1), 0);
        const uint4 a2 = lds128(rsrc + roff(rslot(1)) + 7168), a3 = lds128((rsrc ^ 16) + roff(rslot(1)) + 7168);
        sts128(wdst + UNIT, dequant8(pack4(a0), pack4(a1), s0, lut));
        sts128(wdst + UNIT + 3584, dequant8(pack4(a2), pack4(a3), s0, lut));
        ok0 = mbar_try(xbar + 8 * wg, 0) & mbar_try(ebar, 0);
        pass_on(1);
    }
    mbar_wait2(xbar + 8 * wg, 0, ebar, 0, ok0);

    float acc0[112], acc1[112];
    const uint32_t descA = ((0x400 + wg * 16384) >> 4) | (1u << 16);
    auto mma = [&](int s) {
        const uint32_t da = opq(descA) + ((s >> 2) % 3) * (32768 >> 4) + (s & 3) * 2;
        wgmma_fence();
        wgmma224<1, 8>(acc0, da, bdesc(s)); wgmma224<1, 8>(acc1, da + 512, bdesc(s));
        wgmma_commit();
        wgmma_wait<2>();
    };
    wgmma_fence();
    wgmma224<0, 8>(acc0, descA, bdesc(0)); wgmma224<0, 8>(acc1, descA + 512, bdesc(0));
    wgmma_commit();
    mma(1);
    if (warp < 7) {
        mbar_wait(rawh + 16, 0); fetch(rslot(2), 0); sc = get_sc(sslot(1));
        block(4, 2);
    } else {
        mbar_wait(sig_bar(3), sig_par(3));
        if (elect()) { load_raw(4, rslot(4)); load_x(2, 2, full + 64); prefetch_q(0); prefetch_x(3); prefetch_g(0); }
        __syncwarp();
        mbar_wait(ebar + 8, 0);
    }
    static_for<2, 8>([&](auto S) {
        constexpr int s = S.value;
        mma(s);
        if (warp < 7) { if (s <= 3) block(s + 3, s < 3 ? s + 1 : -1); if (s >= 3) block(s + 4, s + 1); }
        else {
            if (s <= 3) hand(s + 2, [] {});
            if (s >= 3) hand(s + 3, [&] {
                if (s == 4) prefetch_q(1);
                if (s == 5) { load_sc(4, sslot(4), full + 80); prefetch_g(1); }
                if (s == 6) prefetch_x(4);
                if (s == 7) load_x(3, 0, full);
            });
            if (s >= 3) see(s + 1);
        }
    });
    {
        uint32_t ph = 0;
#pragma unroll 1
        for (int cb = 2; cb < 8; cb += 3)
          static_for<2, 5>([&](auto I) {
            constexpr int cc = I.value;
            constexpr int j0 = cc % 3, j1 = (cc + 1) % 3, j2 = (cc + 2) % 3;
            const int c = cb + cc - 2;
            auto sh = [&](auto KS) {
                static_for<0, 2>([&](auto IT) {
                    constexpr int s = 4 * (cc + 3 * IT.value) + KS.value;
                    if constexpr (shares_at(s)) { if (cb == 2 + 3 * IT.value) shares(IC<s>{}); }
                });
            };
            mma(4 * j0);
            if (warp < 7) convert(2 * j1, 0, true, full + 32 * j0 + 8, ph, false, 0, 0, true, j1, true, sig_bar(4 * cc + 4), false, 0);
            else {
                const bool ok = mbar_try(full + 32 * j0 + 8, ph);
                hand_over(sig_bar(4 * cc + 3), sig_par(4 * cc + 3), 2 * j0 + 1, 1, 0, true, 2 * c + 4, j2, [&] { prefetch_q(c); if (cc == 3 && c == 6) prefetch_x(12); sh(IC<0>{}); });
                mbar_wait1(full + 32 * j0 + 8, ph, ok);
            }
            mma(4 * j0 + 1);
            if (warp < 7) convert(2 * j1, 1, true, full + 32 * j0 + 16, ph, true, rawfull + 8 * j0, rpar(2 * cc + 3), true, j0, true, sig_bar(4 * cc + 5), false, 0);
            else {
                const bool ok = mbar_try(full + 32 * j0 + 16, ph);
                hand_over(sig_bar(4 * cc + 4), sig_par(4 * cc + 4), 2 * j1, 0, 32768, false, 0, 0, [&] { load_sc(c + 3, j0, full + 32 * j1 + 16); prefetch_g(c); sh(IC<1>{}); });
                mbar_wait1(full + 32 * j0 + 16, ph, ok);
            }
            mma(4 * j0 + 2);
            if (warp < 7) convert(2 * j1 + 1, 0, true, full + 32 * j0 + 24, ph, false, 0, 0, true, j0, true, sig_bar(4 * cc + 6), false, 0);
            else {
                const bool ok = mbar_try(full + 32 * j0 + 24, ph);
                hand_over(sig_bar(4 * cc + 5), sig_par(4 * cc + 5), 2 * j1, 1, 0, true, 2 * c + 5, j1, [&] { prefetch_x(c + PFX); sh(IC<2>{}); });
                mbar_wait1(full + 32 * j0 + 24, ph, ok);
            }
            if (j1 == 0) asm volatile("xor.b32 %0, %0, 1;" : "+r"(ph));
            mma(4 * j0 + 3);
            if (warp < 7) convert(2 * j1 + 1, 1, true, full + 32 * j1, ph, true, rawfull + 8 * j2, rpar(2 * cc + 4), true, j2, true, sig_bar(4 * cc + 7), true, j2);
            else {
                const bool ok = mbar_try(full + 32 * j1, ph);
                hand_over(sig_bar(4 * cc + 6), sig_par(4 * cc + 6), 2 * j1 + 1, 0, 448, false, 0, 0, [&] { load_x(c + 2, j2, full + 32 * j2); sh(IC<3>{}); });
                mbar_wait1(full + 32 * j1, ph, ok);
            }
          });
    }
    uint4 fa[8];
    auto get_frag = [&](int f, uint32_t rows, int j0 = 0, int j1 = 4) {
        int ln; asm volatile("mov.u32 %0, %%laneid;" : "=r"(ln));
        const uint32_t a = rows + (ln & 15) * 128 + (((ln >> 4) ^ (ln & 7)) << 4);
#pragma unroll
        for (int j = j0; j < j1; j++) fa[4 * f + j] = ldmatrix_x4(a ^ (j * 32));
    };
    static_for<32, 46>([&](auto S) {
        constexpr int s = S.value;
        constexpr int vb = 40 + (s - 37) / 2;
        mma(s);
        if (s == 39) cluster_arrive();
        if (s == 41) cluster_wait();
        if (s == 36) mbar_wait(rawh + 8, 1);
        if (s >= 36 && s < 40) get_frag(0, sbase + uoff(24) + wg * (uoff(23) - uoff(24)) + (warp & 3) * 2048, s - 36, s - 35);
        if (warp < 7) {
            if (s < 36) block(s + 4, s + 1);
            else {
                if (s & 1) signal(sig_bar(vb));
                if (s < 39 || (s & 1)) see(s + 1);
            }
        } else {
            auto loads = [&] {
                static_for<NU, 30>([&](auto V) { if constexpr (utime(V.value) == s) load_w(V.value); });
                if (s == 33) prefetch_x(11);
                if (s == 32) {
                    mbar_expect_tx(rawh + 8, 16384);
                    tma_load_2d(sbase + uoff(24), &tmx64, chunk(12) * 64, mt * BM + 64, rawh + 8);
                    tma_load_2d(sbase + uoff(23), &tmx64, chunk(12) * 64, mt * BM + 192, rawh + 8);
                }
                if (s == 37) prefetch_x(13);
                if (s == 39) snap(1, bars + ubar(21));
                if (s == 41) { prefetch_x(14); prefetch_x(15); }
                if (s == 43) { load_l(12, 0, 0, bars + ubar(24)); load_l(12, 0, 1, bars + ubar(24)); }
                if (s == 34) load_x(10, 1, bars + ubar(20));
                if (s == 39) load_x(11, 2, bars + ubar(22));
                if (s == 44) {
                    asm volatile("prefetch.tensormap [%0];" ::"l"(&tmo64) : "memory");
                    asm volatile("prefetch.tensormap [%0];" ::"l"(&tmo32) : "memory");
                }
                if (s == 45) { mbar_expect_tx(xbar, 16384); load_l(14, 1, 0, xbar); }
                if (s == 45) load_w(30);
                shares(S);
            };
            if (s == 32) { if (elect()) snap(0, full + 8 * (35 % 12)); __syncwarp(); }
            if (s == 35) check(0, 0);
            if (s == 42) check(1, 1);
            if (s <= 36) hand(s + 3, loads);
            else {
                if (!(s & 1)) mbar_wait(sig_bar(40 + (s - 38) / 2), sig_par(40 + (s - 38) / 2));
                if (s == 45) mbar_wait(sig_bar(vb), sig_par(vb));
                if (elect()) loads();
                __syncwarp();
            }
            if (s < 39 || (s & 1)) see(s + 1);
        }
    });
    if (wg == 1) bar_sync(8);
    mma(46);
    if (warp == 7) {
        wgmma_wait<1>();
        if (elect()) { load_w(31); mbar_expect_tx(xbar + 8, 16384); load_l(14, 1, 1, xbar + 8); }
        __syncwarp();
    }
    mma(47);
    if (wg == 0) bar_arrive(8);
    const uint32_t slice0 = sbase + wg * 16384 + (warp & 3) * 2048;
    auto slc = [&](int p) { return slice0 + (p >> 1) * 32768 + (p & 1) * 8192; };
    const int row0 = mt * BM + wg * 128 + (warp & 3) * 16, odd = nt & 1;
    const int colL = nt * BN + odd * 96, colA = nt * BN + (odd ? 32 : 128), colB = nt * BN + (odd ? 0 : 192);
    auto load_s = [&](int i, int p, uint32_t bar) { tma_load_2d(slc(p), &tmx16, chunk(i) * 64, row0 + 64, bar); };
    const uint32_t tA = opq(descA);
    see(48);
    wgmma_wait<0>();
    float lo0[64], hi0[48], lo1[64], hi1[48];
#pragma unroll
    for (int i = 0; i < 64; i++) { asm volatile("mov.b32 %0, %1;" : "=f"(lo0[i]) : "f"(acc0[i])); asm volatile("mov.b32 %0, %1;" : "=f"(lo1[i]) : "f"(acc1[i])); }
#pragma unroll
    for (int i = 0; i < 48; i++) { asm volatile("mov.b32 %0, %1;" : "=f"(hi0[i]) : "f"(acc0[64 + i])); asm volatile("mov.b32 %0, %1;" : "=f"(hi1[i]) : "f"(acc1[64 + i])); }
    auto tdesc = [&](int p, int s) { return tA + (p >> 1) * (32768 >> 4) + (p & 1) * 512 + (s & 3) * 2; };
    auto ldesc = [&](int s) { return tdesc(s >> 2, s); };
    auto gdesc = [&](int s) { return tdesc(((s >> 2) + 3) % 6, s); };
    if (wg == 1) { mbar_wait(xbar + 8, 1); bar_sync(1); }
    static_for<0, 8>([&](auto V) {
        constexpr int v = 24 + V.value, s = 2 * V.value;
        if (v == 26) mbar_wait2(bars + ubar(26), upar(26), bars + ubar(27), upar(27), wg);
        else if (v == 28) mbar_wait2(bars + ubar(28), upar(28), xbar, 1, wg);
        else if (v != 24 && v != 27) mbar_wait1(bars + ubar(v), upar(v), wg);
        wgmma_fence();
        wgmma96<1, 8>(hi0, ldesc(s), bdesc(48 + s) + 128);
        wgmma96<1, 8>(hi0, ldesc(s + 1), bdesc(49 + s) + 128);
    });
    wgmma_commit();
    bar_arrive(1 + wg);
    wgmma_wait<0>();
    stage_cols<64, 0>(hi0, slc(4)); send(slc(4), &tmo64, colA, row0);
    stage_cols<32, 32>(hi0, slc(5));
    bar_sync(2 + wg);
    wgmma_fence();
    static_for<0, 7>([&](auto S) { wgmma128<1, 8>(lo0, ldesc(S.value), bdesc(48 + S.value)); });
    wgmma_commit();
    send(slc(5), &tmo32, colB, row0);
    wgmma_fence();
    static_for<7, 16>([&](auto S) { wgmma128<1, 8>(lo0, ldesc(S.value), bdesc(48 + S.value)); });
    wgmma_commit();
    bar_arrive(3 + wg);
    {
        const uint32_t zero = opq(gridDim.x - 2);
#pragma unroll
        for (int j = 0; j < 4; j++) { fa[j].x ^= zero; fa[j].y ^= zero; fa[j].z ^= zero; fa[j].w ^= zero; asm volatile("" : "+r"(fa[j].x), "+r"(fa[j].y), "+r"(fa[j].z), "+r"(fa[j].w)); }
    }
    if (elect()) { mbar_expect_tx(gbar, 4096); bulk_wait_read<0>(); load_s(13, 4, gbar); load_s(14, 5, gbar); }
    __syncwarp();
    wgmma_wait<0>();
    stage_cols<64, 0>(lo0, slc(2));
    if (elect()) { mbar_expect_tx(gbar + 8, 2048); load_s(15, 0, gbar + 8); }
    __syncwarp();
    const bool okg = mbar_try(gbar, 0);
    send(slc(2), &tmo64, colL, row0);
    stage_cols<64, 32>(lo0, slc(3));
    mbar_wait1(gbar, 0, okg);
    auto mma2 = [&](auto I) { constexpr int s = I.value; if constexpr (s < 4) wgmma128r<8>(lo1, fa[s], bdesc(48 + s)); else wgmma128<1, 8>(lo1, gdesc(s), bdesc(48 + s)); };
    auto mma3 = [&](auto I) { constexpr int s = I.value; if constexpr (s < 8) wgmma96r<8>(hi1, fa[s], bdesc(48 + s) + 128); else wgmma96<1, 8>(hi1, gdesc(s), bdesc(48 + s) + 128); };
    bar_sync(4 + wg);
    wgmma_fence();
    static_for<0, 8>(mma2);
    wgmma_commit();
    const bool okg2 = mbar_try(gbar + 8, 0);
    send(slc(3), &tmo64, colL + 64, row0);
    mbar_wait1(gbar + 8, 0, okg2);
    wgmma_fence();
    static_for<8, 16>(mma2);
    wgmma_commit();
    bar_arrive(5 + wg);
    get_frag(1, slc(4));
    if (elect()) bulk_wait_read<1>();
    __syncwarp();
    wgmma_wait<0>();
    stage_cols<64, 0>(lo1, slc(1)); send(slc(1), &tmo64, colL, row0 + 64);
    stage_cols<64, 32>(lo1, slc(2));
    bar_sync(6 + wg);
    wgmma_fence();
    static_for<0, 6>(mma3);
    wgmma_commit();
    send(slc(2), &tmo64, colL + 64, row0 + 64);
    wgmma_fence();
    static_for<6, 16>(mma3);
    wgmma_commit();
    if (wg == 0) bar_arrive(7);
    wgmma_wait<0>();
    stage_cols<64, 0>(hi1, slc(4)); send(slc(4), &tmo64, colA, row0 + 64);
    stage_cols<32, 32>(hi1, slc(5)); send(slc(5), &tmo32, colB, row0 + 64);
    if (elect()) bulk_wait_read<0>();
    __syncwarp();
}

typedef CUresult (*EncodeFn)(CUtensorMap*, CUtensorMapDataType, cuuint32_t, void*, const cuuint64_t*, const cuuint64_t*,
                             const cuuint32_t*, const cuuint32_t*, CUtensorMapInterleave, CUtensorMapSwizzle,
                             CUtensorMapL2promotion, CUtensorMapFloatOOBfill);

extern "C" void kernel_launch(void* const* d_in, const int* in_sizes, int n_in, void* d_out, int out_size) {
    const __nv_bfloat16* x = (const __nv_bfloat16*)d_in[0];
    const int* qw = (const int*)d_in[1];
    const __nv_bfloat16* cb = (const __nv_bfloat16*)d_in[2];
    const __nv_bfloat16* absmax = (const __nv_bfloat16*)d_in[3];
    static EncodeFn encode = nullptr;
    static void *wimg = nullptr, *gflag = nullptr;
    if (!encode) {
        cudaGetSymbolAddress(&wimg, g_wimg);
        cudaGetSymbolAddress(&gflag, g_flag);
        void* fn = nullptr;
        cudaDriverEntryPointQueryResult qr;
        cudaGetDriverEntryPoint("cuTensorMapEncodeTiled", &fn, cudaEnableDefault, &qr);
        encode = (EncodeFn)fn;
        cudaFuncSetAttribute(nf4_gemm_kernel, cudaFuncAttributeMaxDynamicSharedMemorySize, SMEM_BYTES);
    }
    CUtensorMap tmx, tmq, tmo64, tmo32, tmqp, tmx16, tmx64, tmq1;
    {
        cuuint64_t dims[2] = {(cuuint64_t)K_, (cuuint64_t)M_};
        cuuint64_t strides[1] = {(cuuint64_t)K_ * 2};
        cuuint32_t box[2] = {64, 128};
        cuuint32_t es[2] = {1, 1};
        encode(&tmx, CU_TENSOR_MAP_DATA_TYPE_BFLOAT16, 2, (void*)x, dims, strides, box, es, CU_TENSOR_MAP_INTERLEAVE_NONE,
               CU_TENSOR_MAP_SWIZZLE_128B, CU_TENSOR_MAP_L2_PROMOTION_L2_128B, CU_TENSOR_MAP_FLOAT_OOB_FILL_NONE);
        box[1] = 64;
        encode(&tmx64, CU_TENSOR_MAP_DATA_TYPE_BFLOAT16, 2, (void*)x, dims, strides, box, es, CU_TENSOR_MAP_INTERLEAVE_NONE,
               CU_TENSOR_MAP_SWIZZLE_128B, CU_TENSOR_MAP_L2_PROMOTION_L2_128B, CU_TENSOR_MAP_FLOAT_OOB_FILL_NONE);
        box[1] = 16;
        encode(&tmx16, CU_TENSOR_MAP_DATA_TYPE_BFLOAT16, 2, (void*)x, dims, strides, box, es, CU_TENSOR_MAP_INTERLEAVE_NONE,
               CU_TENSOR_MAP_SWIZZLE_128B, CU_TENSOR_MAP_L2_PROMOTION_L2_128B, CU_TENSOR_MAP_FLOAT_OOB_FILL_NONE);
    }
    {
        cuuint64_t dims[5] = {32, 8, (cuuint64_t)(N_ / 32), 2, (cuuint64_t)(K_ / 16)};
        cuuint64_t strides[4] = {(cuuint64_t)N_ * 4, 128, (cuuint64_t)N_ * 4 * 8, (cuuint64_t)N_ * 4 * 16};
        cuuint32_t box[5] = {32, 8, 7, 1, 2};
        cuuint32_t es[5] = {1, 1, 1, 1, 1};
        encode(&tmq, CU_TENSOR_MAP_DATA_TYPE_INT32, 5, (void*)qw, dims, strides, box, es, CU_TENSOR_MAP_INTERLEAVE_NONE,
               CU_TENSOR_MAP_SWIZZLE_128B, CU_TENSOR_MAP_L2_PROMOTION_L2_128B, CU_TENSOR_MAP_FLOAT_OOB_FILL_NONE);
        box[4] = 1;
        encode(&tmq1, CU_TENSOR_MAP_DATA_TYPE_INT32, 5, (void*)qw, dims, strides, box, es, CU_TENSOR_MAP_INTERLEAVE_NONE,
               CU_TENSOR_MAP_SWIZZLE_128B, CU_TENSOR_MAP_L2_PROMOTION_L2_128B, CU_TENSOR_MAP_FLOAT_OOB_FILL_NONE);
        cuuint64_t dims2[2] = {(cuuint64_t)N_, (cuuint64_t)K_};
        cuuint32_t box2[2] = {224, 8};
        encode(&tmqp, CU_TENSOR_MAP_DATA_TYPE_INT32, 2, (void*)qw, dims2, strides, box2, es, CU_TENSOR_MAP_INTERLEAVE_NONE,
               CU_TENSOR_MAP_SWIZZLE_NONE, CU_TENSOR_MAP_L2_PROMOTION_L2_128B, CU_TENSOR_MAP_FLOAT_OOB_FILL_NONE);
    }
    {
        cuuint64_t dims[2] = {(cuuint64_t)N_, (cuuint64_t)M_};
        cuuint64_t strides[1] = {(cuuint64_t)N_ * 2};
        cuuint32_t box[2] = {64, 16};
        cuuint32_t es[2] = {1, 1};
        encode(&tmo64, CU_TENSOR_MAP_DATA_TYPE_BFLOAT16, 2, d_out, dims, strides, box, es, CU_TENSOR_MAP_INTERLEAVE_NONE,
               CU_TENSOR_MAP_SWIZZLE_128B, CU_TENSOR_MAP_L2_PROMOTION_NONE, CU_TENSOR_MAP_FLOAT_OOB_FILL_NONE);
        box[0] = 32;
        encode(&tmo32, CU_TENSOR_MAP_DATA_TYPE_BFLOAT16, 2, d_out, dims, strides, box, es, CU_TENSOR_MAP_INTERLEAVE_NONE,
               CU_TENSOR_MAP_SWIZZLE_64B, CU_TENSOR_MAP_L2_PROMOTION_NONE, CU_TENSOR_MAP_FLOAT_OOB_FILL_NONE);
    }
    nf4_gemm_kernel<<<dim3(2, 64), 256, SMEM_BYTES>>>(qw, cb, absmax, (uint8_t*)wimg, (unsigned*)gflag, tmx, tmq, tmo64, tmo32, tmqp, tmx16, tmx64, tmq1);
}
```

```cpp
#include <cuda_runtime.h>
#include <cuda_bf16.h>
#include <cuda.h>
#include <stdint.h>

constexpr int M_ = 2048, K_ = 1024, N_ = 3584;
constexpr int BM = 256, BN = 224;
constexpr int UNIT = 14336;
constexpr int NW = 6, NR = 3;
constexpr int NU = 20;
constexpr int G1 = 5, G2 = 8;
constexpr int PFQ = 4, PFX = 3;
constexpr unsigned T2 = 900, T2B = 1300, T3 = 1700;
constexpr int RAW_OFF = 3 * 32768;
constexpr int SC_OFF = RAW_OFF + 2 * UNIT;
constexpr int SC_STRIDE = 464;
constexpr int W_OFF = 127 * 1024;
constexpr int RAW2_OFF = W_OFF + NW * UNIT;
constexpr int BAR_OFF = RAW2_OFF + UNIT;
constexpr int SMEM_BYTES = BAR_OFF + 320;
__device__ __align__(1024) uint8_t g_wimg[16 * 16 * UNIT];
__device__ __align__(128) unsigned g_flag[16 * 32];

__device__ __forceinline__ uint32_t smem_u32(const void* p) { return (uint32_t)__cvta_generic_to_shared(p); }
__device__ __forceinline__ bool elect() {
    uint32_t ok;
    asm volatile("{\n.reg .pred p;\nelect.sync _|p, 0xffffffff;\nselp.u32 %0, 1, 0, p;\n}\n" : "=r"(ok));
    return ok != 0;
}
__device__ __forceinline__ void mbar_init(uint32_t bar, uint32_t cnt) { asm volatile("mbarrier.init.shared::cta.b64 [%0], %1;" ::"r"(bar), "r"(cnt) : "memory"); }
__device__ __forceinline__ void mbar_expect_tx(uint32_t bar, uint32_t bytes) { asm volatile("mbarrier.arrive.expect_tx.shared::cta.b64 _, [%0], %1;" ::"r"(bar), "r"(bytes) : "memory"); }
__device__ __forceinline__ void mbar_arrive(uint32_t bar) { asm volatile("mbarrier.arrive.shared::cta.b64 _, [%0];" ::"r"(bar) : "memory"); }
#define BOUNDED
#define WAIT_INIT "mov.u32 n, 0;\n"
#define WAIT_NEXT "@p bra.uni LAB_DONE;\nadd.u32 n, n, 1;\nsetp.lt.u32 p, n, 0x4000;\n@p bra.uni LAB_WAIT;\n"
__device__ __forceinline__ void mbar_wait(uint32_t bar, uint32_t parity) {
    asm volatile(
        "{\n.reg .pred p;\n.reg .u32 n;\n"
        WAIT_INIT
        "LAB_WAIT:\n"
        "mbarrier.try_wait.parity.shared::cta.b64 p, [%0], %1;\n"
        WAIT_NEXT
        "LAB_DONE:\n}\n" ::"r"(bar), "r"(parity) : "memory");
}
__device__ __forceinline__ bool mbar_try(uint32_t bar, uint32_t parity) {
    uint32_t ok;
    asm volatile("{\n.reg .pred p;\nmbarrier.test_wait.parity.shared::cta.b64 p, [%1], %2;\nselp.u32 %0, 1, 0, p;\n}\n" : "=r"(ok) : "r"(bar), "r"(parity) : "memory");
    return ok != 0;
}
__device__ __forceinline__ void mbar_wait1(uint32_t b0, uint32_t p0, bool skip) {
    asm volatile(
        "{\n.reg .pred p;\n.reg .u32 n;\n"
        "setp.ne.u32 p, %2, 0;\n@p bra.uni LAB_DONE;\n"
        WAIT_INIT
        "LAB_WAIT:\n"
        "mbarrier.try_wait.parity.shared::cta.b64 p, [%0], %1;\n"
        WAIT_NEXT
        "LAB_DONE:\n}\n" ::"r"(b0), "r"(p0), "r"((uint32_t)skip) : "memory");
}
__device__ __forceinline__ void mbar_wait2(uint32_t b0, uint32_t p0, uint32_t b1, uint32_t p1, bool skip = false) {
    asm volatile(
        "{\n.reg .pred p, q;\n.reg .u32 n;\n"
        "setp.ne.u32 p, %4, 0;\n@p bra.uni LAB_DONE;\n"
        WAIT_INIT
        "LAB_WAIT:\n"
        "mbarrier.try_wait.parity.shared::cta.b64 p, [%0], %1;\n"
        "mbarrier.try_wait.parity.shared::cta.b64 q, [%2], %3;\n"
        "and.pred p, p, q;\n"
        WAIT_NEXT
        "LAB_DONE:\n}\n" ::"r"(b0), "r"(p0), "r"(b1), "r"(p1), "r"((uint32_t)skip) : "memory");
}
__device__ __forceinline__ void tma_load_2d(uint32_t dst, const CUtensorMap* tm, int c0, int c1, uint32_t bar) {
    asm volatile("cp.async.bulk.tensor.2d.shared::cluster.global.mbarrier::complete_tx::bytes [%0], [%1, {%2, %3}], [%4];"
                 ::"r"(dst), "l"(tm), "r"(c0), "r"(c1), "r"(bar) : "memory");
}
__device__ __forceinline__ void tma_load_5d(uint32_t dst, const CUtensorMap* tm, int c0, int c1, int c2, int c3, int c4, uint32_t bar) {
    asm volatile("cp.async.bulk.tensor.5d.shared::cluster.global.mbarrier::complete_tx::bytes [%0], [%1, {%2, %3, %4, %5, %6}], [%7];"
                 ::"r"(dst), "l"(tm), "r"(c0), "r"(c1), "r"(c2), "r"(c3), "r"(c4), "r"(bar) : "memory");
}
__device__ __forceinline__ void tma_prefetch_2d(const CUtensorMap* tm, int c0, int c1) {
    asm volatile("cp.async.bulk.prefetch.tensor.2d.L2.global [%0, {%1, %2}];" ::"l"(tm), "r"(c0), "r"(c1) : "memory");
}
__device__ __forceinline__ void bulk_load(uint32_t dst, const void* src, uint32_t bytes, uint32_t bar) {
    asm volatile("cp.async.bulk.shared::cluster.global.mbarrier::complete_tx::bytes [%0], [%1], %2, [%3];"
                 ::"r"(dst), "l"(src), "r"(bytes), "r"(bar) : "memory");
}
__device__ __forceinline__ void cluster_arrive() { asm volatile("barrier.cluster.arrive.relaxed.aligned;" ::: "memory"); }
__device__ __forceinline__ void cluster_wait() { asm volatile("barrier.cluster.wait.acquire.aligned;" ::: "memory"); }
__device__ __forceinline__ uint32_t mapa(uint32_t addr, uint32_t cta) {
    uint32_t r; asm("mapa.shared::cluster.u32 %0, %1, %2;" : "=r"(r) : "r"(addr), "r"(cta)); return r;
}
__device__ __forceinline__ void copy_to_peer(uint32_t cdst, uint32_t src, uint32_t bytes, uint32_t cbar) {
    asm volatile("cp.async.bulk.shared::cluster.shared::cta.mbarrier::complete_tx::bytes [%0], [%1], %2, [%3];"
                 ::"r"(cdst), "r"(src), "r"(bytes), "r"(cbar) : "memory");
}
__device__ __forceinline__ void wgmma_fence() { asm volatile("wgmma.fence.sync.aligned;" ::: "memory"); }
__device__ __forceinline__ void wgmma_commit() { asm volatile("wgmma.commit_group.sync.aligned;" ::: "memory"); }
template <int N> __device__ __forceinline__ void wgmma_wait() { asm volatile("wgmma.wait_group.sync.aligned %0;" ::"n"(N) : "memory"); }
__device__ __forceinline__ uint32_t pack_bf16(float lo, float hi) {
    uint32_t r; asm("cvt.rn.bf16x2.f32 %0, %1, %2;" : "=r"(r) : "f"(hi), "f"(lo)); return r;
}
__device__ __forceinline__ void stmatrix_x4(uint32_t addr, uint32_t a, uint32_t b, uint32_t c, uint32_t d) {
    asm volatile("stmatrix.sync.aligned.m8n8.x4.shared.b16 [%0], {%1, %2, %3, %4};" ::"r"(addr), "r"(a), "r"(b), "r"(c), "r"(d) : "memory");
}
__device__ __forceinline__ uint4 ldmatrix_x4(uint32_t a) {
    uint4 v; asm volatile("ldmatrix.sync.aligned.m8n8.x4.shared.b16 {%0, %1, %2, %3}, [%4];" : "=r"(v.x), "=r"(v.y), "=r"(v.z), "=r"(v.w) : "r"(a) : "memory"); return v;
}
__device__ __forceinline__ uint4 lds128(uint32_t a) {
    uint4 v; asm volatile("ld.shared.v4.b32 {%0, %1, %2, %3}, [%4];" : "=r"(v.x), "=r"(v.y), "=r"(v.z), "=r"(v.w) : "r"(a) : "memory"); return v;
}
__device__ __forceinline__ void sts128(uint32_t a, uint4 v) {
    asm volatile("st.shared.v4.b32 [%0], {%1, %2, %3, %4};" ::"r"(a), "r"(v.x), "r"(v.y), "r"(v.z), "r"(v.w) : "memory");
}
__device__ __forceinline__ uint4 ldg128(const void* p) {
    uint4 v; asm volatile("ld.global.nc.v4.b32 {%0, %1, %2, %3}, [%4];" : "=r"(v.x), "=r"(v.y), "=r"(v.z), "=r"(v.w) : "l"(p) : "memory"); return v;
}
__device__ __forceinline__ unsigned clk() { unsigned c; asm volatile("mov.u32 %0, %%clock;" : "=r"(c) :: "memory"); return c; }
__device__ __forceinline__ uint32_t mul_bf16x2(uint32_t a, uint32_t b) { uint32_t r; asm("mul.rn.bf16x2 %0, %1, %2;" : "=r"(r) : "r"(a), "r"(b)); return r; }
struct Lut { uint32_t lo[4], hi[4]; };
__device__ __forceinline__ uint32_t prmt(uint32_t a, uint32_t b, uint32_t s) { uint32_t r; asm("prmt.b32 %0, %1, %2, %3;" : "=r"(r) : "r"(a), "r"(b), "r"(s)); return r; }
__device__ __forceinline__ uint32_t pack4(const uint4& q) {
    uint32_t ab, cd, p;
    asm volatile("mad.lo.u32 %0, %1, 16, %2;" : "=r"(ab) : "r"(q.y), "r"(q.x));
    asm volatile("mad.lo.u32 %0, %1, 16, %2;" : "=r"(cd) : "r"(q.w), "r"(q.z));
    asm volatile("mad.lo.u32 %0, %1, 256, %2;" : "=r"(p) : "r"(cd), "r"(ab));
    return p;
}
__device__ __forceinline__ void lookup4(uint32_t p, const Lut& t, uint32_t& w01, uint32_t& w23) {
    const uint32_t t8 = p & 0x8888u, s7 = p & 0x7777u;
    const uint32_t sel = (t8 >> 1) + 0x3210u;
    const uint32_t lo = prmt(prmt(t.lo[0], t.lo[1], p), prmt(t.lo[2], t.lo[3], s7), sel);
    const uint32_t hi = prmt(prmt(t.hi[0], t.hi[1], p), prmt(t.hi[2], t.hi[3], s7), sel);
    w01 = prmt(lo, hi, 0x5140);
    w23 = prmt(lo, hi, 0x7362);
}
__device__ __forceinline__ uint4 dequant8(uint32_t p0, uint32_t p1, const uint4& sc, const Lut& t) {
    uint4 r;
    lookup4(p0, t, r.x, r.y);
    lookup4(p1, t, r.z, r.w);
    r.x = mul_bf16x2(r.x, sc.x); r.y = mul_bf16x2(r.y, sc.y); r.z = mul_bf16x2(r.z, sc.z); r.w = mul_bf16x2(r.w, sc.w);
    return r;
}
__device__ __forceinline__ void fence_async_smem() { asm volatile("fence.proxy.async.shared::cta;" ::: "memory"); }

template <int SCALE_D, int BHI, uint32_t AHI = 0x40000040u>
__device__ __forceinline__ void wgmma224(float (&d)[112], uint32_t descA, uint32_t descB) {
    asm volatile(
        "{\n.reg .pred p;\n.reg .b64 da, db;\nsetp.ne.b32 p, %114, 0;\n"
        "mov.b64 da, {%112, %116};\nmov.b64 db, {%113, %115};\n"
        "wgmma.mma_async.sync.aligned.m64n224k16.f32.bf16.bf16 "
        "{%0, %1, %2, %3, %4, %5, %6, %7, %8, %9, %10, %11, %12, %13, %14, %15, "
        "%16, %17, %18, %19, %20, %21, %22, %23, %24, %25, %26, %27, %28, %29, %30, %31, "
        "%32, %33, %34, %35, %36, %37, %38, %39, %40, %41, %42, %43, %44, %45, %46, %47, "
        "%48, %49, %50, %51, %52, %53, %54, %55, %56, %57, %58, %59, %60, %61, %62, %63, "
        "%64, %65, %66, %67, %68, %69, %70, %71, %72, %73, %74, %75, %76, %77, %78, %79, "
        "%80, %81, %82, %83, %84, %85, %86, %87, %88, %89, %90, %91, %92, %93, %94, %95, "
        "%96, %97, %98, %99, %100, %101, %102, %103, %104, %105, %106, %107, %108, %109, %110, %111}, "
        "da, db, p, 1, 1, 0, 1;\n}\n"
        : "+f"(d[0]), "+f"(d[1]), "+f"(d[2]), "+f"(d[3]), "+f"(d[4]), "+f"(d[5]), "+f"(d[6]), "+f"(d[7]),
          "+f"(d[8]), "+f"(d[9]), "+f"(d[10]), "+f"(d[11]), "+f"(d[12]), "+f"(d[13]), "+f"(d[14]), "+f"(d[15]),
          "+f"(d[16]), "+f"(d[17]), "+f"(d[18]), "+f"(d[19]), "+f"(d[20]), "+f"(d[21]), "+f"(d[22]), "+f"(d[23]),
          "+f"(d[24]), "+f"(d[25]), "+f"(d[26]), "+f"(d[27]), "+f"(d[28]), "+f"(d[29]), "+f"(d[30]), "+f"(d[31]),
          "+f"(d[32]), "+f"(d[33]), "+f"(d[34]), "+f"(d[35]), "+f"(d[36]), "+f"(d[37]), "+f"(d[38]), "+f"(d[39]),
          "+f"(d[40]), "+f"(d[41]), "+f"(d[42]), "+f"(d[43]), "+f"(d[44]), "+f"(d[45]), "+f"(d[46]), "+f"(d[47]),
          "+f"(d[48]), "+f"(d[49]), "+f"(d[50]), "+f"(d[51]), "+f"(d[52]), "+f"(d[53]), "+f"(d[54]), "+f"(d[55]),
          "+f"(d[56]), "+f"(d[57]), "+f"(d[58]), "+f"(d[59]), "+f"(d[60]), "+f"(d[61]), "+f"(d[62]), "+f"(d[63]),
          "+f"(d[64]), "+f"(d[65]), "+f"(d[66]), "+f"(d[67]), "+f"(d[68]), "+f"(d[69]), "+f"(d[70]), "+f"(d[71]),
          "+f"(d[72]), "+f"(d[73]), "+f"(d[74]), "+f"(d[75]), "+f"(d[76]), "+f"(d[77]), "+f"(d[78]), "+f"(d[79]),
          "+f"(d[80]), "+f"(d[81]), "+f"(d[82]), "+f"(d[83]), "+f"(d[84]), "+f"(d[85]), "+f"(d[86]), "+f"(d[87]),
          "+f"(d[88]), "+f"(d[89]), "+f"(d[90]), "+f"(d[91]), "+f"(d[92]), "+f"(d[93]), "+f"(d[94]), "+f"(d[95]),
          "+f"(d[96]), "+f"(d[97]), "+f"(d[98]), "+f"(d[99]), "+f"(d[100]), "+f"(d[101]), "+f"(d[102]), "+f"(d[103]),
          "+f"(d[104]), "+f"(d[105]), "+f"(d[106]), "+f"(d[107]), "+f"(d[108]), "+f"(d[109]), "+f"(d[110]), "+f"(d[111])
        : "r"(descA), "r"(descB), "n"(SCALE_D), "n"(BHI), "n"(AHI));
}

template <int SCALE_D, int BHI, uint32_t AHI = 0x40000040u>
__device__ __forceinline__ void wgmma128(float (&d)[64], uint32_t descA, uint32_t descB) {
    asm volatile(
        "{\n.reg .pred p;\n.reg .b64 da, db;\nsetp.ne.b32 p, %66, 0;\n"
        "mov.b64 da, {%64, %68};\nmov.b64 db, {%65, %67};\n"
        "wgmma.mma_async.sync.aligned.m64n128k16.f32.bf16.bf16 "
        "{%0, %1, %2, %3, %4, %5, %6, %7, %8, %9, %10, %11, %12, %13, %14, %15, "
        "%16, %17, %18, %19, %20, %21, %22, %23, %24, %25, %26, %27, %28, %29, %30, %31, "
        "%32, %33, %34, %35, %36, %37, %38, %39, %40, %41, %42, %43, %44, %45, %46, %47, "
        "%48, %49, %50, %51, %52, %53, %54, %55, %56, %57, %58, %59, %60, %61, %62, %63}, "
        "da, db, p, 1, 1, 0, 1;\n}\n"
        : "+f"(d[0]), "+f"(d[1]), "+f"(d[2]), "+f"(d[3]), "+f"(d[4]), "+f"(d[5]), "+f"(d[6]), "+f"(d[7]),
          "+f"(d[8]), "+f"(d[9]), "+f"(d[10]), "+f"(d[11]), "+f"(d[12]), "+f"(d[13]), "+f"(d[14]), "+f"(d[15]),
          "+f"(d[16]), "+f"(d[17]), "+f"(d[18]), "+f"(d[19]), "+f"(d[20]), "+f"(d[21]), "+f"(d[22]), "+f"(d[23]),
          "+f"(d[24]), "+f"(d[25]), "+f"(d[26]), "+f"(d[27]), "+f"(d[28]), "+f"(d[29]), "+f"(d[30]), "+f"(d[31]),
          "+f"(d[32]), "+f"(d[33]), "+f"(d[34]), "+f"(d[35]), "+f"(d[36]), "+f"(d[37]), "+f"(d[38]), "+f"(d[39]),
          "+f"(d[40]), "+f"(d[41]), "+f"(d[42]), "+f"(d[43]), "+f"(d[44]), "+f"(d[45]), "+f"(d[46]), "+f"(d[47]),
          "+f"(d[48]), "+f"(d[49]), "+f"(d[50]), "+f"(d[51]), "+f"(d[52]), "+f"(d[53]), "+f"(d[54]), "+f"(d[55]),
          "+f"(d[56]), "+f"(d[57]), "+f"(d[58]), "+f"(d[59]), "+f"(d[60]), "+f"(d[61]), "+f"(d[62]), "+f"(d[63])
        : "r"(descA), "r"(descB), "n"(SCALE_D), "n"(BHI), "n"(AHI));
}

template <int SCALE_D, int BHI, uint32_t AHI = 0x40000040u>
__device__ __forceinline__ void wgmma96(float (&d)[48], uint32_t descA, uint32_t descB) {
    asm volatile(
        "{\n.reg .pred p;\n.reg .b64 da, db;\nsetp.ne.b32 p, %50, 0;\n"
        "mov.b64 da, {%48, %52};\nmov.b64 db, {%49, %51};\n"
        "wgmma.mma_async.sync.aligned.m64n96k16.f32.bf16.bf16 "
        "{%0, %1, %2, %3, %4, %5, %6, %7, %8, %9, %10, %11, %12, %13, %14, %15, "
        "%16, %17, %18, %19, %20, %21, %22, %23, %24, %25, %26, %27, %28, %29, %30, %31, "
        "%32, %33, %34, %35, %36, %37, %38, %39, %40, %41, %42, %43, %44, %45, %46, %47}, "
        "da, db, p, 1, 1, 0, 1;\n}\n"
        : "+f"(d[0]), "+f"(d[1]), "+f"(d[2]), "+f"(d[3]), "+f"(d[4]), "+f"(d[5]), "+f"(d[6]), "+f"(d[7]),
          "+f"(d[8]), "+f"(d[9]), "+f"(d[10]), "+f"(d[11]), "+f"(d[12]), "+f"(d[13]), "+f"(d[14]), "+f"(d[15]),
          "+f"(d[16]), "+f"(d[17]), "+f"(d[18]), "+f"(d[19]), "+f"(d[20]), "+f"(d[21]), "+f"(d[22]), "+f"(d[23]),
          "+f"(d[24]), "+f"(d[25]), "+f"(d[26]), "+f"(d[27]), "+f"(d[28]), "+f"(d[29]), "+f"(d[30]), "+f"(d[31]),
          "+f"(d[32]), "+f"(d[33]), "+f"(d[34]), "+f"(d[35]), "+f"(d[36]), "+f"(d[37]), "+f"(d[38]), "+f"(d[39]),
          "+f"(d[40]), "+f"(d[41]), "+f"(d[42]), "+f"(d[43]), "+f"(d[44]), "+f"(d[45]), "+f"(d[46]), "+f"(d[47])
        : "r"(descA), "r"(descB), "n"(SCALE_D), "n"(BHI), "n"(AHI));
}

template <int BHI>
__device__ __forceinline__ void wgmma128r(float (&d)[64], const uint4& a, uint32_t descB) {
    asm volatile(
        "{\n.reg .pred p;\n.reg .b64 db;\nsetp.eq.b32 p, 0, 0;\n"
        "mov.b64 db, {%68, %69};\n"
        "wgmma.mma_async.sync.aligned.m64n128k16.f32.bf16.bf16 "
        "{%0, %1, %2, %3, %4, %5, %6, %7, %8, %9, %10, %11, %12, %13, %14, %15, "
        "%16, %17, %18, %19, %20, %21, %22, %23, %24, %25, %26, %27, %28, %29, %30, %31, "
        "%32, %33, %34, %35, %36, %37, %38, %39, %40, %41, %42, %43, %44, %45, %46, %47, "
        "%48, %49, %50, %51, %52, %53, %54, %55, %56, %57, %58, %59, %60, %61, %62, %63}, "
        "{%64, %65, %66, %67}, db, p, 1, 1, 1;\n}\n"
        : "+f"(d[0]), "+f"(d[1]), "+f"(d[2]), "+f"(d[3]), "+f"(d[4]), "+f"(d[5]), "+f"(d[6]), "+f"(d[7]),
          "+f"(d[8]), "+f"(d[9]), "+f"(d[10]), "+f"(d[11]), "+f"(d[12]), "+f"(d[13]), "+f"(d[14]), "+f"(d[15]),
          "+f"(d[16]), "+f"(d[17]), "+f"(d[18]), "+f"(d[19]), "+f"(d[20]), "+f"(d[21]), "+f"(d[22]), "+f"(d[23]),
          "+f"(d[24]), "+f"(d[25]), "+f"(d[26]), "+f"(d[27]), "+f"(d[28]), "+f"(d[29]), "+f"(d[30]), "+f"(d[31]),
          "+f"(d[32]), "+f"(d[33]), "+f"(d[34]), "+f"(d[35]), "+f"(d[36]), "+f"(d[37]), "+f"(d[38]), "+f"(d[39]),
          "+f"(d[40]), "+f"(d[41]), "+f"(d[42]), "+f"(d[43]), "+f"(d[44]), "+f"(d[45]), "+f"(d[46]), "+f"(d[47]),
          "+f"(d[48]), "+f"(d[49]), "+f"(d[50]), "+f"(d[51]), "+f"(d[52]), "+f"(d[53]), "+f"(d[54]), "+f"(d[55]),
          "+f"(d[56]), "+f"(d[57]), "+f"(d[58]), "+f"(d[59]), "+f"(d[60]), "+f"(d[61]), "+f"(d[62]), "+f"(d[63])
        : "r"(a.x), "r"(a.y), "r"(a.z), "r"(a.w), "r"(descB), "n"(BHI));
}

template <int BHI>
__device__ __forceinline__ void wgmma96r(float (&d)[48], const uint4& a, uint32_t descB) {
    asm volatile(
        "{\n.reg .pred p;\n.reg .b64 db;\nsetp.eq.b32 p, 0, 0;\n"
        "mov.b64 db, {%52, %53};\n"
        "wgmma.mma_async.sync.aligned.m64n96k16.f32.bf16.bf16 "
        "{%0, %1, %2, %3, %4, %5, %6, %7, %8, %9, %10, %11, %12, %13, %14, %15, "
        "%16, %17, %18, %19, %20, %21, %22, %23, %24, %25, %26, %27, %28, %29, %30, %31, "
        "%32, %33, %34, %35, %36, %37, %38, %39, %40, %41, %42, %43, %44, %45, %46, %47}, "
        "{%48, %49, %50, %51}, db, p, 1, 1, 1;\n}\n"
        : "+f"(d[0]), "+f"(d[1]), "+f"(d[2]), "+f"(d[3]), "+f"(d[4]), "+f"(d[5]), "+f"(d[6]), "+f"(d[7]),
          "+f"(d[8]), "+f"(d[9]), "+f"(d[10]), "+f"(d[11]), "+f"(d[12]), "+f"(d[13]), "+f"(d[14]), "+f"(d[15]),
          "+f"(d[16]), "+f"(d[17]), "+f"(d[18]), "+f"(d[19]), "+f"(d[20]), "+f"(d[21]), "+f"(d[22]), "+f"(d[23]),
          "+f"(d[24]), "+f"(d[25]), "+f"(d[26]), "+f"(d[27]), "+f"(d[28]), "+f"(d[29]), "+f"(d[30]), "+f"(d[31]),
          "+f"(d[32]), "+f"(d[33]), "+f"(d[34]), "+f"(d[35]), "+f"(d[36]), "+f"(d[37]), "+f"(d[38]), "+f"(d[39]),
          "+f"(d[40]), "+f"(d[41]), "+f"(d[42]), "+f"(d[43]), "+f"(d[44]), "+f"(d[45]), "+f"(d[46]), "+f"(d[47])
        : "r"(a.x), "r"(a.y), "r"(a.z), "r"(a.w), "r"(descB), "n"(BHI));
}

__device__ __forceinline__ uint32_t opq(uint32_t v) { asm volatile("" : "+r"(v)); return v; }
template <int I> struct IC { static constexpr int value = I; };
template <int B, int E, class F> __device__ __forceinline__ void static_for(F&& f) {
    if constexpr (B < E) { f(IC<B>{}); static_for<B + 1, E>(f); }
}

__device__ __forceinline__ void tma_store_2d(const CUtensorMap* tm, uint32_t src, int c0, int c1) {
    asm volatile("cp.async.bulk.tensor.2d.global.shared::cta.bulk_group [%0, {%2, %3}], [%1];" ::"l"(tm), "r"(src), "r"(c0), "r"(c1) : "memory");
}
__device__ __forceinline__ void bulk_store(void* dst, uint32_t src, uint32_t bytes) {
    asm volatile("cp.async.bulk.global.shared::cta.bulk_group [%0], [%1], %2;" ::"l"(dst), "r"(src), "r"(bytes) : "memory");
}
__device__ __forceinline__ void bulk_commit() { asm volatile("cp.async.bulk.commit_group;" ::: "memory"); }
template <int N> __device__ __forceinline__ void bulk_wait_read() { asm volatile("cp.async.bulk.wait_group.read %0;" ::"n"(N) : "memory"); }
__device__ __forceinline__ void bar_arrive(int id) { asm volatile("bar.arrive %0, 256;" ::"r"(id) : "memory"); }
__device__ __forceinline__ void bar_sync(int id) { asm volatile("bar.sync %0, 256;" ::"r"(id) : "memory"); }
template <int NC, int OFF, int N>
__device__ __forceinline__ void stage_cols(const float (&acc)[N], uint32_t stg) {
    int lane; asm volatile("mov.u32 %0, %%laneid;" : "=r"(lane));
    const int r = lane & 15;
    const uint32_t a0 = NC == 64 ? stg + r * 128 + (((lane >> 4) ^ (r & 7)) << 4) : stg + r * 64 + (((lane >> 4) ^ ((r >> 1) & 3)) << 4);
#pragma unroll
    for (int j = 0; j < NC / 16; j++) {
        const int i = OFF + 8 * j;
        stmatrix_x4(a0 ^ (j * 32), pack_bf16(acc[i], acc[i + 1]), pack_bf16(acc[i + 2], acc[i + 3]), pack_bf16(acc[i + 4], acc[i + 5]), pack_bf16(acc[i + 6], acc[i + 7]));
    }
}
__device__ __forceinline__ void send(uint32_t stg, const CUtensorMap* tmo, int col, int row) {
    fence_async_smem();
    __syncwarp();
    if (elect()) { tma_store_2d(tmo, stg, col, row); bulk_commit(); }
    __syncwarp();
}

__host__ __device__ constexpr int rslot(int u) { return (2 * u) % 3; }
__host__ __device__ constexpr int roff(int slot) { return slot < 2 ? slot * UNIT : RAW2_OFF - RAW_OFF; }
__host__ __device__ constexpr int rpar(int u) { return (u / 3 - (u % 3 == 0)) & 1; }
__host__ __device__ constexpr int sslot(int c) { return c < 3 ? c + 3 : c % 3; }
__host__ __device__ constexpr int vturn(int v) {
    return v < 20 ? v : v == 20 ? -21 : v == 21 ? -22 : v == 22 ? 21 : v == 23 ? -20 : v == 24 ? 20 : v < 29 ? v - 3 : v == 29 ? -24 : v == 30 ? -25 : 27;
}
__host__ __device__ constexpr int uoff(int v) { return vturn(v) < 0 ? RAW_OFF + roff(rslot(-vturn(v))) : W_OFF + (vturn(v) % NW) * UNIT; }
__host__ __device__ constexpr int ubar(int v) { return vturn(v) < 0 ? 96 + 8 * rslot(-vturn(v)) : 16 * (vturn(v) % NW); }
__host__ __device__ constexpr int upar(int v) { return vturn(v) < 0 ? rpar(-vturn(v)) : (vturn(v) / NW) & 1; }
__host__ __device__ constexpr int utime(int v) {
    return v < 22 ? v + 15 : v == 22 || v == 25 ? 38 : v < 25 ? 40 : v < 28 ? 42 : 44;
}
__host__ __device__ constexpr int sh_at(int g, int k) { return (g ? 4 * G2 : 4 * G1) - 3 + (((g ? 0x01458 : 0x01479) >> (16 - 4 * k)) & 15); }
__host__ __device__ constexpr bool shares_at(int s) { for (int k = 0; k < 5; k++) if (sh_at(0, k) == s || sh_at(1, k) == s) return true; return false; }
__host__ __device__ constexpr uint32_t bdesc(int s) { return (uint32_t)(((0x400 + uoff(s >> 1)) >> 4) | ((7168u >> 4) << 16)) + (s & 1) * 224; }

__global__ void __cluster_dims__(2, 1, 1) __launch_bounds__(256, 1)
nf4_gemm_kernel(const int* __restrict__ qw, const __nv_bfloat16* __restrict__ cb, const __nv_bfloat16* __restrict__ absmax,
                uint8_t* __restrict__ wimg, unsigned* __restrict__ gflag, uint8_t* __restrict__ out,
                const __grid_constant__ CUtensorMap tmx, const __grid_constant__ CUtensorMap tmq, const __grid_constant__ CUtensorMap tmo64,
                const __grid_constant__ CUtensorMap tmo32, const __grid_constant__ CUtensorMap tmqp, const __grid_constant__ CUtensorMap tmx16,
                const __grid_constant__ CUtensorMap tmx64, const __grid_constant__ CUtensorMap tmq1) {
    extern __shared__ __align__(1024) uint8_t smem[];
    const uint32_t sbase = smem_u32(smem);
    const uint32_t cl = blockIdx.y;
    const uint32_t tile = cl < 36 ? (cl < 4 ? cl * 16 + 15 : ((cl - 4) & 7) + ((cl - 4) & 24) * 2) : cl - 28 + (((cl - 36) * 37) >> 8) * 9;
    const int rank = blockIdx.x, nt = tile & 15, pair = tile >> 4;
    uint4 q[4], c0, c1;
    uint2 sf;
    if (threadIdx.x < 224) {
        const uint32_t t = threadIdx.x;
        const int* p = qw + (uint32_t)((t & 3) * (N_ - 1) + t + blockIdx.x * (8 * N_) + nt * BN);
        q[0] = ldg128(p); q[1] = ldg128(p + 4 * N_);
        q[2] = ldg128(p + 16 * N_); q[3] = ldg128(p + 20 * N_);
        const void* ps = absmax + (uint32_t)(opq(t & ~3u) + nt * BN);
        asm volatile("ld.global.nc.v2.b32 {%0, %1}, [%2];" : "=r"(sf.x), "=r"(sf.y) : "l"(ps) : "memory");
        c0 = ldg128(cb); c1 = ldg128(cb + 8);
    }
    const unsigned tstart = clk();
    const int mt = pair * 2 + rank;
    const int lane = threadIdx.x & 31;
    const int warp = __reduce_max_sync(~0u, threadIdx.x >> 5);
    const int wg = warp >> 2;
    const uint32_t bars = sbase + BAR_OFF;
    const uint32_t full = bars, rawfull = bars + 96, written = bars + 120, xbar = bars + 144, gbar = bars + 160 + wg * 16;
    const uint32_t rawh = bars + 192 - 8, ebar = bars + 216, ones = bars + 256;
    const uint32_t wbase = sbase + W_OFF;
    __syncwarp();

    auto insert = [](uint64_t m, int pos, int v) { const uint64_t low = (1ull << (4 * pos)) - 1; return (m & low) | ((m & ~low) << 4) | ((uint64_t)v << (4 * pos)); };
    const uint64_t others = (0xedcfedu >> (4 * pair)) & 0xfff;
    const uint64_t cmap = insert(insert(0x76543210ull, G1, 8 + pair), G2, 12 + pair) | ((others - 0x444) << 40) | (others << 52);
    auto chunk = [&](int i) { return (int)(cmap >> (4 * i)) & 15; };
    unsigned* flag = gflag + nt * 32;
    uint8_t* wpan = wimg + nt * (16 * UNIT);
    auto load_x = [&](int i, int slot, uint32_t bar) {
        tma_load_2d(sbase + slot * 32768, &tmx, chunk(i) * 64, mt * BM, bar);
        tma_load_2d(sbase + slot * 32768 + 16384, &tmx, chunk(i) * 64, mt * BM + 128, bar);
    };
    auto load_l = [&](int i, int slot, int g, uint32_t bar) {
        tma_load_2d(sbase + slot * 32768 + g * 16384, &tmx64, chunk(i) * 64, mt * BM + g * 128, bar);
        tma_load_2d(sbase + slot * 32768 + g * 16384 + 8192, &tmx64, chunk(i + 1) * 64, mt * BM + g * 128, bar);
    };
    auto snap = [&](int ss, uint32_t bar) { bulk_load(sbase + SC_OFF + ss * SC_STRIDE + 448, flag, 16, bar); };
    auto load_sc = [&](int i, int ss, uint32_t bar) {
        bulk_load(sbase + SC_OFF + ss * SC_STRIDE, absmax + chunk(i) * N_ + nt * BN, 448, bar);
    };
    auto load_raw = [&](int u, int slot) {
        mbar_expect_tx(rawfull + 8 * slot, UNIT);
        tma_load_5d(sbase + RAW_OFF + roff(slot), &tmq, 0, 0, nt * 7, rank, 4 * chunk(u >> 1) + 2 * (u & 1), rawfull + 8 * slot);
    };
    auto load_half = [&](int b, uint32_t more) {
        const uint32_t bar = (b & 1) ? rawfull + 8 * rslot(b >> 1) : rawh + 8 * (b >> 1);
        mbar_expect_tx(bar, 7168 + more);
        tma_load_5d(sbase + RAW_OFF + roff(rslot(b >> 1)) + (b & 1) * 7168, &tmq1, 0, 0, nt * 7, rank, b, bar);
    };
    auto load_w = [&](int v) {
        mbar_expect_tx(bars + ubar(v), UNIT + (!(v & 1) && v <= 24 ? 32768 : 0) + (v == 21 ? 16 : 0));
        bulk_load(sbase + uoff(v), wpan + (2 * (chunk(v >> 1) - 8) + (v & 1)) * UNIT, UNIT, bars + ubar(v));
    };
    auto prefetch_q = [&](int c) { if (c + PFQ < 8) tma_prefetch_2d(&tmqp, nt * BN, (c + PFQ) * 64 + pair * 16 + rank * 8); };
    auto prefetch_g = [&](int c) {
        if (c < 6) {
            const int k = c, k0 = k + (k >= 3);
            tma_prefetch_2d(&tmqp, nt * BN, (8 + (k0 & 4) + pair) * 64 + (k0 & 3) * 16 + rank * 8);
            if (k == 1 || k == 4) tma_prefetch_2d(&tmqp, nt * BN, (8 + (k0 & 4) + pair) * 64 + 48 + rank * 8);
        }
    };
    auto prefetch_x = [&](int i) { tma_prefetch_2d(&tmx16, chunk(i) * 64, mt * BM + nt * 16); };
    if (warp == 7) {
        if (elect()) {
            mbar_init(xbar, 1); mbar_init(rawh + 8, 1); mbar_init(rawfull + 8 * rslot(1), 1); mbar_init(xbar + 8, 1);
            fence_async_smem();
            load_half(2, 448);
            bulk_load(sbase + SC_OFF + sslot(0) * SC_STRIDE, absmax + nt * BN, 448, rawh + 8);
            load_half(3, 0);
            mbar_expect_tx(xbar, 16384);
            tma_load_2d(sbase, &tmx, 0, mt * BM, xbar);
            mbar_expect_tx(xbar + 8, 16384);
            tma_load_2d(sbase + 16384, &tmx, 0, mt * BM + 128, xbar + 8);
            mbar_init(rawfull + 8 * rslot(2), 1); mbar_init(rawfull + 8 * rslot(3), 1); mbar_init(rawh + 16, 1); mbar_init(rawh + 24, 1);
            mbar_init(ebar, 7); mbar_init(ebar + 8, 7);
            sts128(ones, make_uint4(1, 0, 0, 0)); sts128(ones + 16, make_uint4(0, 1, 0, 0));
#pragma unroll
            for (int s = 0; s < 12; s++) { mbar_init(full + 8 * s, 1); if (s < 4) mbar_arrive(full + 8 * s); }
#pragma unroll
            for (int s = 0; s < 3; s++) mbar_init(written + 8 * s, 7);
#pragma unroll
            for (int s = 0; s < 4; s++) mbar_init(bars + 160 + 8 * s, 4);
            asm volatile("fence.mbarrier_init.release.cluster;" ::: "memory");
            fence_async_smem();
            if ((sbase & 0xffffff) != 0x400) __trap();
        }
        __syncwarp();
        cluster_arrive();
        if (elect()) {
            asm volatile("prefetch.tensormap [%0];" ::"l"(&tmq) : "memory");
            asm volatile("prefetch.tensormap [%0];" ::"l"(&tmqp) : "memory");
            asm volatile("prefetch.tensormap [%0];" ::"l"(&tmx16) : "memory");
            asm volatile("prefetch.tensormap [%0];" ::"l"(&tmx64) : "memory");
            while (clk() - tstart < T2) { }
            load_half(4, 2 * 448 + 16);
            load_sc(1, sslot(1), rawh + 16); load_sc(2, sslot(2), rawh + 16); snap(sslot(1), rawh + 16);
            load_half(5, 0);
            while (clk() - tstart < T2B) { }
            tma_load_2d(sbase + 32768, &tmx, 64, mt * BM, full + 32);
            load_half(6, 0); load_half(7, 0);
            tma_load_2d(sbase + 32768 + 16384, &tmx, 64, mt * BM + 128, full + 32);
            load_sc(3, sslot(3), full + 48);
            while (clk() - tstart < T3) { }
            prefetch_q(-2); prefetch_q(-1);
            asm volatile("cp.async.bulk.prefetch.L2.global [%0], 448;" ::"l"(absmax + (2 * mt) * N_ + nt * BN) : "memory");
            asm volatile("cp.async.bulk.prefetch.L2.global [%0], 448;" ::"l"(absmax + (2 * mt + 1) * N_ + nt * BN) : "memory");
        }
        __syncwarp();
        cluster_wait();
    } else {
        cluster_arrive();
    }
    const uint32_t rsrc = __shfl_sync(~0u, sbase + RAW_OFF + warp * 1024 + (lane & 7) * 128 + ((((lane >> 3) * 2) ^ (lane & 7)) << 4), lane);
    const uint32_t ssrc = sbase + SC_OFF + warp * 64;
    const int wpos = (nt & 1) ? (0x73210546 >> (4 * warp)) & 7 : warp;
    const uint32_t wown = wbase + rank * 7168 + wpos * 512;
    const uint32_t wdst = __shfl_sync(~0u, wown + lane * 16, lane);
    auto get_sc = [&](int ss) { return lds128(((opq(wdst) >> 3) & 0x30) + ssrc + ss * SC_STRIDE); };
    const uint32_t whalf = wbase + rank * 7168;
    const uint32_t pwhalf = mapa(whalf, rank ^ 1), pbars = mapa(bars, rank ^ 1);
    Lut lut;
    uint4 sc;
    uint4 q0, q1;
    auto fetch = [&](int slot, int h) {
        q0 = lds128(rsrc + roff(slot) + h * 7168);
        q1 = lds128((opq(rsrc) ^ 16) + roff(slot) + h * 7168);
    };
    auto signal = [&](uint32_t bar) { __syncwarp(); if (elect()) mbar_arrive(bar); __syncwarp(); };
    auto convert = [&](int ws, int h, bool w1, uint32_t bar1, uint32_t par1, bool w2, uint32_t bar2, uint32_t par2, bool next, int rsn,
                       bool sig, uint32_t sbar, bool scales, int cs) {
        bool ok1 = true, ok2 = true;
        if (w2) ok2 = mbar_try(bar2, par2);
        if (w1) ok1 = mbar_try(bar1, par1);
        uint4 w = dequant8(pack4(q0), pack4(q1), sc, lut);
        asm volatile("" : "+r"(w.x), "+r"(w.y), "+r"(w.z), "+r"(w.w));
        if (w1 && w2) mbar_wait2(bar2, par2, bar1, par1, ok1 && ok2);
        else if (w2) mbar_wait1(bar2, par2, ok2);
        else if (w1) mbar_wait1(bar1, par1, ok1);
        if (next) fetch(rsn, h ^ 1);
        sts128(wdst + ws * UNIT + h * 3584, w);
        if (sig) signal(sbar);
        if (scales) sc = get_sc(cs);
    };
    auto hand_over = [&](uint32_t sbar, uint32_t par, int ws, int h, uint32_t more, bool raw, int un, int rs, auto extra) {
        mbar_wait(sbar, par);
        fence_async_smem();
        if (elect()) {
            if (raw) load_raw(un, rs);
            copy_to_peer(pwhalf + ws * UNIT + h * 3584, whalf + ws * UNIT + h * 3584, 3584, pbars + 8 * (2 * ws + h));
            mbar_expect_tx(full + 8 * (2 * ws + h), 3584 + more);
            extra();
        }
        __syncwarp();
    };
    auto share = [&](int g, uint32_t o, uint32_t n) {
        bulk_store(wpan + 2 * (chunk(g) - 8) * UNIT + rank * 7168 + o, whalf + 2 * (g % 3) * UNIT + o, n);
        bulk_commit();
    };
    auto publish = [&](int k) {
        asm volatile("cp.async.bulk.wait_group 0;" ::: "memory");
        asm volatile("cp.reduce.async.bulk.global.shared::cta.bulk_group.add.u32 [%0], [%1], 16;" ::"l"(flag), "r"(ones + 16 * k) : "memory");
    };
    auto check = [&](int k, int ss) {
        unsigned f0, f1;
        asm volatile("ld.shared.u32 %0, [%1];" : "=r"(f0) : "r"(sbase + SC_OFF + sslot(1) * SC_STRIDE + 448 + 4 * k) : "memory");
        asm volatile("ld.shared.u32 %0, [%1];" : "=r"(f1) : "r"(sbase + SC_OFF + ss * SC_STRIDE + 448 + 4 * k) : "memory");
        asm volatile("{\n.reg .pred p;\n.reg .u32 n, d;\nmov.u32 n, 0;\nLAB_POLL:\nsub.u32 d, %0, %1;\nsetp.ge.u32 p, d, 8;\n@p bra.uni LAB_DONE;\n"
                     "ld.relaxed.gpu.global.u32 %0, [%2];\nadd.u32 n, n, 1;\nsetp.lt.u32 p, n, 0x10000;\n@p bra.uni LAB_POLL;\nLAB_DONE:\n}\n"
                     : "+r"(f1) : "r"(f0 & ~7u), "l"(flag + k) : "memory");
    };
    auto shares = [&](auto S) {
        constexpr int s = S.value;
        static_for<0, 4>([&](auto K) {
            constexpr int k = K.value;
            if constexpr (sh_at(0, k) == s) { share(G1, (k >> 1) * UNIT + (k & 1) * 3584, 3584); if (k == 3) bulk_wait_read<1>(); }
            if constexpr (sh_at(1, k) == s) share(G2, (k >> 1) * UNIT + (k & 1) * 3584, 3584);
        });
        if (s == sh_at(0, 4)) publish(0);
        if (s == sh_at(1, 4)) publish(1);
    };
    auto sig_bar = [&](int b) { return written + 8 * (b % 3); };
    auto sig_par = [](int b) { return (b / 3 - 1) & 1; };
    auto see = [&](int s) { if (s < 2 * NU) mbar_wait(full + 8 * (s % 12), (s / 12) & 1); else mbar_wait(bars + ubar(s >> 1), upar(s >> 1)); };
    auto block = [&](int b, int sn) {
        const int u = b >> 1, h = b & 1;
        const bool next = b + 1 < 2 * NU;
        convert(u % NW, h, sn == 2 || sn >= 4, sn == 2 ? ebar + 8 : full + 8 * (sn % 12), (sn / 12) & 1,
                next && (h || b < 8), b == 5 ? rawh + 24 : rawfull + 8 * rslot((b + 1) >> 1), b == 5 ? 0 : rpar((b + 1) >> 1),
                next, rslot((b + 1) >> 1), true, sig_bar(b), (b & 3) == 3 && next, sslot((b + 1) >> 2));
    };
    auto hand = [&](int b, auto extra) {
        const int u = b >> 1;
        hand_over(sig_bar(b), sig_par(b), u % NW, b & 1, (b & 3) == 0 ? 32768 : (b & 3) == 2 && b < 36 ? 448 : b == 35 ? 16 : 0, (b & 1) && u + NR < NU, u + NR, rslot(u), extra);
    };
    auto pass_on = [&](int u) {
        fence_async_smem();
        __syncwarp();
        if (elect()) {
            const uint32_t o = wpos * 512 + u * UNIT;
            copy_to_peer(pwhalf + o, whalf + o, 512, pbars + 216 + 8 * u);
            copy_to_peer(pwhalf + o + 3584, whalf + o + 3584, 512, pbars + 216 + 8 * u);
            if (u == 1) mbar_arrive(sig_bar(3));
            mbar_expect_tx(ebar + 8 * u, 1024);
        }
        __syncwarp();
    };
    bool ok0 = false;
    if (warp < 7) {
        lut.lo[0] = __byte_perm(c0.x, c0.y, 0x6420); lut.hi[0] = __byte_perm(c0.x, c0.y, 0x7531);
        lut.lo[1] = __byte_perm(c0.z, c0.w, 0x6420); lut.hi[1] = __byte_perm(c0.z, c0.w, 0x7531);
        lut.lo[2] = __byte_perm(c1.x, c1.y, 0x6420); lut.hi[2] = __byte_perm(c1.x, c1.y, 0x7531);
        lut.lo[3] = __byte_perm(c1.z, c1.w, 0x6420); lut.hi[3] = __byte_perm(c1.z, c1.w, 0x7531);
        const uint32_t d = wown + (lane >> 3) * 128 + (lane & 3) * 16 + (lane & 4) * 2;
#pragma unroll
        for (int j = 0; j < 4; j++) {
            uint32_t a, b;
            lookup4(pack4(q[j]), lut, a, b);
            asm volatile("st.shared.v2.b32 [%0], {%1, %2};" ::"r"(d + (j >> 1) * 3584 + (j & 1) * 64), "r"(mul_bf16x2(a, sf.x)), "r"(mul_bf16x2(b, sf.y)) : "memory");
        }
        cluster_wait();
        pass_on(0);
        mbar_wait(rawh + 8, 0);
        const uint4 a0 = lds128(rsrc + roff(rslot(1))), a1 = lds128((rsrc ^ 16) + roff(rslot(1))), s0 = get_sc(sslot(0));
        mbar_wait(rawfull + 8 * rslot(1), 0);
        const uint4 a2 = lds128(rsrc + roff(rslot(1)) + 7168), a3 = lds128((rsrc ^ 16) + roff(rslot(1)) + 7168);
        sts128(wdst + UNIT, dequant8(pack4(a0), pack4(a1), s0, lut));
        sts128(wdst + UNIT + 3584, dequant8(pack4(a2), pack4(a3), s0, lut));
        ok0 = mbar_try(xbar + 8 * wg, 0) & mbar_try(ebar, 0);
        pass_on(1);
    }
    mbar_wait2(xbar + 8 * wg, 0, ebar, 0, ok0);

    float acc0[112], acc1[112];
    const uint32_t descA = ((0x400 + wg * 16384) >> 4) | (1u << 16);
    auto mma = [&](int s) {
        const uint32_t da = opq(descA) + ((s >> 2) % 3) * (32768 >> 4) + (s & 3) * 2;
        wgmma_fence();
        wgmma224<1, 8>(acc0, da, bdesc(s)); wgmma224<1, 8>(acc1, da + 512, bdesc(s));
        wgmma_commit();
        wgmma_wait<2>();
    };
    wgmma_fence();
    wgmma224<0, 8>(acc0, descA, bdesc(0)); wgmma224<0, 8>(acc1, descA + 512, bdesc(0));
    wgmma_commit();
    mma(1);
    if (warp < 7) {
        mbar_wait(rawh + 16, 0); fetch(rslot(2), 0); sc = get_sc(sslot(1));
        block(4, 2);
    } else {
        mbar_wait(sig_bar(3), sig_par(3));
        if (elect()) { load_raw(4, rslot(4)); load_x(2, 2, full + 64); prefetch_q(0); prefetch_x(3); prefetch_g(0); }
        __syncwarp();
        mbar_wait(ebar + 8, 0);
    }
    static_for<2, 8>([&](auto S) {
        constexpr int s = S.value;
        mma(s);
        if (warp < 7) { if (s <= 3) block(s + 3, s < 3 ? s + 1 : -1); if (s >= 3) block(s + 4, s + 1); }
        else {
            if (s <= 3) hand(s + 2, [] {});
            if (s >= 3) hand(s + 3, [&] {
                if (s == 4) prefetch_q(1);
                if (s == 5) { load_sc(4, sslot(4), full + 80); prefetch_g(1); }
                if (s == 6) prefetch_x(4);
                if (s == 7) load_x(3, 0, full);
            });
            if (s >= 3) see(s + 1);
        }
    });
    {
        uint32_t ph = 0;
#pragma unroll 1
        for (int cb = 2; cb < 8; cb += 3)
          static_for<2, 5>([&](auto I) {
            constexpr int cc = I.value;
            constexpr int j0 = cc % 3, j1 = (cc + 1) % 3, j2 = (cc + 2) % 3;
            const int c = cb + cc - 2;
            auto sh = [&](auto KS) {
                static_for<0, 2>([&](auto IT) {
                    constexpr int s = 4 * (cc + 3 * IT.value) + KS.value;
                    if constexpr (shares_at(s)) { if (cb == 2 + 3 * IT.value) shares(IC<s>{}); }
                });
            };
            mma(4 * j0);
            if (warp < 7) convert(2 * j1, 0, true, full + 32 * j0 + 8, ph, false, 0, 0, true, j1, true, sig_bar(4 * cc + 4), false, 0);
            else {
                const bool ok = mbar_try(full + 32 * j0 + 8, ph);
                hand_over(sig_bar(4 * cc + 3), sig_par(4 * cc + 3), 2 * j0 + 1, 1, 0, true, 2 * c + 4, j2, [&] { prefetch_q(c); if (cc == 3 && c == 6) prefetch_x(12); sh(IC<0>{}); });
                mbar_wait1(full + 32 * j0 + 8, ph, ok);
            }
            mma(4 * j0 + 1);
            if (warp < 7) convert(2 * j1, 1, true, full + 32 * j0 + 16, ph, true, rawfull + 8 * j0, rpar(2 * cc + 3), true, j0, true, sig_bar(4 * cc + 5), false, 0);
            else {
                const bool ok = mbar_try(full + 32 * j0 + 16, ph);
                hand_over(sig_bar(4 * cc + 4), sig_par(4 * cc + 4), 2 * j1, 0, 32768, false, 0, 0, [&] { load_sc(c + 3, j0, full + 32 * j1 + 16); prefetch_g(c); sh(IC<1>{}); });
                mbar_wait1(full + 32 * j0 + 16, ph, ok);
            }
            mma(4 * j0 + 2);
            if (warp < 7) convert(2 * j1 + 1, 0, true, full + 32 * j0 + 24, ph, false, 0, 0, true, j0, true, sig_bar(4 * cc + 6), false, 0);
            else {
                const bool ok = mbar_try(full + 32 * j0 + 24, ph);
                hand_over(sig_bar(4 * cc + 5), sig_par(4 * cc + 5), 2 * j1, 1, 0, true, 2 * c + 5, j1, [&] { prefetch_x(c + PFX); sh(IC<2>{}); });
                mbar_wait1(full + 32 * j0 + 24, ph, ok);
            }
            if (j1 == 0) asm volatile("xor.b32 %0, %0, 1;" : "+r"(ph));
            mma(4 * j0 + 3);
            if (warp < 7) convert(2 * j1 + 1, 1, true, full + 32 * j1, ph, true, rawfull + 8 * j2, rpar(2 * cc + 4), true, j2, true, sig_bar(4 * cc + 7), true, j2);
            else {
                const bool ok = mbar_try(full + 32 * j1, ph);
                hand_over(sig_bar(4 * cc + 6), sig_par(4 * cc + 6), 2 * j1 + 1, 0, 448, false, 0, 0, [&] { load_x(c + 2, j2, full + 32 * j2); sh(IC<3>{}); });
                mbar_wait1(full + 32 * j1, ph, ok);
            }
          });
    }
    uint4 fa[10];
    auto get_frag = [&](int f, uint32_t rows, int j0, int j1) {
        int ln; asm volatile("mov.u32 %0, %%laneid;" : "=r"(ln));
        const uint32_t a = rows + (ln & 15) * 128 + (((ln >> 4) ^ (ln & 7)) << 4);
#pragma unroll
        for (int j = j0; j < j1; j++) fa[f + j] = ldmatrix_x4(a ^ (j * 32));
    };
    static_for<32, 46>([&](auto S) {
        constexpr int s = S.value;
        constexpr int vb = 40 + (s - 37) / 2;
        mma(s);
        if (s == 39) cluster_arrive();
        if (s == 41) cluster_wait();
        if (s == 36) mbar_wait(rawh + 8, 1);
        if (s >= 36 && s < 40) get_frag(2, sbase + uoff(24) + wg * (uoff(23) - uoff(24)) + (warp & 3) * 2048, s - 36, s - 35);
        if (warp < 7) {
            if (s < 36) block(s + 4, s + 1);
            else {
                if (s & 1) signal(sig_bar(vb));
                if (s < 39 || (s & 1)) see(s + 1);
            }
        } else {
            auto loads = [&] {
                static_for<NU, 30>([&](auto V) { if constexpr (utime(V.value) == s) load_w(V.value); });
                if (s == 33) prefetch_x(11);
                if (s == 32) {
                    mbar_expect_tx(rawh + 8, 16384);
                    tma_load_2d(sbase + uoff(24), &tmx64, chunk(12) * 64, mt * BM + 64, rawh + 8);
                    tma_load_2d(sbase + uoff(23), &tmx64, chunk(12) * 64, mt * BM + 192, rawh + 8);
                }
                if (s == 37) prefetch_x(13);
                if (s == 39) snap(1, bars + ubar(21));
                if (s == 41) { prefetch_x(14); prefetch_x(15); }
                if (s == 43) { load_l(12, 0, 0, bars + ubar(24)); load_l(12, 0, 1, bars + ubar(24)); }
                if (s == 34) load_x(10, 1, bars + ubar(20));
                if (s == 39) load_x(11, 2, bars + ubar(22));
                if (s == 44) {
                    asm volatile("prefetch.tensormap [%0];" ::"l"(&tmo64) : "memory");
                    asm volatile("prefetch.tensormap [%0];" ::"l"(&tmo32) : "memory");
                }
                if (s == 45) { mbar_expect_tx(xbar, 16384); load_l(14, 1, 0, xbar); }
                if (s == 45) load_w(30);
                shares(S);
            };
            if (s == 32) { if (elect()) snap(0, full + 8 * (35 % 12)); __syncwarp(); }
            if (s == 35) check(0, 0);
            if (s == 42) check(1, 1);
            if (s <= 36) hand(s + 3, loads);
            else {
                if (!(s & 1)) mbar_wait(sig_bar(40 + (s - 38) / 2), sig_par(40 + (s - 38) / 2));
                if (s == 45) mbar_wait(sig_bar(vb), sig_par(vb));
                if (elect()) loads();
                __syncwarp();
            }
            if (s < 39 || (s & 1)) see(s + 1);
        }
    });
    const uint32_t slice0 = sbase + wg * 16384 + (warp & 3) * 2048;
    auto slc = [&](int p) { return slice0 + (p >> 1) * 32768 + (p & 1) * 8192; };
    get_frag(-2, slc(5), 2, 4);
    if (wg == 1) bar_sync(8);
    wgmma_fence();
    wgmma224<1, 8>(acc0, descA + 4096 + 4, bdesc(46)); wgmma224<1, 8>(acc0, descA + 4096 + 6, bdesc(47));
    wgmma_commit();
    see(48);
    wgmma_fence();
    wgmma224<1, 8>(acc0, descA, bdesc(48)); wgmma224<1, 8>(acc0, descA + 2, bdesc(49));
    wgmma_commit();
    wgmma_wait<2>();
    if (wg == 0) bar_arrive(8);
    else if (warp == 7) {
        if (elect()) { load_w(31); mbar_expect_tx(xbar + 8, 16384); load_l(14, 1, 1, xbar + 8); }
        __syncwarp();
    }
    const int row0 = mt * BM + wg * 128 + (warp & 3) * 16, odd = nt & 1;
    const int colL = nt * BN + odd * 96, colA = nt * BN + (odd ? 32 : 128), colB = nt * BN + (odd ? 0 : 192);
    auto load_s = [&](int i, int p, uint32_t bar) { tma_load_2d(slc(p), &tmx16, chunk(i) * 64, row0 + 64, bar); };
    const uint32_t tA = opq(descA);
    if (elect()) { mbar_expect_tx(gbar, 2048); load_s(13, 5, gbar); }
    __syncwarp();
    wgmma_wait<0>();
    float lo0[64], hi0[48], lo1[64], hi1[48];
#pragma unroll
    for (int i = 0; i < 64; i++) { asm volatile("mov.b32 %0, %1;" : "=f"(lo0[i]) : "f"(acc0[i])); asm volatile("mov.b32 %0, %1;" : "=f"(lo1[i]) : "f"(acc1[i])); }
#pragma unroll
    for (int i = 0; i < 48; i++) { asm volatile("mov.b32 %0, %1;" : "=f"(hi0[i]) : "f"(acc0[64 + i])); asm volatile("mov.b32 %0, %1;" : "=f"(hi1[i]) : "f"(acc1[64 + i])); }
    auto tdesc = [&](int p, int s) { return tA + (p >> 1) * (32768 >> 4) + (p & 1) * 512 + (s & 3) * 2; };
    auto ldesc = [&](int s) { return tdesc((s >> 2) - 12, s); };
    auto gdesc = [&](int s) { return tdesc(s < 56 ? 5 : (s >> 2) - 14, s); };
    auto mma1 = [&](auto S) { wgmma128<1, 8>(lo0, ldesc(S.value), bdesc(S.value)); };
    auto mma2 = [&](auto S) { constexpr int s = S.value; if constexpr (s < 52) wgmma128r<8>(lo1, fa[s - 46], bdesc(s)); else wgmma128<1, 8>(lo1, gdesc(s), bdesc(s)); };
    auto mma3 = [&](auto S) { constexpr int s = S.value; if constexpr (s < 56) wgmma96r<8>(hi1, fa[s - 46], bdesc(s) + 128); else wgmma96<1, 8>(hi1, gdesc(s), bdesc(s) + 128); };
    if (wg == 1) { mbar_wait(xbar + 8, 1); bar_sync(1); }
    static_for<25, 32>([&](auto V) {
        constexpr int v = V.value;
        if (v == 26) mbar_wait2(bars + ubar(26), upar(26), bars + ubar(27), upar(27), wg);
        else if (v == 28) mbar_wait2(bars + ubar(28), upar(28), xbar, 1, wg);
        else if (v != 27) mbar_wait1(bars + ubar(v), upar(v), wg);
        wgmma_fence();
        wgmma96<1, 8>(hi0, ldesc(2 * v), bdesc(2 * v) + 128);
        wgmma96<1, 8>(hi0, ldesc(2 * v + 1), bdesc(2 * v + 1) + 128);
    });
    wgmma_commit();
    bar_arrive(1 + wg);
    wgmma_wait<0>();
    stage_cols<64, 0>(hi0, slc(4)); send(slc(4), &tmo64, colA, row0);
    bar_sync(2 + wg);
    wgmma_fence();
    static_for<50, 64>(mma1);
    wgmma_commit();
    bar_arrive(3 + wg);
    if (elect()) bulk_wait_read<0>();
    __syncwarp();
    stage_cols<32, 32>(hi0, slc(4));
    {
        const uint32_t zero = opq(gridDim.x - 2);
#pragma unroll
        for (int j = 0; j < 6; j++) { fa[j].x ^= zero; fa[j].y ^= zero; fa[j].z ^= zero; fa[j].w ^= zero; asm volatile("" : "+r"(fa[j].x), "+r"(fa[j].y), "+r"(fa[j].z), "+r"(fa[j].w)); }
    }
    mbar_wait(gbar, 0);
    send(slc(4), &tmo32, colB, row0);
    wgmma_wait<0>();
    stage_cols<64, 0>(lo0, slc(2));
    if (elect()) { mbar_expect_tx(gbar + 8, 4096); load_s(14, 0, gbar + 8); load_s(15, 1, gbar + 8); }
    __syncwarp();
    send(slc(2), &tmo64, colL, row0);
    bar_sync(4 + wg);
    wgmma_fence();
    static_for<46, 53>(mma2);
    wgmma_commit();
    const bool okg2 = mbar_try(gbar + 8, 0);
    stage_cols<64, 32>(lo0, slc(3));
    wgmma_fence();
    static_for<53, 56>(mma2);
    mbar_wait1(gbar + 8, 0, okg2);
    wgmma_fence();
    static_for<56, 59>(mma2);
    wgmma_commit();
    send(slc(3), &tmo64, colL + 64, row0);
    wgmma_fence();
    static_for<59, 64>(mma2);
    wgmma_commit();
    bar_arrive(5 + wg);
    get_frag(6, slc(5), 0, 4);
    if (elect()) bulk_wait_read<1>();
    __syncwarp();
    wgmma_wait<0>();
    stage_cols<64, 0>(lo1, slc(4)); send(slc(4), &tmo64, colL, row0 + 64);
    stage_cols<64, 32>(lo1, slc(2));
    if (wg == 0) send(slc(2), &tmo64, colL + 64, row0 + 64);
    bar_sync(6 + wg);
    wgmma_fence();
    static_for<46, 51>(mma3);
    wgmma_commit();
    if (wg == 1) send(slc(2), &tmo64, colL + 64, row0 + 64);
    wgmma_fence();
    static_for<51, 64>(mma3);
    wgmma_commit();
    if (wg == 0) bar_arrive(7);
    wgmma_wait<0>();
    if (wg == 1) {
        int ln; asm volatile("mov.u32 %0, %%laneid;" : "=r"(ln));
        uint8_t* oa = out + (size_t)(row0 + 64 + (ln >> 3)) * (N_ * 2) + colA * 2 + (ln & 7) * 16;
        uint8_t* ob = out + (size_t)(row0 + 64 + (ln >> 2)) * (N_ * 2) + colB * 2 + (ln & 3) * 16;
        const uint32_t sa = slc(5) + (ln >> 3) * 128 + (((ln & 7) ^ (ln >> 3)) << 4), sb = slc(0) + (ln >> 2) * 64 + (((ln ^ (ln >> 3)) & 3) << 4);
        stage_cols<64, 0>(hi1, slc(5));
        __syncwarp();
        uint4 v[6];
#pragma unroll
        for (int j = 0; j < 4; j++) v[j] = lds128((sa ^ ((j & 1) * 64)) + j * 512);
        stage_cols<32, 32>(hi1, slc(0));
#pragma unroll
        for (int j = 0; j < 4; j++) asm volatile("st.global.v4.b32 [%0], {%1, %2, %3, %4};" ::"l"(oa + j * (4 * N_ * 2)), "r"(v[j].x), "r"(v[j].y), "r"(v[j].z), "r"(v[j].w) : "memory");
        __syncwarp();
#pragma unroll
        for (int j = 4; j < 6; j++) v[j] = lds128(sb + (j - 4) * 512);
#pragma unroll
        for (int j = 4; j < 6; j++) asm volatile("st.global.v4.b32 [%0], {%1, %2, %3, %4};" ::"l"(ob + (j - 4) * (8 * N_ * 2)), "r"(v[j].x), "r"(v[j].y), "r"(v[j].z), "r"(v[j].w) : "memory");
    } else {
        stage_cols<64, 0>(hi1, slc(5)); send(slc(5), &tmo64, colA, row0 + 64);
        stage_cols<32, 32>(hi1, slc(0)); send(slc(0), &tmo32, colB, row0 + 64);
    }
    if (elect()) bulk_wait_read<0>();
    __syncwarp();
}

typedef CUresult (*EncodeFn)(CUtensorMap*, CUtensorMapDataType, cuuint32_t, void*, const cuuint64_t*, const cuuint64_t*,
                             const cuuint32_t*, const cuuint32_t*, CUtensorMapInterleave, CUtensorMapSwizzle,
                             CUtensorMapL2promotion, CUtensorMapFloatOOBfill);

extern "C" void kernel_launch(void* const* d_in, const int* in_sizes, int n_in, void* d_out, int out_size) {
    const __nv_bfloat16* x = (const __nv_bfloat16*)d_in[0];
    const int* qw = (const int*)d_in[1];
    const __nv_bfloat16* cb = (const __nv_bfloat16*)d_in[2];
    const __nv_bfloat16* absmax = (const __nv_bfloat16*)d_in[3];
    static EncodeFn encode = nullptr;
    static void *wimg = nullptr, *gflag = nullptr;
    if (!encode) {
        cudaGetSymbolAddress(&wimg, g_wimg);
        cudaGetSymbolAddress(&gflag, g_flag);
        void* fn = nullptr;
        cudaDriverEntryPointQueryResult qr;
        cudaGetDriverEntryPoint("cuTensorMapEncodeTiled", &fn, cudaEnableDefault, &qr);
        encode = (EncodeFn)fn;
        cudaFuncSetAttribute(nf4_gemm_kernel, cudaFuncAttributeMaxDynamicSharedMemorySize, SMEM_BYTES);
    }
    CUtensorMap tmx, tmq, tmo64, tmo32, tmqp, tmx16, tmx64, tmq1;
    {
        cuuint64_t dims[2] = {(cuuint64_t)K_, (cuuint64_t)M_};
        cuuint64_t strides[1] = {(cuuint64_t)K_ * 2};
        cuuint32_t box[2] = {64, 128};
        cuuint32_t es[2] = {1, 1};
        encode(&tmx, CU_TENSOR_MAP_DATA_TYPE_BFLOAT16, 2, (void*)x, dims, strides, box, es, CU_TENSOR_MAP_INTERLEAVE_NONE,
               CU_TENSOR_MAP_SWIZZLE_128B, CU_TENSOR_MAP_L2_PROMOTION_L2_128B, CU_TENSOR_MAP_FLOAT_OOB_FILL_NONE);
        box[1] = 64;
        encode(&tmx64, CU_TENSOR_MAP_DATA_TYPE_BFLOAT16, 2, (void*)x, dims, strides, box, es, CU_TENSOR_MAP_INTERLEAVE_NONE,
               CU_TENSOR_MAP_SWIZZLE_128B, CU_TENSOR_MAP_L2_PROMOTION_L2_128B, CU_TENSOR_MAP_FLOAT_OOB_FILL_NONE);
        box[1] = 16;
        encode(&tmx16, CU_TENSOR_MAP_DATA_TYPE_BFLOAT16, 2, (void*)x, dims, strides, box, es, CU_TENSOR_MAP_INTERLEAVE_NONE,
               CU_TENSOR_MAP_SWIZZLE_128B, CU_TENSOR_MAP_L2_PROMOTION_L2_128B, CU_TENSOR_MAP_FLOAT_OOB_FILL_NONE);
    }
    {
        cuuint64_t dims[5] = {32, 8, (cuuint64_t)(N_ / 32), 2, (cuuint64_t)(K_ / 16)};
        cuuint64_t strides[4] = {(cuuint64_t)N_ * 4, 128, (cuuint64_t)N_ * 4 * 8, (cuuint64_t)N_ * 4 * 16};
        cuuint32_t box[5] = {32, 8, 7, 1, 2};
        cuuint32_t es[5] = {1, 1, 1, 1, 1};
        encode(&tmq, CU_TENSOR_MAP_DATA_TYPE_INT32, 5, (void*)qw, dims, strides, box, es, CU_TENSOR_MAP_INTERLEAVE_NONE,
               CU_TENSOR_MAP_SWIZZLE_128B, CU_TENSOR_MAP_L2_PROMOTION_L2_128B, CU_TENSOR_MAP_FLOAT_OOB_FILL_NONE);
        box[4] = 1;
        encode(&tmq1, CU_TENSOR_MAP_DATA_TYPE_INT32, 5, (void*)qw, dims, strides, box, es, CU_TENSOR_MAP_INTERLEAVE_NONE,
               CU_TENSOR_MAP_SWIZZLE_128B, CU_TENSOR_MAP_L2_PROMOTION_L2_128B, CU_TENSOR_MAP_FLOAT_OOB_FILL_NONE);
        cuuint64_t dims2[2] = {(cuuint64_t)N_, (cuuint64_t)K_};
        cuuint32_t box2[2] = {224, 8};
        encode(&tmqp, CU_TENSOR_MAP_DATA_TYPE_INT32, 2, (void*)qw, dims2, strides, box2, es, CU_TENSOR_MAP_INTERLEAVE_NONE,
               CU_TENSOR_MAP_SWIZZLE_NONE, CU_TENSOR_MAP_L2_PROMOTION_L2_128B, CU_TENSOR_MAP_FLOAT_OOB_FILL_NONE);
    }
    {
        cuuint64_t dims[2] = {(cuuint64_t)N_, (cuuint64_t)M_};
        cuuint64_t strides[1] = {(cuuint64_t)N_ * 2};
        cuuint32_t box[2] = {64, 16};
        cuuint32_t es[2] = {1, 1};
        encode(&tmo64, CU_TENSOR_MAP_DATA_TYPE_BFLOAT16, 2, d_out, dims, strides, box, es, CU_TENSOR_MAP_INTERLEAVE_NONE,
               CU_TENSOR_MAP_SWIZZLE_128B, CU_TENSOR_MAP_L2_PROMOTION_NONE, CU_TENSOR_MAP_FLOAT_OOB_FILL_NONE);
        box[0] = 32;
        encode(&tmo32, CU_TENSOR_MAP_DATA_TYPE_BFLOAT16, 2, d_out, dims, strides, box, es, CU_TENSOR_MAP_INTERLEAVE_NONE,
               CU_TENSOR_MAP_SWIZZLE_64B, CU_TENSOR_MAP_L2_PROMOTION_NONE, CU_TENSOR_MAP_FLOAT_OOB_FILL_NONE);
    }
    nf4_gemm_kernel<<<dim3(2, 64), 256, SMEM_BYTES>>>(qw, cb, absmax, (uint8_t*)wimg, (unsigned*)gflag, (uint8_t*)d_out, tmx, tmq, tmo64, tmo32, tmqp, tmx16, tmx64, tmq1);
}
```
